```python
import torch

def _softmax(x, axis=-1):
    return torch.softmax(x, dim=axis)
def _gelu(x):
    return torch.nn.functional.gelu(x, approximate="tanh")
def _silu(x):
    return torch.nn.functional.silu(x)
def _sigmoid(x):
    return torch.sigmoid(x)
def _layernorm(x, axis=-1, eps=1e-5):
    m = x.mean(dim=axis, keepdim=True)
    v = x.var(dim=axis, keepdim=True, unbiased=False)
    return (x - m) / torch.sqrt(v + eps)
def _scatter_add(tgt, idx, src, axis=0):
    return tgt.clone().index_add_(axis, idx, src)
def _segment_sum(src, seg, n):
    out = torch.zeros((n,) + src.shape[1:], dtype=src.dtype)
    return out.index_add_(0, seg, src)
def _pad(x, pw):
    flat = tuple(v for pair in reversed(pw) for v in pair)
    return torch.nn.functional.pad(x, flat)

kernel_name = 'concat_heads__compressed_kv_cla__sliding_local_dilated__prompt'

def setup_inputs():

    _w = (lambda a: (lambda t: t.to(torch.bfloat16) if t.is_floating_point() else t)(torch.as_tensor(a)))
    def _A_setup():
        B, H, Sq, Sk, D, M = 1, 32, 2048, 2048, 128, 1024
        Dc = 4 * D
        return {
            "x": _w((lambda *s: torch.randn(*s, dtype=torch.bfloat16) * 0.2)(B, Sq, M)),
            "c_kv": _w((lambda *s: torch.randn(*s, dtype=torch.bfloat16) * 1.6)(B, Sk, Dc)),
            "w_q": _w((lambda *s: torch.randn(*s, dtype=torch.bfloat16) * 3.2)(M, H, D) * (M ** -0.5)),
            "w_uk": _w((lambda *s: torch.randn(*s, dtype=torch.bfloat16) * 3.2)(Dc, H, D) * (Dc ** -0.5)),
            "w_uv": _w((lambda *s: torch.randn(*s, dtype=torch.bfloat16) * 1.6)(Dc, H, D) * (Dc ** -0.5)),
            "w_o": _w((lambda *s: torch.randn(*s, dtype=torch.bfloat16) * 1.6)(H, D, M) * ((H * D) ** -0.5)),
        }
    _A_in = _A_setup()

    def _B_setup():
        B, S, D = 1, 2048, 1024
        return {
            "x": _w((lambda *s: torch.randn(*s, dtype=torch.bfloat16) * 0.2)(B, S, D)),
            "wqkv": _w((lambda *s: torch.randn(*s, dtype=torch.bfloat16) * 0.2)(D, 3 * D)),
            "wo": _w((lambda *s: torch.randn(*s, dtype=torch.bfloat16) * 0.05)(D, D)),
        }
    _B_in = _B_setup()

    return {
        "A_x": _A_in["x"],
        "A_c_kv": _A_in["c_kv"],
        "A_w_q": _A_in["w_q"],
        "A_w_uk": _A_in["w_uk"],
        "A_w_uv": _A_in["w_uv"],
        "A_w_o": _A_in["w_o"],
        "B_x": _B_in["x"],
        "B_wqkv": _B_in["wqkv"],
        "B_wo": _B_in["wo"],
    }

def reference(A_x, A_c_kv, A_w_q, A_w_uk, A_w_uv, A_w_o, B_x, B_wqkv, B_wo):
    def _A_ref(x, c_kv, w_q, w_uk, w_uv, w_o):
        B, Sq, M = x.shape[0], x.shape[1], x.shape[2]
        Sk = c_kv.shape[1]
        H, D = w_q.shape[1], w_q.shape[2]
        q = torch.einsum("bqm,mhd->bhqd", x, w_q)
        k = torch.einsum("bkc,chd->bhkd", c_kv, w_uk)
        v = torch.einsum("bkc,chd->bhkd", c_kv, w_uv)
        scores = torch.einsum("bhqd,bhkd->bhqk", q, k) * (D ** -0.5)
        off = Sk - Sq
        qi = torch.arange(Sq)[:, None]
        kj = torch.arange(Sk)[None, :]
        cmask = kj <= (qi + off)
        scores = torch.where(cmask[None, None], scores, -1e9)
        p = _softmax(scores, axis=-1)
        ctx = torch.einsum("bhqk,bhkd->bhqd", p, v)
        return torch.einsum("bhqd,hdm->bqm", ctx, w_o)

    def _B_ref(x, wqkv, wo):
        B, S, D = x.shape
        H = 32; Dh = D // H
        W, dil = 8, 2
        qkv = (lambda x, *d: x.permute(*d))((x @ wqkv).reshape(B, S, 3, H, Dh), 2, 0, 3, 1, 4)
        q, k, v = qkv[0], qkv[1], qkv[2]
        scale = Dh ** -0.5
        pos = torch.arange(S)
        off = torch.arange(W) * dil
        idx = pos[:, None] - off[None, :]
        mask = idx >= 0
        idx_c = torch.where(mask, idx, 0).reshape(-1)
        kg = k[:, :, idx_c, :].reshape(B, H, S, W, Dh)
        vg = v[:, :, idx_c, :].reshape(B, H, S, W, Dh)
        logits = torch.einsum("bhsd,bhswd->bhsw", q, kg) * scale
        logits = torch.where(mask[None, None, :, :], logits, -1e9)
        attn = _softmax(logits, axis=-1)
        o = torch.einsum("bhsw,bhswd->bhsd", attn, vg)
        return (lambda x, *d: x.permute(*d))(o, 0, 2, 1, 3).reshape(B, S, D) @ wo

    a = _A_ref(A_x, A_c_kv, A_w_q, A_w_uk, A_w_uv, A_w_o)
    b = _B_ref(B_x, B_wqkv, B_wo)
    return torch.concatenate([a, b], axis=-1)
```

```cpp
#include <cuda_runtime.h>
#include <cuda_bf16.h>
#include <cuda.h>
#include <stdint.h>
#include <string.h>

namespace {

typedef __nv_bfloat16 bf16;

constexpr int SEQ = 2048;
constexpr int NHEAD = 32;
constexpr int HD = 128;
constexpr int DM = 1024;
constexpr int DC = 512;
constexpr int HHD = NHEAD * HD;

__device__ __align__(1024) bf16 g_q[SEQ * HHD];
__device__ __align__(1024) bf16 g_k[SEQ * HHD];
__device__ __align__(1024) bf16 g_v[SEQ * HHD];
__device__ __align__(1024) bf16 g_ctx[SEQ * HHD];
__device__ __align__(1024) bf16 g_qkvb[SEQ * 3 * DM];
__device__ __align__(1024) bf16 g_ob[SEQ * DM];
constexpr int CNT_QKV = 0, CNT_CTX = 16, CNT_QKVB = 32, CNT_DONE = 33, CNT_QUEUE = 34, CNT_OB = 35, CNT_N = 39;
__device__ uint32_t g_cnt[CNT_N * 8];

__device__ __forceinline__ uint32_t smem_u32(const void* p) {
  return static_cast<uint32_t>(__cvta_generic_to_shared(p));
}
__device__ __forceinline__ void mbar_init(uint32_t bar, uint32_t count) {
  asm volatile("mbarrier.init.shared::cta.b64 [%0], %1;" ::"r"(bar), "r"(count) : "memory");
}
__device__ __forceinline__ void mbar_expect_tx(uint32_t bar, uint32_t bytes) {
  asm volatile("mbarrier.arrive.expect_tx.shared::cta.b64 _, [%0], %1;" ::"r"(bar), "r"(bytes) : "memory");
}
__device__ __forceinline__ void mbar_arrive(uint32_t bar) {
  asm volatile("mbarrier.arrive.shared::cta.b64 _, [%0];" ::"r"(bar) : "memory");
}
__device__ __forceinline__ void mbar_arrive_if(uint32_t bar, bool on) {
  asm volatile("{\n.reg .pred p;\nsetp.ne.b32 p, %1, 0;\n@p mbarrier.arrive.shared::cta.b64 _, [%0];\n}" ::"r"(bar),
               "r"((int)on)
               : "memory");
}
__device__ __forceinline__ void mbar_arrive_cluster_if(uint32_t bar, uint32_t cta, bool on) {
  asm volatile(
      "{\n.reg .b32 ra;\n.reg .pred p;\nsetp.ne.b32 p, %2, 0;\nmapa.shared::cluster.u32 ra, %0, %1;\n"
      "@p mbarrier.arrive.shared::cluster.b64 _, [ra];\n}" ::"r"(bar),
      "r"(cta), "r"((int)on)
      : "memory");
}
__device__ __forceinline__ void mbar_arrive_cluster(uint32_t bar, uint32_t cta) {
  asm volatile(
      "{\n.reg .b32 ra;\nmapa.shared::cluster.u32 ra, %0, %1;\n"
      "mbarrier.arrive.shared::cluster.b64 _, [ra];\n}" ::"r"(bar),
      "r"(cta)
      : "memory");
}
__device__ __forceinline__ bool mbar_try_wait(uint32_t bar, uint32_t parity) {
  uint32_t ok;
  asm volatile(
      "{\n.reg .pred p;\nmbarrier.try_wait.parity.shared::cta.b64 p, [%1], %2;\nselp.u32 %0, 1, 0, p;\n}"
      : "=r"(ok)
      : "r"(bar), "r"(parity)
      : "memory");
  return ok != 0;
}
__device__ __forceinline__ bool mbar_test(uint32_t bar, uint32_t parity) {
  uint32_t ok;
  asm volatile(
      "{\n.reg .pred p;\nmbarrier.test_wait.parity.shared::cta.b64 p, [%1], %2;\nselp.u32 %0, 1, 0, p;\n}"
      : "=r"(ok)
      : "r"(bar), "r"(parity)
      : "memory");
  return ok != 0;
}
#define DBG(i, v)
__device__ __forceinline__ void mbar_wait(uint32_t bar, uint32_t parity) {
  asm volatile(
      "{\n.reg .pred p;\n.reg .u32 t;\n"
      "mbarrier.try_wait.parity.shared::cta.b64 p, [%0], %1;\n"
      "@p bra DONE;\n"
      "mov.u32 t, 0x100000;\n"
      "LAB_WAIT:\n"
      "mbarrier.try_wait.parity.shared::cta.b64 p, [%0], %1;\n"
      "@p bra DONE;\n"
      "sub.u32 t, t, 1;\n"
      "setp.ne.u32 p, t, 0;\n"
      "@p bra LAB_WAIT;\n"
      "trap;\n"
      "DONE:\n}" ::"r"(bar),
      "r"(parity)
      : "memory");
}
constexpr uint64_t EV_NORMAL = 0x1000000000000000ull, EV_FIRST = 0x12F0000000000000ull;
__device__ __forceinline__ void tma_load_3d(uint32_t dst, const CUtensorMap* map, int c0, int c1, int c2,
                                            uint32_t bar, uint64_t hint) {
  asm volatile(
      "cp.async.bulk.tensor.3d.shared::cluster.global.mbarrier::complete_tx::bytes.L2::cache_hint [%0], [%1, {%3, %4, %5}], [%2], %6;" ::"r"(dst),
      "l"(map), "r"(bar), "r"(c0), "r"(c1), "r"(c2), "l"(hint)
      : "memory");
}
__device__ __forceinline__ void tma_load_3d_mc(uint32_t dst, const CUtensorMap* map, int c0, int c1, int c2,
                                               uint32_t bar, uint16_t mask, uint64_t hint) {
  asm volatile(
      "cp.async.bulk.tensor.3d.shared::cluster.global.mbarrier::complete_tx::bytes.multicast::cluster.L2::cache_hint [%0], [%1, {%3, %4, %5}], [%2], %6, %7;" ::"r"(dst),
      "l"(map), "r"(bar), "r"(c0), "r"(c1), "r"(c2), "h"(mask), "l"(hint)
      : "memory");
}
__device__ __forceinline__ void tma_prefetch_3d(const CUtensorMap* map, int c0, int c1, int c2) {
  asm volatile("cp.async.bulk.prefetch.tensor.3d.L2.global.tile [%0, {%1, %2, %3}];" ::"l"(map), "r"(c0), "r"(c1), "r"(c2)
               : "memory");
}
__device__ __forceinline__ void tma_store_3d(const CUtensorMap* map, uint32_t src, int c0, int c1, int c2, uint64_t hint) {
  asm volatile("cp.async.bulk.tensor.3d.global.shared::cta.bulk_group.L2::cache_hint [%0, {%2, %3, %4}], [%1], %5;" ::"l"(map),
               "r"(src), "r"(c0), "r"(c1), "r"(c2), "l"(hint)
               : "memory");
}
__device__ __forceinline__ void bulk_commit() { asm volatile("cp.async.bulk.commit_group;" ::: "memory"); }
template <int N>
__device__ __forceinline__ void bulk_wait_read() {
  asm volatile("cp.async.bulk.wait_group.read %0;" ::"n"(N) : "memory");
}
template <int N>
__device__ __forceinline__ void bulk_wait() {
  asm volatile("cp.async.bulk.wait_group %0;" ::"n"(N) : "memory");
}
__device__ __forceinline__ void fence_proxy_async_smem() {
  asm volatile("fence.proxy.async.shared::cta;" ::: "memory");
}
__device__ __forceinline__ void prefetch_tmap(const CUtensorMap* map) {
  asm volatile("prefetch.tensormap [%0];" ::"l"(map) : "memory");
}
__device__ __forceinline__ void cluster_sync_all() {
  asm volatile("barrier.cluster.arrive.relaxed.aligned;\nbarrier.cluster.wait.acquire.aligned;" ::: "memory");
}
__device__ __forceinline__ uint32_t cluster_ctarank() {
  uint32_t r;
  asm volatile("mov.u32 %0, %%cluster_ctarank;" : "=r"(r));
  return r;
}
__device__ __forceinline__ bool elect_one() {
  uint32_t pred;
  asm volatile("{\n.reg .pred P;\nelect.sync _|P, 0xffffffff;\nselp.b32 %0, 1, 0, P;\n}" : "=r"(pred));
  return pred != 0;
}
__device__ __forceinline__ void named_bar_sync(int id, int n) {
  asm volatile("bar.sync %0, %1;" ::"r"(id), "r"(n) : "memory");
}
__device__ __forceinline__ void named_bar_arrive(int id, int n) {
  asm volatile("bar.arrive %0, %1;" ::"r"(id), "r"(n) : "memory");
}
__device__ __forceinline__ void named_bar_sync_if(int id, int n, bool on) {
  asm volatile("{\n.reg .pred p;\nsetp.ne.b32 p, %2, 0;\n@p bar.sync %0, %1;\n}" ::"r"(id), "r"(n), "r"((int)on) : "memory");
}
__device__ __forceinline__ void named_bar_arrive_if(int id, int n, bool on) {
  asm volatile("{\n.reg .pred p;\nsetp.ne.b32 p, %2, 0;\n@p bar.arrive %0, %1;\n}" ::"r"(id), "r"(n), "r"((int)on) : "memory");
}
template <int N>
__device__ __forceinline__ void reg_alloc() {
  asm volatile("setmaxnreg.inc.sync.aligned.u32 %0;" ::"n"(N));
}
template <int N>
__device__ __forceinline__ void reg_dealloc() {
  asm volatile("setmaxnreg.dec.sync.aligned.u32 %0;" ::"n"(N));
}
__device__ __forceinline__ void wgmma_fence() { asm volatile("wgmma.fence.sync.aligned;" ::: "memory"); }
__device__ __forceinline__ void wgmma_commit() { asm volatile("wgmma.commit_group.sync.aligned;" ::: "memory"); }
template <int N>
__device__ __forceinline__ void wgmma_wait() {
  asm volatile("wgmma.wait_group.sync.aligned %0;" ::"n"(N) : "memory");
}
template <int N>
__device__ __forceinline__ void fence_regs(float (&d)[N]) {
#pragma unroll
  for (int i = 0; i < N; i++) asm volatile("" : "+f"(d[i])::"memory");
}
__device__ __forceinline__ void fence_regs(uint32_t (&d)[32]) {
#pragma unroll
  for (int i = 0; i < 16; i++) asm volatile("" : "+r"(d[i])::"memory");
}
template <int N>
__device__ __forceinline__ void undef_regs(float (&d)[N]) {
#pragma unroll
  for (int i = 0; i < N; i++) d[i] = 0.f;
}
template <int N>
__device__ __forceinline__ void undef_regs(uint32_t (&d)[N]) {
#pragma unroll
  for (int i = 0; i < N; i++) d[i] = 0u;
}
__device__ __forceinline__ void sched_fence(float x) {
  asm volatile("{\n.reg .pred p;\nsetp.lt.f32 p, %0, 0f00000000;\n@p trap;\n}" ::"f"(x) : "memory");
}
__device__ __forceinline__ uint32_t pack_bf16(float lo, float hi) {
  uint32_t r;
  asm("cvt.rn.bf16x2.f32 %0, %1, %2;" : "=r"(r) : "f"(hi), "f"(lo));
  return r;
}
__device__ __forceinline__ void stmatrix_x4(uint32_t addr, uint32_t r0, uint32_t r1, uint32_t r2, uint32_t r3) {
  asm volatile("stmatrix.sync.aligned.m8n8.x4.shared.b16 [%0], {%1, %2, %3, %4};" ::"r"(addr), "r"(r0), "r"(r1),
               "r"(r2), "r"(r3)
               : "memory");
}
__device__ __forceinline__ void stmatrix_x4_p(uint32_t addr, uint32_t r0, uint32_t r1, uint32_t r2, uint32_t r3,
                                              bool on) {
  asm volatile("{\n.reg .pred p;\nsetp.ne.b32 p, %5, 0;\n@p stmatrix.sync.aligned.m8n8.x4.shared.b16 [%0], {%1, %2, %3, %4};\n}" ::"r"(addr),
               "r"(r0), "r"(r1), "r"(r2), "r"(r3), "r"((int)on)
               : "memory");
}
__device__ __forceinline__ float ex2(float x) {
  float y;
  asm("ex2.approx.ftz.f32 %0, %1;" : "=f"(y) : "f"(x));
  return y;
}
__device__ __forceinline__ float rcp(float x) {
  float y;
  asm("rcp.approx.ftz.f32 %0, %1;" : "=f"(y) : "f"(x));
  return y;
}
#define BBV 0
__device__ __forceinline__ float ex2v(float x) {
  float y;
  asm volatile("ex2.approx.ftz.f32 %0, %1;" : "=f"(y) : "f"(x));
  return y;
}
__device__ __forceinline__ void ex2_over(float& y, float x, uint32_t k) {
  asm volatile("{\n.reg .pred p;\nsetp.ne.u32 p, %2, 0x7fffffff;\n@p ex2.approx.ftz.f32 %0, %1;\n}" : "+f"(y) : "f"(x), "r"(k));
}
__device__ __forceinline__ float addv(float a, float b) {
  float y;
  asm volatile("add.f32 %0, %1, %2;" : "=f"(y) : "f"(a), "f"(b));
  return y;
}
__device__ __forceinline__ uint32_t packv(float lo, float hi) {
  uint32_t r;
  asm volatile("cvt.rn.bf16x2.f32 %0, %1, %2;" : "=r"(r) : "f"(hi), "f"(lo));
  return r;
}
__device__ __forceinline__ float maskv(float x, int lim, int col) {
  float y;
  asm volatile("{\n.reg .pred p;\nsetp.ge.s32 p, %2, %3;\nselp.f32 %0, %1, 0fFF800000, p;\n}" : "=f"(y) : "f"(x), "r"(lim), "r"(col));
  return y;
}
__device__ __forceinline__ void bb_split(uint32_t x, uint32_t k) {
  asm volatile("{\n.reg .pred p;\nsetp.eq.u32 p, %0, %1;\n@p trap;\n}" ::"r"(x), "r"(0x7fffff00u + k));
}
__device__ __forceinline__ void mbar_arrive_elect(uint32_t bar, bool on) {
  asm volatile("{\n.reg .pred p, q;\nelect.sync _|q, 0xffffffff;\nsetp.ne.and.b32 p, %1, 0, q;\n@p mbarrier.arrive.shared::cta.b64 _, [%0];\n}" ::"r"(bar),
               "r"((int)on)
               : "memory");
}
__device__ __forceinline__ float mbar_test2(uint32_t bar0, uint32_t par0, uint32_t bar1, uint32_t par1) {
  float f;
  asm volatile(
      "{\n.reg .pred p, q;\nmbarrier.test_wait.parity.shared::cta.b64 p, [%1], %2;\n"
      "mbarrier.test_wait.parity.shared::cta.b64 q, [%3], %4;\nand.pred p, p, q;\nselp.f32 %0, 0f00000000, 0f80000000, p;\n}"
      : "=f"(f)
      : "r"(bar0), "r"(par0), "r"(bar1), "r"(par1)
      : "memory");
  return f;
}
__device__ __forceinline__ void mbar_wait_rest(uint32_t bar, uint32_t parity, bool ok) {
  asm volatile(
      "{\n.reg .pred p;\n.reg .u32 t;\n"
      "setp.ne.b32 p, %2, 0;\n"
      "@p bra DONE;\n"
      "mov.u32 t, 0x100000;\n"
      "LAB_WAIT:\n"
      "mbarrier.try_wait.parity.shared::cta.b64 p, [%0], %1;\n"
      "@p bra DONE;\n"
      "sub.u32 t, t, 1;\n"
      "setp.ne.u32 p, t, 0;\n"
      "@p bra LAB_WAIT;\n"
      "trap;\n"
      "DONE:\n}" ::"r"(bar),
      "r"(parity), "r"((int)ok)
      : "memory");
}
__device__ __forceinline__ void cnt_signal(int idx, uint32_t inc = 1) {
  asm volatile("red.release.gpu.global.add.u32 [%0], %1;" ::"l"(g_cnt + idx * 8), "r"(inc) : "memory");
}
__device__ __forceinline__ uint32_t cnt_next(int idx) {
  uint32_t v;
  asm volatile("atom.relaxed.gpu.global.add.u32 %0, [%1], 1;" : "=r"(v) : "l"(g_cnt + idx * 8) : "memory");
  return v;
}
__device__ __forceinline__ uint32_t cnt_peek(int idx) {
  uint32_t v;
  asm volatile("ld.acquire.gpu.global.u32 %0, [%1];" : "=r"(v) : "l"(g_cnt + idx * 8) : "memory");
  return v;
}
__device__ __forceinline__ void cnt_wait(int idx, uint32_t target) {
  asm volatile(
      "{\n.reg .pred p;\n.reg .u32 v, t0, t1;\n"
      "ld.acquire.gpu.global.u32 v, [%0];\n"
      "setp.ge.u32 p, v, %1;\n"
      "@p bra DONE;\n"
      "mov.u32 t0, %%clock;\n"
      "LAB_WAIT:\n"
      "nanosleep.u32 100;\n"
      "ld.acquire.gpu.global.u32 v, [%0];\n"
      "setp.ge.u32 p, v, %1;\n"
      "@p bra DONE;\n"
      "mov.u32 t1, %%clock;\n"
      "sub.u32 t1, t1, t0;\n"
      "setp.lt.u32 p, t1, 0x80000000;\n"
      "@p bra LAB_WAIT;\n"
      "trap;\n"
      "DONE:\n}" ::"l"(g_cnt + idx * 8),
      "r"(target)
      : "memory");
}
__device__ __forceinline__ void cnt_wait_bit(int idx, uint32_t bit, uint32_t& v) {
  asm volatile(
      "{\n.reg .pred p;\n.reg .u32 x, t0, t1;\n"
      "and.b32 x, %0, %2;\n"
      "setp.ne.u32 p, x, 0;\n"
      "@p bra DONE;\n"
      "mov.u32 t0, %%clock;\n"
      "LAB_WAIT:\n"
      "ld.acquire.gpu.global.u32 %0, [%1];\n"
      "and.b32 x, %0, %2;\n"
      "setp.ne.u32 p, x, 0;\n"
      "@p bra DONE;\n"
      "nanosleep.u32 64;\n"
      "mov.u32 t1, %%clock;\n"
      "sub.u32 t1, t1, t0;\n"
      "setp.lt.u32 p, t1, 0x80000000;\n"
      "@p bra LAB_WAIT;\n"
      "trap;\n"
      "DONE:\n}" : "+r"(v) : "l"(g_cnt + idx * 8),
      "r"(bit)
      : "memory");
}
__device__ __forceinline__ bool cnt_done(uint32_t total) {
  uint32_t old;
  asm volatile("atom.acq_rel.gpu.global.add.u32 %0, [%1], 1;" : "=r"(old) : "l"(g_cnt + CNT_DONE * 8) : "memory");
  return old == total - 1;
}
__device__ __forceinline__ void cnt_rearm() {
#pragma unroll
  for (int i = 0; i < CNT_N; i++) g_cnt[i * 8] = 0;
}
__device__ __forceinline__ void fence_proxy_async_global() { asm volatile("fence.proxy.async.global;" ::: "memory"); }
__device__ __forceinline__ void mma_16816(float (&c)[4], uint32_t a0, uint32_t a1, uint32_t a2, uint32_t a3,
                                          uint32_t b0, uint32_t b1) {
  asm("mma.sync.aligned.m16n8k16.row.col.f32.bf16.bf16.f32 {%0, %1, %2, %3}, {%4, %5, %6, %7}, {%8, %9}, {%0, %1, %2, %3};"
      : "+f"(c[0]), "+f"(c[1]), "+f"(c[2]), "+f"(c[3])
      : "r"(a0), "r"(a1), "r"(a2), "r"(a3), "r"(b0), "r"(b1));
}
__device__ __forceinline__ void mma_1688(float (&c)[4], uint32_t a0, uint32_t a1, uint32_t b0) {
  asm("mma.sync.aligned.m16n8k8.row.col.f32.bf16.bf16.f32 {%0, %1, %2, %3}, {%4, %5}, {%6}, {%0, %1, %2, %3};"
      : "+f"(c[0]), "+f"(c[1]), "+f"(c[2]), "+f"(c[3])
      : "r"(a0), "r"(a1), "r"(b0));
}
__device__ __forceinline__ uint32_t movm_t(uint32_t a) {
  uint32_t d;
  asm("movmatrix.sync.aligned.m8n8.trans.b16 %0, %1;" : "=r"(d) : "r"(a));
  return d;
}
__device__ __forceinline__ uint4 ldg128(const bf16* p) {
  uint4 v;
  asm volatile("ld.global.v4.u32 {%0, %1, %2, %3}, [%4];" : "=r"(v.x), "=r"(v.y), "=r"(v.z), "=r"(v.w) : "l"(p) : "memory");
  return v;
}
#define TL(role, code)
#define TL0(code)
#define TL_DECL
#define TR_DECL
#define TR(code)
#define TRI(id, code)
#define TW_DECL
#define TW(w, stmt) stmt
#define TW_FLUSH()
#define TW_END()

__device__ __forceinline__ uint32_t make_desc(uint32_t addr, uint32_t lbo_bytes) {
  return (addr >> 4) + ((lbo_bytes >> 4) << 16);
}

__device__ __forceinline__ void wgmma_ss_n256_tb(float (&d)[128], uint32_t da, uint32_t db, int scale_d) {
  asm volatile("{\n.reg .pred p;\n.reg .b64 a, b;\nsetp.ne.b32 p, %130, 0;\nmov.b64 a, {%128, 0x40000040};\nmov.b64 b, {%129, 0x40000040};\n"
    "wgmma.mma_async.sync.aligned.m64n256k16.f32.bf16.bf16 {%0, %1, %2, %3, %4, %5, %6, %7, %8, %9, %10, %11, %12, %13, %14, %15, %16, %17, %18, %19, %20, %21, %22, %23, %24, %25, %26, %27, %28, %29, %30, %31, %32, %33, %34, %35, %36, %37, %38, %39, %40, %41, %42, %43, %44, %45, %46, %47, %48, %49, %50, %51, %52, %53, %54, %55, %56, %57, %58, %59, %60, %61, %62, %63, %64, %65, %66, %67, %68, %69, %70, %71, %72, %73, %74, %75, %76, %77, %78, %79, %80, %81, %82, %83, %84, %85, %86, %87, %88, %89, %90, %91, %92, %93, %94, %95, %96, %97, %98, %99, %100, %101, %102, %103, %104, %105, %106, %107, %108, %109, %110, %111, %112, %113, %114, %115, %116, %117, %118, %119, %120, %121, %122, %123, %124, %125, %126, %127}, a, b, p, 1, 1, 0, 1;\n}\n"
    : "+f"(d[0]), "+f"(d[1]), "+f"(d[2]), "+f"(d[3]), "+f"(d[4]), "+f"(d[5]), "+f"(d[6]), "+f"(d[7]), "+f"(d[8]), "+f"(d[9]), "+f"(d[10]), "+f"(d[11]), "+f"(d[12]), "+f"(d[13]), "+f"(d[14]), "+f"(d[15]), "+f"(d[16]), "+f"(d[17]), "+f"(d[18]), "+f"(d[19]), "+f"(d[20]), "+f"(d[21]), "+f"(d[22]), "+f"(d[23]), "+f"(d[24]), "+f"(d[25]), "+f"(d[26]), "+f"(d[27]), "+f"(d[28]), "+f"(d[29]), "+f"(d[30]), "+f"(d[31]), "+f"(d[32]), "+f"(d[33]), "+f"(d[34]), "+f"(d[35]), "+f"(d[36]), "+f"(d[37]), "+f"(d[38]), "+f"(d[39]), "+f"(d[40]), "+f"(d[41]), "+f"(d[42]), "+f"(d[43]), "+f"(d[44]), "+f"(d[45]), "+f"(d[46]), "+f"(d[47]), "+f"(d[48]), "+f"(d[49]), "+f"(d[50]), "+f"(d[51]), "+f"(d[52]), "+f"(d[53]), "+f"(d[54]), "+f"(d[55]), "+f"(d[56]), "+f"(d[57]), "+f"(d[58]), "+f"(d[59]), "+f"(d[60]), "+f"(d[61]), "+f"(d[62]), "+f"(d[63]), "+f"(d[64]), "+f"(d[65]), "+f"(d[66]), "+f"(d[67]), "+f"(d[68]), "+f"(d[69]), "+f"(d[70]), "+f"(d[71]), "+f"(d[72]), "+f"(d[73]), "+f"(d[74]), "+f"(d[75]), "+f"(d[76]), "+f"(d[77]), "+f"(d[78]), "+f"(d[79]), "+f"(d[80]), "+f"(d[81]), "+f"(d[82]), "+f"(d[83]), "+f"(d[84]), "+f"(d[85]), "+f"(d[86]), "+f"(d[87]), "+f"(d[88]), "+f"(d[89]), "+f"(d[90]), "+f"(d[91]), "+f"(d[92]), "+f"(d[93]), "+f"(d[94]), "+f"(d[95]), "+f"(d[96]), "+f"(d[97]), "+f"(d[98]), "+f"(d[99]), "+f"(d[100]), "+f"(d[101]), "+f"(d[102]), "+f"(d[103]), "+f"(d[104]), "+f"(d[105]), "+f"(d[106]), "+f"(d[107]), "+f"(d[108]), "+f"(d[109]), "+f"(d[110]), "+f"(d[111]), "+f"(d[112]), "+f"(d[113]), "+f"(d[114]), "+f"(d[115]), "+f"(d[116]), "+f"(d[117]), "+f"(d[118]), "+f"(d[119]), "+f"(d[120]), "+f"(d[121]), "+f"(d[122]), "+f"(d[123]), "+f"(d[124]), "+f"(d[125]), "+f"(d[126]), "+f"(d[127])
    : "r"(da), "r"(db), "r"(scale_d));
}
__device__ __forceinline__ void wgmma_ss_n128(float (&d)[64], uint32_t da, uint32_t db, int scale_d) {
  asm volatile("{\n.reg .pred p;\n.reg .b64 a, b;\nsetp.ne.b32 p, %66, 0;\nmov.b64 a, {%64, 0x40000040};\nmov.b64 b, {%65, 0x40000040};\n"
    "wgmma.mma_async.sync.aligned.m64n128k16.f32.bf16.bf16 {%0, %1, %2, %3, %4, %5, %6, %7, %8, %9, %10, %11, %12, %13, %14, %15, %16, %17, %18, %19, %20, %21, %22, %23, %24, %25, %26, %27, %28, %29, %30, %31, %32, %33, %34, %35, %36, %37, %38, %39, %40, %41, %42, %43, %44, %45, %46, %47, %48, %49, %50, %51, %52, %53, %54, %55, %56, %57, %58, %59, %60, %61, %62, %63}, a, b, p, 1, 1, 0, 0;\n}\n"
    : "+f"(d[0]), "+f"(d[1]), "+f"(d[2]), "+f"(d[3]), "+f"(d[4]), "+f"(d[5]), "+f"(d[6]), "+f"(d[7]), "+f"(d[8]), "+f"(d[9]), "+f"(d[10]), "+f"(d[11]), "+f"(d[12]), "+f"(d[13]), "+f"(d[14]), "+f"(d[15]), "+f"(d[16]), "+f"(d[17]), "+f"(d[18]), "+f"(d[19]), "+f"(d[20]), "+f"(d[21]), "+f"(d[22]), "+f"(d[23]), "+f"(d[24]), "+f"(d[25]), "+f"(d[26]), "+f"(d[27]), "+f"(d[28]), "+f"(d[29]), "+f"(d[30]), "+f"(d[31]), "+f"(d[32]), "+f"(d[33]), "+f"(d[34]), "+f"(d[35]), "+f"(d[36]), "+f"(d[37]), "+f"(d[38]), "+f"(d[39]), "+f"(d[40]), "+f"(d[41]), "+f"(d[42]), "+f"(d[43]), "+f"(d[44]), "+f"(d[45]), "+f"(d[46]), "+f"(d[47]), "+f"(d[48]), "+f"(d[49]), "+f"(d[50]), "+f"(d[51]), "+f"(d[52]), "+f"(d[53]), "+f"(d[54]), "+f"(d[55]), "+f"(d[56]), "+f"(d[57]), "+f"(d[58]), "+f"(d[59]), "+f"(d[60]), "+f"(d[61]), "+f"(d[62]), "+f"(d[63])
    : "r"(da), "r"(db), "r"(scale_d));
}
__device__ __forceinline__ void wgmma_ss_n64(float (&d)[32], uint32_t da, uint32_t db, int scale_d) {
  asm volatile("{\n.reg .pred p;\n.reg .b64 a, b;\nsetp.ne.b32 p, %34, 0;\nmov.b64 a, {%32, 0x40000040};\nmov.b64 b, {%33, 0x40000040};\n"
    "wgmma.mma_async.sync.aligned.m64n64k16.f32.bf16.bf16 {%0, %1, %2, %3, %4, %5, %6, %7, %8, %9, %10, %11, %12, %13, %14, %15, %16, %17, %18, %19, %20, %21, %22, %23, %24, %25, %26, %27, %28, %29, %30, %31}, a, b, p, 1, 1, 0, 0;\n}\n"
    : "+f"(d[0]), "+f"(d[1]), "+f"(d[2]), "+f"(d[3]), "+f"(d[4]), "+f"(d[5]), "+f"(d[6]), "+f"(d[7]), "+f"(d[8]), "+f"(d[9]), "+f"(d[10]), "+f"(d[11]), "+f"(d[12]), "+f"(d[13]), "+f"(d[14]), "+f"(d[15]), "+f"(d[16]), "+f"(d[17]), "+f"(d[18]), "+f"(d[19]), "+f"(d[20]), "+f"(d[21]), "+f"(d[22]), "+f"(d[23]), "+f"(d[24]), "+f"(d[25]), "+f"(d[26]), "+f"(d[27]), "+f"(d[28]), "+f"(d[29]), "+f"(d[30]), "+f"(d[31])
    : "r"(da), "r"(db), "r"(scale_d));
}
__device__ __forceinline__ void wgmma_rs_n128_tb(float (&d)[64], uint32_t a0, uint32_t a1, uint32_t a2, uint32_t a3, uint32_t db, int scale_d) {
  asm volatile("{\n.reg .pred p;\n.reg .b64 b;\nsetp.ne.b32 p, %69, 0;\nmov.b64 b, {%68, 0x40000040};\n"
    "wgmma.mma_async.sync.aligned.m64n128k16.f32.bf16.bf16 {%0, %1, %2, %3, %4, %5, %6, %7, %8, %9, %10, %11, %12, %13, %14, %15, %16, %17, %18, %19, %20, %21, %22, %23, %24, %25, %26, %27, %28, %29, %30, %31, %32, %33, %34, %35, %36, %37, %38, %39, %40, %41, %42, %43, %44, %45, %46, %47, %48, %49, %50, %51, %52, %53, %54, %55, %56, %57, %58, %59, %60, %61, %62, %63}, {%64, %65, %66, %67}, b, p, 1, 1, 1;\n}\n"
    : "+f"(d[0]), "+f"(d[1]), "+f"(d[2]), "+f"(d[3]), "+f"(d[4]), "+f"(d[5]), "+f"(d[6]), "+f"(d[7]), "+f"(d[8]), "+f"(d[9]), "+f"(d[10]), "+f"(d[11]), "+f"(d[12]), "+f"(d[13]), "+f"(d[14]), "+f"(d[15]), "+f"(d[16]), "+f"(d[17]), "+f"(d[18]), "+f"(d[19]), "+f"(d[20]), "+f"(d[21]), "+f"(d[22]), "+f"(d[23]), "+f"(d[24]), "+f"(d[25]), "+f"(d[26]), "+f"(d[27]), "+f"(d[28]), "+f"(d[29]), "+f"(d[30]), "+f"(d[31]), "+f"(d[32]), "+f"(d[33]), "+f"(d[34]), "+f"(d[35]), "+f"(d[36]), "+f"(d[37]), "+f"(d[38]), "+f"(d[39]), "+f"(d[40]), "+f"(d[41]), "+f"(d[42]), "+f"(d[43]), "+f"(d[44]), "+f"(d[45]), "+f"(d[46]), "+f"(d[47]), "+f"(d[48]), "+f"(d[49]), "+f"(d[50]), "+f"(d[51]), "+f"(d[52]), "+f"(d[53]), "+f"(d[54]), "+f"(d[55]), "+f"(d[56]), "+f"(d[57]), "+f"(d[58]), "+f"(d[59]), "+f"(d[60]), "+f"(d[61]), "+f"(d[62]), "+f"(d[63])
    : "r"(a0), "r"(a1), "r"(a2), "r"(a3), "r"(db), "r"(scale_d));
}
__device__ __forceinline__ void wgmma_ss_n72_init(float (&d)[36], uint32_t da, uint32_t db) {
  asm volatile("{\n.reg .pred p;\n.reg .b64 a, b;\nsetp.ne.b32 p, 0, 0;\nmov.b64 a, {%36, 0x40000040};\nmov.b64 b, {%37, 0x40000040};\n"
    "wgmma.mma_async.sync.aligned.m64n72k16.f32.bf16.bf16 {%0, %1, %2, %3, %4, %5, %6, %7, %8, %9, %10, %11, %12, %13, %14, %15, %16, %17, %18, %19, %20, %21, %22, %23, %24, %25, %26, %27, %28, %29, %30, %31, %32, %33, %34, %35}, a, b, p, 1, 1, 0, 0;\n}\n"
    : "=f"(d[0]), "=f"(d[1]), "=f"(d[2]), "=f"(d[3]), "=f"(d[4]), "=f"(d[5]), "=f"(d[6]), "=f"(d[7]), "=f"(d[8]), "=f"(d[9]), "=f"(d[10]), "=f"(d[11]), "=f"(d[12]), "=f"(d[13]), "=f"(d[14]), "=f"(d[15]), "=f"(d[16]), "=f"(d[17]), "=f"(d[18]), "=f"(d[19]), "=f"(d[20]), "=f"(d[21]), "=f"(d[22]), "=f"(d[23]), "=f"(d[24]), "=f"(d[25]), "=f"(d[26]), "=f"(d[27]), "=f"(d[28]), "=f"(d[29]), "=f"(d[30]), "=f"(d[31]), "=f"(d[32]), "=f"(d[33]), "=f"(d[34]), "=f"(d[35])
    : "r"(da), "r"(db));
}
__device__ __forceinline__ void wgmma_ss_n72(float (&d)[36], uint32_t da, uint32_t db, int scale_d) {
  asm volatile("{\n.reg .pred p;\n.reg .b64 a, b;\nsetp.ne.b32 p, %38, 0;\nmov.b64 a, {%36, 0x40000040};\nmov.b64 b, {%37, 0x40000040};\n"
    "wgmma.mma_async.sync.aligned.m64n72k16.f32.bf16.bf16 {%0, %1, %2, %3, %4, %5, %6, %7, %8, %9, %10, %11, %12, %13, %14, %15, %16, %17, %18, %19, %20, %21, %22, %23, %24, %25, %26, %27, %28, %29, %30, %31, %32, %33, %34, %35}, a, b, p, 1, 1, 0, 0;\n}\n"
    : "+f"(d[0]), "+f"(d[1]), "+f"(d[2]), "+f"(d[3]), "+f"(d[4]), "+f"(d[5]), "+f"(d[6]), "+f"(d[7]), "+f"(d[8]), "+f"(d[9]), "+f"(d[10]), "+f"(d[11]), "+f"(d[12]), "+f"(d[13]), "+f"(d[14]), "+f"(d[15]), "+f"(d[16]), "+f"(d[17]), "+f"(d[18]), "+f"(d[19]), "+f"(d[20]), "+f"(d[21]), "+f"(d[22]), "+f"(d[23]), "+f"(d[24]), "+f"(d[25]), "+f"(d[26]), "+f"(d[27]), "+f"(d[28]), "+f"(d[29]), "+f"(d[30]), "+f"(d[31]), "+f"(d[32]), "+f"(d[33]), "+f"(d[34]), "+f"(d[35])
    : "r"(da), "r"(db), "r"(scale_d));
}
__device__ __forceinline__ void wgmma_rs_n32_tb_init(float (&d)[16], uint32_t a0, uint32_t a1, uint32_t a2, uint32_t a3, uint32_t db) {
  asm volatile("{\n.reg .pred p;\n.reg .b64 b;\nsetp.ne.b32 p, 0, 0;\nmov.b64 b, {%20, 0x40000040};\n"
    "wgmma.mma_async.sync.aligned.m64n32k16.f32.bf16.bf16 {%0, %1, %2, %3, %4, %5, %6, %7, %8, %9, %10, %11, %12, %13, %14, %15}, {%16, %17, %18, %19}, b, p, 1, 1, 1;\n}\n"
    : "=f"(d[0]), "=f"(d[1]), "=f"(d[2]), "=f"(d[3]), "=f"(d[4]), "=f"(d[5]), "=f"(d[6]), "=f"(d[7]), "=f"(d[8]), "=f"(d[9]), "=f"(d[10]), "=f"(d[11]), "=f"(d[12]), "=f"(d[13]), "=f"(d[14]), "=f"(d[15])
    : "r"(a0), "r"(a1), "r"(a2), "r"(a3), "r"(db));
}
__device__ __forceinline__ void wgmma_rs_n32_tb(float (&d)[16], uint32_t a0, uint32_t a1, uint32_t a2, uint32_t a3, uint32_t db, int scale_d) {
  asm volatile("{\n.reg .pred p;\n.reg .b64 b;\nsetp.ne.b32 p, %21, 0;\nmov.b64 b, {%20, 0x40000040};\n"
    "wgmma.mma_async.sync.aligned.m64n32k16.f32.bf16.bf16 {%0, %1, %2, %3, %4, %5, %6, %7, %8, %9, %10, %11, %12, %13, %14, %15}, {%16, %17, %18, %19}, b, p, 1, 1, 1;\n}\n"
    : "+f"(d[0]), "+f"(d[1]), "+f"(d[2]), "+f"(d[3]), "+f"(d[4]), "+f"(d[5]), "+f"(d[6]), "+f"(d[7]), "+f"(d[8]), "+f"(d[9]), "+f"(d[10]), "+f"(d[11]), "+f"(d[12]), "+f"(d[13]), "+f"(d[14]), "+f"(d[15])
    : "r"(a0), "r"(a1), "r"(a2), "r"(a3), "r"(db), "r"(scale_d));
}
template <int OA, int OB>
__device__ __forceinline__ void wgmma_ss_n128_tb(float (&d)[64], uint32_t da, uint32_t db, int scale_d) {
  asm volatile("{\n.reg .pred p;\n.reg .b64 a, b;\n.reg .b32 x, y;\nsetp.ne.b32 p, %66, 0;\nadd.u32 x, %64, %67;\nadd.u32 y, %65, %68;\nmov.b64 a, {x, 0x40000040};\nmov.b64 b, {y, 0x40000040};\n"
    "wgmma.mma_async.sync.aligned.m64n128k16.f32.bf16.bf16 {%0, %1, %2, %3, %4, %5, %6, %7, %8, %9, %10, %11, %12, %13, %14, %15, %16, %17, %18, %19, %20, %21, %22, %23, %24, %25, %26, %27, %28, %29, %30, %31, %32, %33, %34, %35, %36, %37, %38, %39, %40, %41, %42, %43, %44, %45, %46, %47, %48, %49, %50, %51, %52, %53, %54, %55, %56, %57, %58, %59, %60, %61, %62, %63}, a, b, p, 1, 1, 0, 1;\n}\n"
    : "+f"(d[0]), "+f"(d[1]), "+f"(d[2]), "+f"(d[3]), "+f"(d[4]), "+f"(d[5]), "+f"(d[6]), "+f"(d[7]), "+f"(d[8]), "+f"(d[9]), "+f"(d[10]), "+f"(d[11]), "+f"(d[12]), "+f"(d[13]), "+f"(d[14]), "+f"(d[15]), "+f"(d[16]), "+f"(d[17]), "+f"(d[18]), "+f"(d[19]), "+f"(d[20]), "+f"(d[21]), "+f"(d[22]), "+f"(d[23]), "+f"(d[24]), "+f"(d[25]), "+f"(d[26]), "+f"(d[27]), "+f"(d[28]), "+f"(d[29]), "+f"(d[30]), "+f"(d[31]), "+f"(d[32]), "+f"(d[33]), "+f"(d[34]), "+f"(d[35]), "+f"(d[36]), "+f"(d[37]), "+f"(d[38]), "+f"(d[39]), "+f"(d[40]), "+f"(d[41]), "+f"(d[42]), "+f"(d[43]), "+f"(d[44]), "+f"(d[45]), "+f"(d[46]), "+f"(d[47]), "+f"(d[48]), "+f"(d[49]), "+f"(d[50]), "+f"(d[51]), "+f"(d[52]), "+f"(d[53]), "+f"(d[54]), "+f"(d[55]), "+f"(d[56]), "+f"(d[57]), "+f"(d[58]), "+f"(d[59]), "+f"(d[60]), "+f"(d[61]), "+f"(d[62]), "+f"(d[63])
    : "r"(da), "r"(db), "r"(scale_d), "n"(OA), "n"(OB));
}
template <int OA, int OB>
__device__ __forceinline__ void wgmma_ss_n256_tbo(float (&d)[128], uint32_t da, uint32_t db, int scale_d) {
  asm volatile("{\n.reg .pred p;\n.reg .b64 a, b;\n.reg .b32 x, y;\nsetp.ne.b32 p, %130, 0;\nadd.u32 x, %128, %131;\nadd.u32 y, %129, %132;\nmov.b64 a, {x, 0x40000040};\nmov.b64 b, {y, 0x40000040};\n"
    "wgmma.mma_async.sync.aligned.m64n256k16.f32.bf16.bf16 {%0, %1, %2, %3, %4, %5, %6, %7, %8, %9, %10, %11, %12, %13, %14, %15, %16, %17, %18, %19, %20, %21, %22, %23, %24, %25, %26, %27, %28, %29, %30, %31, %32, %33, %34, %35, %36, %37, %38, %39, %40, %41, %42, %43, %44, %45, %46, %47, %48, %49, %50, %51, %52, %53, %54, %55, %56, %57, %58, %59, %60, %61, %62, %63, %64, %65, %66, %67, %68, %69, %70, %71, %72, %73, %74, %75, %76, %77, %78, %79, %80, %81, %82, %83, %84, %85, %86, %87, %88, %89, %90, %91, %92, %93, %94, %95, %96, %97, %98, %99, %100, %101, %102, %103, %104, %105, %106, %107, %108, %109, %110, %111, %112, %113, %114, %115, %116, %117, %118, %119, %120, %121, %122, %123, %124, %125, %126, %127}, a, b, p, 1, 1, 0, 1;\n}\n"
    : "+f"(d[0]), "+f"(d[1]), "+f"(d[2]), "+f"(d[3]), "+f"(d[4]), "+f"(d[5]), "+f"(d[6]), "+f"(d[7]), "+f"(d[8]), "+f"(d[9]), "+f"(d[10]), "+f"(d[11]), "+f"(d[12]), "+f"(d[13]), "+f"(d[14]), "+f"(d[15]), "+f"(d[16]), "+f"(d[17]), "+f"(d[18]), "+f"(d[19]), "+f"(d[20]), "+f"(d[21]), "+f"(d[22]), "+f"(d[23]), "+f"(d[24]), "+f"(d[25]), "+f"(d[26]), "+f"(d[27]), "+f"(d[28]), "+f"(d[29]), "+f"(d[30]), "+f"(d[31]), "+f"(d[32]), "+f"(d[33]), "+f"(d[34]), "+f"(d[35]), "+f"(d[36]), "+f"(d[37]), "+f"(d[38]), "+f"(d[39]), "+f"(d[40]), "+f"(d[41]), "+f"(d[42]), "+f"(d[43]), "+f"(d[44]), "+f"(d[45]), "+f"(d[46]), "+f"(d[47]), "+f"(d[48]), "+f"(d[49]), "+f"(d[50]), "+f"(d[51]), "+f"(d[52]), "+f"(d[53]), "+f"(d[54]), "+f"(d[55]), "+f"(d[56]), "+f"(d[57]), "+f"(d[58]), "+f"(d[59]), "+f"(d[60]), "+f"(d[61]), "+f"(d[62]), "+f"(d[63]), "+f"(d[64]), "+f"(d[65]), "+f"(d[66]), "+f"(d[67]), "+f"(d[68]), "+f"(d[69]), "+f"(d[70]), "+f"(d[71]), "+f"(d[72]), "+f"(d[73]), "+f"(d[74]), "+f"(d[75]), "+f"(d[76]), "+f"(d[77]), "+f"(d[78]), "+f"(d[79]), "+f"(d[80]), "+f"(d[81]), "+f"(d[82]), "+f"(d[83]), "+f"(d[84]), "+f"(d[85]), "+f"(d[86]), "+f"(d[87]), "+f"(d[88]), "+f"(d[89]), "+f"(d[90]), "+f"(d[91]), "+f"(d[92]), "+f"(d[93]), "+f"(d[94]), "+f"(d[95]), "+f"(d[96]), "+f"(d[97]), "+f"(d[98]), "+f"(d[99]), "+f"(d[100]), "+f"(d[101]), "+f"(d[102]), "+f"(d[103]), "+f"(d[104]), "+f"(d[105]), "+f"(d[106]), "+f"(d[107]), "+f"(d[108]), "+f"(d[109]), "+f"(d[110]), "+f"(d[111]), "+f"(d[112]), "+f"(d[113]), "+f"(d[114]), "+f"(d[115]), "+f"(d[116]), "+f"(d[117]), "+f"(d[118]), "+f"(d[119]), "+f"(d[120]), "+f"(d[121]), "+f"(d[122]), "+f"(d[123]), "+f"(d[124]), "+f"(d[125]), "+f"(d[126]), "+f"(d[127])
    : "r"(da), "r"(db), "r"(scale_d), "n"(OA), "n"(OB));
}

constexpr int NCTA = 132;
constexpr int NCLUSTER = 66;
constexpr int NPROB = 6;
#define DO_LOCAL true
#define DO_ATT true
#define NA_CL_ 32
#define NITEMS 512
constexpr int G1_MAX = 24, NA_CL = NA_CL_, NB_CTA = NCTA - 2 * NA_CL;
constexpr int TILE32K = 32768;
constexpr uint32_t DBASE = 1024;
constexpr int OFF_STG = 4 * TILE32K;
constexpr int OFF_A = 5 * TILE32K;
constexpr int OFF_BAR = 7 * TILE32K;
constexpr int L_K = 8192, L_V = L_K + 9216, L_P = L_V + 9216;
constexpr int SMEM_BYTES = OFF_BAR + 1024;
constexpr int B_GFULL = 0, B_GEMPTY = 32, B_AFULL = 64, B_AEMPTY = 104, B_QFULL = 144, B_QEMPTY = 160,
              B_SFULL = 176, B_SEMPTY = 208, B_OFULL = 240, B_STGFREE = 256, S_CODE = 272, B_SFULL2 = 304;
#define ASL 4
constexpr int A_SLOTS = ASL;
#define FS 2
#define HW 1
#define REG_C 232
#define REG_P 40

struct Params {
  CUtensorMap ta[NPROB];
  CUtensorMap tb[NPROB];
  CUtensorMap tc[NPROB];
  CUtensorMap tq, tk, tv, to, tl, th;
  bf16* ob;
  const bf16* qkvb;
  int opt;
  uint16_t g[NCLUSTER][G1_MAX];
  uint16_t order[512];
};
__device__ __forceinline__ uint32_t tail_item(uint32_t code) {
  return (code & 0x7FFF) < 64 ? (5u << 8) | ((code & 4) << 4) | (code & 0x33) : 0xFFFFu;
}
#define HM 0x39383F30
#define HINT(b) ((HM >> (b) & 1) ? EV_FIRST : EV_NORMAL)
__device__ __forceinline__ uint32_t lds32(uint32_t a) {
  uint32_t v;
  asm volatile("ld.shared.u32 %0, [%1];" : "=r"(v) : "r"(a) : "memory");
  return v;
}
__device__ __forceinline__ uint4 lds128(uint32_t a) {
  uint4 v;
  asm volatile("ld.shared.v4.u32 {%0, %1, %2, %3}, [%4];" : "=r"(v.x), "=r"(v.y), "=r"(v.z), "=r"(v.w) : "r"(a) : "memory");
  return v;
}
__device__ __forceinline__ void sts64(uint32_t a, float x, float y) {
  asm volatile("st.shared.v2.f32 [%0], {%1, %2};" ::"r"(a), "f"(x), "f"(y) : "memory");
}
__device__ __forceinline__ void sts32(uint32_t a, uint32_t v) {
  asm volatile("st.shared.u32 [%0], %1;" ::"r"(a), "r"(v) : "memory");
}
__device__ __forceinline__ uint32_t opaque_tid() {
  uint32_t t;
  asm volatile("mov.u32 %0, %%tid.x;" : "=r"(t));
  return t;
}
__device__ __forceinline__ uint32_t stg_off(uint32_t tid) {
  return (tid >> 5) * 2048 + (tid & 15) * 128 + ((((tid >> 4) & 1) ^ (tid & 7)) << 4);
}
__device__ __forceinline__ int prob_nkb4(int prob) { return (0x4F4224 >> (prob * 4) & 15) + (prob == 4); }

constexpr float SM_C = 0.08838834764831845f * 1.4426950408889634f;
constexpr float SM_HI = 1099511627776.0f;
constexpr float SM_LO = 8.673617379884035e-19f;
__device__ __forceinline__ void softmax_max(const float (&s)[64], float& a0, float& a1) {
  a0 = fmaxf(s[0], s[1]);
  a1 = fmaxf(s[2], s[3]);
#pragma unroll
  for (int j = 1; j < 16; j++) {
    a0 = fmaxf(a0, fmaxf(s[4 * j], s[4 * j + 1]));
    a1 = fmaxf(a1, fmaxf(s[4 * j + 2], s[4 * j + 3]));
  }
  a0 = fmaxf(a0, __shfl_xor_sync(0xffffffffu, a0, 1));
  a1 = fmaxf(a1, __shfl_xor_sync(0xffffffffu, a1, 1));
  a0 = fmaxf(a0, __shfl_xor_sync(0xffffffffu, a0, 2));
  a1 = fmaxf(a1, __shfl_xor_sync(0xffffffffu, a1, 2));
}
template <int J0, int J1, bool OFS, int N>
__device__ __forceinline__ void softmax_exp(const float (&s)[64], float b0, float b1, uint32_t (&out)[N], float& t0,
                                            float& t1) {
#pragma unroll
  for (int j = J0; j < J1; j++) {
    const float e0 = ex2(OFS ? s[4 * j] + b0 : s[4 * j]);
    const float e1 = ex2(OFS ? s[4 * j + 1] + b0 : s[4 * j + 1]);
    const float e2 = ex2(OFS ? s[4 * j + 2] + b1 : s[4 * j + 2]);
    const float e3 = ex2(OFS ? s[4 * j + 3] + b1 : s[4 * j + 3]);
    t0 += e0 + e1;
    t1 += e2 + e3;
    out[2 * j] = pack_bf16(e0, e1);
    out[2 * j + 1] = pack_bf16(e2, e3);
  }
}

__device__ __forceinline__ uint32_t scale_q(uint32_t x) {
  uint32_t t, y;
  asm("mul.rn.bf16x2 %0, %1, %2;" : "=r"(t) : "r"(x), "r"(0xb9d8b9d8u));
  asm("fma.rn.bf16x2 %0, %1, %2, %3;" : "=r"(y) : "r"(x), "r"(0x3e033e03u), "r"(t));
  return y;
}

__global__ void __cluster_dims__(2, 1, 1) __launch_bounds__(384, 1) mega_kernel(const __grid_constant__ Params p) {
  extern __shared__ __align__(1024) uint8_t smem_raw[];
  const uint32_t sbase = smem_u32(smem_raw);
  if ((sbase & 0x3FFFFu) != DBASE) __trap();
  const uint32_t s_bar = sbase + OFF_BAR;
  const int warp0 = __shfl_sync(0xffffffffu, threadIdx.x >> 5, 0);
  const int cluster_id = blockIdx.x >> 1;
  const bool isB = cluster_id >= NA_CL;
#define EARLY 1
  auto early = [&](int s0, int s1) {
    const int prob = isB ? 3 : cluster_id >> 4;
    const int ng = (isB ? (cluster_id - NA_CL) >> 3 : (cluster_id >> 3) & 1) * 4;
    const uint32_t t0 = clock();
#pragma unroll 1
    for (int s = s0; s < s1; s++) {
      const uint32_t full = s_bar + B_GFULL + 8 * s;
      mbar_expect_tx(full, 49152);
      while ((uint32_t)clock() - t0 < s * 850u) {}
      tma_load_3d(sbase + OFF_A + s * 16384, &p.ta[prob], 0, (blockIdx.x & 15) * 128, s, full, EV_NORMAL);
      tma_load_3d(sbase + s * TILE32K, &p.tb[prob], 0, s * 64, ng, full, EV_NORMAL);
      tma_load_3d(sbase + s * TILE32K + 16384, &p.tb[prob], 0, s * 64, ng + 2, full, EV_NORMAL);
    }
  };
  if (threadIdx.x == 256) {
    for (int s = 0; s < 4; s++) mbar_init(s_bar + B_GFULL + 8 * s, 1);
    asm volatile("fence.mbarrier_init.release.cluster;" ::: "memory");
  }
  if (threadIdx.x == 0) {
    for (int s = 0; s < 4; s++) {
      mbar_init(s_bar + B_GEMPTY + 8 * s, 4);
      mbar_init(s_bar + B_SFULL + 8 * s, 4);
      mbar_init(s_bar + B_SFULL2 + 8 * s, 4);
      mbar_init(s_bar + B_SEMPTY + 8 * s, 1);
    }
    for (int s = 0; s < A_SLOTS; s++) {
      mbar_init(s_bar + B_AFULL + 8 * s, 1);
      mbar_init(s_bar + B_AEMPTY + 8 * s, s == 1 && !isB ? 8 : 2);
    }
    for (int s = 0; s < 2; s++) {
      mbar_init(s_bar + B_QFULL + 8 * s, 1);
      mbar_init(s_bar + B_QEMPTY + 8 * s, 2);
    }
    mbar_init(s_bar + B_OFULL, 8);
    mbar_init(s_bar + B_STGFREE, 1);
    asm volatile("fence.mbarrier_init.release.cluster;" ::: "memory");
  }
  if (threadIdx.x == 320) sts32(s_bar + S_CODE, 0);
  __syncwarp();
  asm volatile("barrier.cluster.arrive.relaxed.aligned;" ::: "memory");
  if (warp0 >= 8) reg_dealloc<REG_P>();
  if (threadIdx.x == 288) prefetch_tmap(&p.tb[isB ? 3 : cluster_id >> 4]);
  if (EARLY && warp0 == 8 && elect_one()) early(0, 4);
  __syncwarp();
  asm volatile("barrier.cluster.wait.acquire.aligned;" ::: "memory");

  if (warp0 >= 8) {
    const int lane = threadIdx.x & 31;
    const uint32_t rank = blockIdx.x & 1;
    if (warp0 == 8) {
      if (elect_one()) {
        TL_DECL;
        uint32_t gphase = 1 - EARLY;
        uint32_t tail = 0;
        int gi = 0;
        uint32_t rsel = rank, aswz = 0, lastq = 0, n = 0;
        for (int seg = 0; seg < 2; seg++) {
          for (;;) {
            uint32_t item = p.g[cluster_id][gi++];
            if (item == 0x500u) item = tail;
            if (item >= 0x600u) break;
            const int prob = item >> 8;
            const int rt = ((item >> 4) & 15) * 2 + rsel;
            const int ngrp0 = (item & 15) * 4;
            const int nkb4 = prob_nkb4(prob);
            const CUtensorMap* ta = &p.ta[prob];
            const CUtensorMap* tb = &p.tb[prob];
            TL(1, item);
            if (prob == 5) {
              uint32_t seen = 0;
              cnt_wait_bit(CNT_OB + (rt >> 2), 32u << (rt & 3) * 8, seen);
              fence_proxy_async_global();
            }
            for (int kb4 = EARLY && gi == 1; kb4 < nkb4; kb4++) {
              uint32_t seen = 0;
#pragma unroll 1
              for (int s = 0; s < 4; s++) {
                const int bs = s ^ (n & 1);
                if (prob == 4 && !(s & 1)) {
                  cnt_wait_bit(CNT_CTX + kb4, 16u << (s * 8), seen);
                  fence_proxy_async_global();
                }
                if (prob == 5 && kb4 == 0) {
                  mbar_wait(s_bar + B_AEMPTY + 8 * bs, (~(n + (s & 1)) >> 1) & 1);
                  if (s == 2) mbar_wait(s_bar + B_QEMPTY + (aswz ? 0 : 8), lastq);
                }
                mbar_wait(s_bar + B_GEMPTY + 8 * s, gphase);
                const uint32_t full = s_bar + B_GFULL + 8 * s;
                mbar_expect_tx(full, 49152);
                tma_load_3d(sbase + OFF_A + ((s * 16384) ^ aswz), ta, 0, rt * 128, kb4 * 4 + s, full, HINT(prob));
                if (prob == 5) {
                  tma_load_3d(sbase + bs * TILE32K, tb, 0, (kb4 * 4 + s) * 64, ngrp0, full, HINT(8 + prob));
                  tma_load_3d(sbase + bs * TILE32K + 16384, tb, 0, (kb4 * 4 + s) * 64, ngrp0 + 2, full, HINT(8 + prob));
                } else {
                  tma_load_3d_mc(sbase + s * TILE32K + rank * 16384, tb, 0, (kb4 * 4 + s) * 64, ngrp0 + rank * 2, full,
                                 (uint16_t)3, HINT(8 + prob));
                }
              }
              gphase ^= 1;
            }
          }
          if (seg == 0 && isB && DO_ATT) {
            int pv_row = 0, pv_col = 0;
            uint64_t pv_hint = 0;
#define ACQ_SLOT(slot, n)                                                              \
  {                                                                                    \
    if ((n) < 2) mbar_wait(s_bar + B_GEMPTY + 8 * (slot), gphase);                     \
    mbar_wait(s_bar + B_AEMPTY + 8 * (slot), (~(n) >> 1) & 1);                         \
  }
#define LOAD_V()                                                                       \
  {                                                                                    \
    const uint32_t vs = 3 - (n & 1);                                                   \
    ACQ_SLOT(vs, n - 1);                                                               \
    mbar_expect_tx(s_bar + B_AFULL + 8 * vs, TILE32K);                                 \
    tma_load_3d(sbase + vs * TILE32K, &p.tv, 0, pv_row, pv_col, s_bar + B_AFULL + 8 * vs, pv_hint); \
  }
#define NEXT_CODE() (nxt < 512 ? p.order[nxt] : nxt + (0x8000u - 512))
            uint32_t code = p.order[blockIdx.x - 2 * NA_CL];
            int it = 0;
            uint32_t seen = 0;
            for (;; it++) {
              if (it == 1) mbar_wait(s_bar + B_STGFREE, 0);
              if (code & 0x8000u) break;
              const int head = code >> 4;
              const int qt = code & 15;
              uint32_t nxt = 0;
              TL(1, 0x1000 | code);
              if (seen < 48) cnt_wait(CNT_QKV + (head >> 1), 48);
              fence_proxy_async_global();
              {
                const int b = it & 1;
                if (it < 2) {
                  mbar_wait(s_bar + B_GEMPTY + 16 * b, gphase);
                  mbar_wait(s_bar + B_GEMPTY + 16 * b + 8, gphase);
                }
                mbar_wait(s_bar + B_QEMPTY + 8 * b, ((it >> 1) & 1) ^ 1);
                mbar_expect_tx(s_bar + B_QFULL + 8 * b, TILE32K);
                tma_load_3d(sbase + OFF_A + b * TILE32K, &p.tq, 0, qt * 128, head * 2, s_bar + B_QFULL + 8 * b, HINT(24));
              }
#pragma unroll 1
              for (int t = qt; t >= 0; t--) {
                if (t == min(qt, 1)) nxt = cnt_next(CNT_QUEUE) + NB_CTA;
                if (t == 0) {
                  code = NEXT_CODE();
                  sts32(s_bar + S_CODE + 4 * ((it + 1) & 7), code);
                  seen = cnt_peek(CNT_QKV + ((code >> 5) & 15));
                }
                ACQ_SLOT(n & 1, n);
                mbar_expect_tx(s_bar + B_AFULL + 8 * (n & 1), TILE32K);
                tma_load_3d(sbase + (n & 1) * TILE32K, &p.tk, 0, t * 128, head * 2, s_bar + B_AFULL + 8 * (n & 1), HINT(t == qt ? 29 : 25));
                if (n) LOAD_V();
                n++;
                pv_row = t * 128;
                pv_col = head * 2;
                pv_hint = HINT(t == qt ? 29 : 26);
              }
            }
            ACQ_SLOT(n & 1, n);
            mbar_arrive(s_bar + B_AFULL + 8 * (n & 1));
            LOAD_V();
            tail = tail_item(code);
            aswz = (it & 1) * TILE32K;
            mbar_wait(s_bar + B_QEMPTY + 8 * (it & 1), ((it >> 1) & 1) ^ 1);
            rsel = (code >> 3) & 1;
            lastq = ((it - 1) >> 1) & 1;
          }
        }
        if (cnt_done(NCTA * 2)) cnt_rearm();
#pragma unroll 1
        for (int s = 0; s < 4; s++) mbar_wait(s_bar + B_GEMPTY + 8 * s, gphase);
        TL(1, 0xFFFF);
      }
    } else if (warp0 == 9) {
      if (elect_one()) {
        TL_DECL;
        uint32_t tail = 0;
        int gi = 0;
        uint32_t rsel = rank, aswz = 0;
        bool rearm = false;
        for (int seg = 0; seg < 2; seg++) {
          for (;;) {
            uint32_t item = p.g[cluster_id][gi++];
            if (item == 0x500u) item = tail;
            if (item >= 0x600u) break;
            const int prob = item >> 8;
            const int rt = ((item >> 4) & 15) * 2 + rsel;
            const int cg = (item & 15) * 4 + (prob == 5 ? 16 : 0);
            const CUtensorMap* tc = &p.tc[prob];
            const int nl = (p.g[cluster_id][gi] >> 8) == 4 && DO_LOCAL ? 8 : 1;
            const int grp = ((blockIdx.x >> 4) & 1) * 48 + (blockIdx.x & 15), r0 = (blockIdx.x >> 5) * 512;
            if (nl > 1) {
              cnt_wait(CNT_QKVB, 192);
              fence_proxy_async_global();
              sts32(s_bar + S_CODE, 2);
            }
            if (prob >= 4) rearm = cnt_done(NCTA * 2);
            const bool lastt = p.g[cluster_id][gi] >= 0x600u;
#pragma unroll 1
            for (int c = 0; c < 8; c++) {
              const int q = lastt ? c & 3 : c >> 1, w = lastt ? c >> 2 : c & 1;
              const int idx = w * 2 + (q & 1);
              const bool alt = lastt && q >= 2;
              mbar_wait(s_bar + (alt ? B_SFULL2 : B_SFULL) + 8 * idx, lastt ? seg : q >> 1);
              tma_store_3d(tc, sbase + (alt ? OFF_A + ((q * 16384) ^ aswz) + w * 8192 : OFF_STG + idx * 8192), 0,
                           rt * 128 + w * 64, cg + q, HINT(16 + prob));
              bulk_commit();
              if (c > 0 && !lastt) {
                bulk_wait_read<1>();
                mbar_arrive(s_bar + B_SEMPTY + 8 * ((w ^ 1) * 2 + (((c - 1) >> 1) & 1)));
              }
            }
            bulk_wait_read<0>();
            mbar_arrive(s_bar + (lastt ? B_STGFREE : B_SEMPTY + 8 * 3));
#pragma unroll 1
            for (int c = 0; c < nl; c++) {
              if (nl > 1) {
                mbar_wait(s_bar + B_AEMPTY, (c & 1) ^ 1);
                mbar_expect_tx(s_bar + B_AFULL, L_V);
                tma_load_3d(sbase + OFF_STG, &p.tl, 0, r0 + c * 64, grp, s_bar + B_AFULL, HINT(28));
                tma_load_3d(sbase + OFF_STG + L_K, &p.th, 0, r0 + c * 64 - 8, 16 + grp, s_bar + B_AFULL, HINT(28));
                mbar_wait(s_bar + B_AEMPTY + 8, (c & 1) ^ 1);
                mbar_expect_tx(s_bar + B_AFULL + 8, 9216);
                tma_load_3d(sbase + OFF_STG + L_V, &p.th, 0, r0 + c * 64 - 8, 32 + grp, s_bar + B_AFULL + 8, HINT(28));
                sts32(s_bar + S_CODE, c + 3);
              }
              if (c) {
                mbar_wait(s_bar + B_OFULL, ~c & 1);
                cnt_signal(CNT_OB + (blockIdx.x >> 5) * 2 + ((c - 1) >> 2), 1u << ((c - 1) & 3) * 8);
              } else if (prob < 4) {
                bulk_wait<0>();
                cnt_signal(prob == 3 ? CNT_QKVB : CNT_QKV + (item & 15));
                TL(2, item);
              }
            }
            if (nl > 1) {
              mbar_wait(s_bar + B_OFULL, 1);
              cnt_signal(CNT_OB + (blockIdx.x >> 5) * 2 + 1, 1u << 24);
              TL(2, 0x600);
            }
          }
          if (seg == 0 && isB && DO_ATT) {
            uint32_t code = p.order[blockIdx.x - 2 * NA_CL];
            for (int it = 0; !(code & 0x8000u); it++) {
              aswz = (~it & 1) * TILE32K;
              mbar_wait(s_bar + B_OFULL, it & 1);
              tma_store_3d(&p.to, sbase + OFF_STG, 0, (code & 15) * 128, (code >> 4) * 2, HINT(27));
              bulk_commit();
              const uint32_t nxt = lds32(s_bar + S_CODE + 4 * ((it + 1) & 7));
              bulk_wait_read<0>();
              mbar_arrive(s_bar + B_STGFREE);
              bulk_wait<0>();
              cnt_signal(CNT_CTX + (code >> 5), 1u << (code & 16));
              TL(2, 0x1000 | code);
              code = nxt;
            }
            tail = tail_item(code);
            rsel = (code >> 3) & 1;
            if (tail == 0xFFFFu) rearm = cnt_done(NCTA * 2);
          }
        }
        if (rearm) cnt_rearm();
        TL(2, 0xFFFF);
      }
    } else if (warp0 == 10 && !isB && DO_LOCAL) {
      const char* src = reinterpret_cast<const char*>(p.qkvb) + (((blockIdx.x >> 4) & 1) * 48 + (blockIdx.x & 15)) * 128;
      int spin = 0;
#pragma unroll 1
      for (int c = 0; c < 8; c++) {
        while (lds32(s_bar + S_CODE) <= c && ++spin < 100000) __nanosleep(256);
#pragma unroll 1
        for (int r = c ? 8 + lane : lane; r < 72; r += 32) {
          const int row = max((int)(blockIdx.x >> 5) * 512 + c * 64 - 8 + r, 0);
#pragma unroll
          for (int j = 0; j < 3; j++) asm volatile("prefetch.global.L2 [%0];" ::"l"(src + (size_t)row * 12288 + j * 2048));
        }
      }
    }
  } else {
    reg_alloc<REG_C>();
    const int warp = __shfl_sync(0xffffffffu, opaque_tid() >> 5, 0);
    const int wg = warp >> 2;
    const int lane = threadIdx.x & 31;
    TL_DECL;
    TR_DECL;
    uint32_t gphase = 0;
    uint32_t tail = 0, aswz = 0, rot = 0, etgt = warp & 1, stgpar = 1;
    int gi = 0;
    for (int seg = 0; seg < 2; seg++) {
      uint32_t item = p.g[cluster_id][gi++];
      if (item == 0x500u) item = tail;
      if (item < 0x600u) {
        float acc[128];
        uint32_t pk[64];
        int have = 0;
#define G_STORE_CHUNK(q)                                                                               \
  {                                                                                                    \
    const uint32_t st_base = sbase + OFF_STG + wg * 8192 + stg_off(opaque_tid());                      \
    if (have == 2) { _Pragma("unroll") for (int j = 0; j < 16; j++) pk[(q) * 16 + j] = scale_q(pk[(q) * 16 + j]); } \
    mbar_wait(s_bar + B_SEMPTY + 8 * (wg * 2 + ((q) & 1)), (((q) >> 1) & 1) ^ 1);                      \
    _Pragma("unroll") for (int j = 0; j < 4; j++)                                                      \
        stmatrix_x4((st_base ^ (j << 5)) + ((q) & 1) * 8192, pk[(q) * 16 + j * 4],                     \
                    pk[(q) * 16 + j * 4 + 1], pk[(q) * 16 + j * 4 + 2], pk[(q) * 16 + j * 4 + 3]);     \
    fence_proxy_async_smem();                                                                          \
    __syncwarp();                                                                                      \
    mbar_arrive_elect(s_bar + B_SFULL + 8 * (wg * 2 + ((q) & 1)), true);                              \
  }
#define G_STAGE(s) G_STAGE_Y(s, false, false, )
#define G_STAGE_X(s, ...) G_STAGE_Y(s, false, false, __VA_ARGS__)
#define G_STAGE_Y(s, first, last, ...)                                                                    \
  {                                                                                                       \
    mbar_wait_rest(s_bar + B_GFULL + 8 * (s), gphase, gok && (first));                                    \
    TR(9);                                                                                                \
    const uint32_t da = make_desc(DBASE + OFF_A + (((s) * 16384) ^ aswz) + wg * 8192, 16);                \
    const uint32_t db = make_desc(DBASE + ((s) ^ rot) * TILE32K, 8192);                                   \
    named_bar_sync_if(5 + wg, 256, !(first));                                                             \
    wgmma_fence();                                                                                        \
    _Pragma("unroll") for (int k = 0; k < 5; k++) {                                                       \
      __VA_ARGS__;                                                                                        \
      if (k == 0) wgmma_ss_n256_tbo<0, 0>(acc, da, db, !(first));                                         \
      if (k == 1) wgmma_ss_n256_tbo<2, 128>(acc, da, db, 1);                                              \
      if (k == 2) wgmma_ss_n256_tbo<4, 256>(acc, da, db, 1);                                              \
      if (k == 3) wgmma_ss_n256_tbo<6, 384>(acc, da, db, 1);                                              \
    }                                                                                                     \
    wgmma_commit();                                                                                       \
    named_bar_arrive_if(6 - wg, 256, !(wg ? (last) : (first)));                                           \
    if (!(first)) {                                                                                       \
      wgmma_wait<1>();                                                                                    \
      mbar_arrive_cluster_if(s_bar + B_GEMPTY + 8 * (((s) + 3) & 3), etgt, lane == 0 && (warp & 3) < 2);  \
    }                                                                                                     \
  }
        TL0(item);
        undef_regs(acc);
        {
          constexpr bool gok = false;
          G_STAGE_Y(0, true, false, )
        }
        undef_regs(pk);
        for (;;) {
          constexpr bool gok = false;
          const int nkb4 = prob_nkb4(item >> 8);
          const uint32_t next = p.g[cluster_id][gi++];
          if (have) G_STORE_CHUNK(0)
          G_STAGE(1)
          G_STAGE(2)
          if (have) G_STORE_CHUNK(1)
          G_STAGE(3)
          gphase ^= 1;
          G_STAGE(0)
          if (have) G_STORE_CHUNK(2)
          G_STAGE(1)
          G_STAGE(2)
          if (have) G_STORE_CHUNK(3)
          G_STAGE_Y(3, false, nkb4 == 2, )
          gphase ^= 1;
          int kb4 = 2;
          if (nkb4 == 16 && DO_LOCAL) {
            constexpr uint32_t aswz = 0, rot = 0;
            G_STAGE(0)
            G_STAGE(1)
            for (; kb4 < 10; kb4++) {
              float ls[36];
              TR(10);
              mbar_wait(s_bar + B_AFULL, kb4 & 1);
              TR(11);
              {
                const uint32_t dq = make_desc(DBASE + OFF_STG + wg * 64, 16);
                G_STAGE_X(2, if (k == 1) wgmma_ss_n72_init(ls, dq, dq + L_K / 16); if (k == 3) wgmma_ss_n72(ls, dq + 2, dq + L_K / 16 + 2, 1))
              }
              mbar_wait(s_bar + B_AFULL + 8, kb4 & 1);
              const int tid = opaque_tid();
              uint32_t vw[16];
              uint4 pw[8];
              {
                const uint32_t va = sbase + OFF_STG + L_V + ((tid >> 4) & 7) * 1024 + wg * 64 + (tid & 15) * 4;
#pragma unroll
                for (int j = 1; j < 16; j++) vw[j] = lds32((va ^ ((j & 7) << 4)) + j * 128);
              }
              G_STAGE(3)
              gphase ^= 1;
              fence_regs(ls);
              mbar_arrive_if(s_bar + B_AEMPTY, (threadIdx.x & 127) == 0);
              {
                const int d = (tid & 3) * 2 - ((tid >> 2) & 7);
                const bool p0 = d > 0, p1 = d >= 0;
                const int w = warp & 3;
                float x0, x1, y0, y1;
#define L_PICK(w_)                                   \
  {                                                  \
    x0 = p0 ? ls[8 * (w_)] : ls[8 * (w_) + 4];       \
    x1 = p1 ? ls[8 * (w_) + 1] : ls[8 * (w_) + 5];   \
    y0 = p0 ? ls[8 * (w_) + 6] : ls[8 * (w_) + 10];  \
    y1 = p1 ? ls[8 * (w_) + 7] : ls[8 * (w_) + 11];  \
  }
                if (w == 0) {
                  if (kb4 == 2 && blockIdx.x < 32) ls[0] = ls[1] = -INFINITY;
                  L_PICK(0)
                } else if (w == 1) L_PICK(1)
                else if (w == 2) L_PICK(2)
                else L_PICK(3)
                constexpr float C = 0.17677669529663687f * 1.4426950408889634f;
                float mx = fmaxf(x0, x1), my = fmaxf(y0, y1);
                mx = fmaxf(mx, __shfl_xor_sync(0xffffffffu, mx, 1));
                my = fmaxf(my, __shfl_xor_sync(0xffffffffu, my, 1));
                mx = -C * fmaxf(mx, __shfl_xor_sync(0xffffffffu, mx, 2));
                my = -C * fmaxf(my, __shfl_xor_sync(0xffffffffu, my, 2));
                x0 = ex2(fmaf(x0, C, mx));
                x1 = ex2(fmaf(x1, C, mx));
                y0 = ex2(fmaf(y0, C, my));
                y1 = ex2(fmaf(y1, C, my));
                float sx = x0 + x1, sy = y0 + y1;
                sx += __shfl_xor_sync(0xffffffffu, sx, 1);
                sy += __shfl_xor_sync(0xffffffffu, sy, 1);
                sx += __shfl_xor_sync(0xffffffffu, sx, 2);
                sy += __shfl_xor_sync(0xffffffffu, sy, 2);
                sx = rcp(sx);
                sy = rcp(sy);
                const uint32_t pa = sbase + OFF_STG + L_P + (tid >> 5) * 512 + (tid & 31) * 8;
                sts64(pa, x0 * sx, x1 * sx);
                sts64(pa + 256, y0 * sy, y1 * sy);
                __syncwarp();
              }
              const uint32_t pr = sbase + OFF_STG + L_P + (tid >> 4) * 256;
              uint32_t* dst = reinterpret_cast<uint32_t*>(p.ob) + (blockIdx.x & 15) * 32 + wg * 16 + (tid & 15) +
                              (((blockIdx.x >> 5) * 512 + (kb4 - 2) * 64 + ((tid >> 4) & 7) * 8) * 2 + ((blockIdx.x >> 4) & 1)) * 512;
#define L_PV(g0)                                                                                       \
  _Pragma("unroll") for (int g = (g0); g < (g0) + 4; g++) {                                            \
    const uint4 a = pw[2 * (g & 3)], b = pw[2 * (g & 3) + 1];                                          \
    const uint32_t w[8] = {a.x, a.y, a.z, a.w, b.x, b.y, b.z, b.w};                                    \
    float o0 = 0.f, o1 = 0.f;                                                                          \
    _Pragma("unroll") for (int c = 0; c < 8; c++) {                                                    \
      const uint32_t u = vw[c > g ? c : c + 8];                                                        \
      o0 = fmaf(__uint_as_float(w[c]), __uint_as_float(u << 16), o0);                                  \
      o1 = fmaf(__uint_as_float(w[c]), __uint_as_float(u & 0xFFFF0000u), o1);                          \
    }                                                                                                  \
    dst[g * 1024] = pack_bf16(o0, o1);                                                                 \
  }
#pragma unroll
              for (int j = 0; j < 8; j++) pw[j] = lds128(pr + j * 16);
              mbar_arrive_elect(s_bar + B_AEMPTY + 8, true);
              G_STAGE(0)
              L_PV(0)
#pragma unroll
              for (int j = 0; j < 8; j++) pw[j] = lds128(pr + 128 + j * 16);
              G_STAGE(1)
              L_PV(4)
              __syncwarp();
              mbar_arrive_elect(s_bar + B_OFULL, true);
            }
            G_STAGE(2)
            G_STAGE(3)
            gphase ^= 1;
            kb4++;
          }
          const bool fin = next >= 0x600u;
          for (; kb4 < nkb4 - fin; kb4++) {
            G_STAGE(0)
            G_STAGE(1)
            G_STAGE(2)
            G_STAGE_Y(3, false, kb4 + 1 == nkb4, )
            gphase ^= 1;
          }
          if (fin) break;
          wgmma_wait<0>();
          mbar_arrive_cluster_if(s_bar + B_GEMPTY + 8 * 3, etgt, lane == 0 && (warp & 3) < 2);
          {
            const bool gok = mbar_test(s_bar + B_GFULL, gphase);
            fence_regs(acc);
#pragma unroll
            for (int j = 0; j < 64; j++) pk[j] = pack_bf16(acc[2 * j], acc[2 * j + 1]);
            have = item < 0x100u ? 2 : 1;
            item = next;
            TL0(item);
            G_STAGE_Y(0, true, false, )
          }
        }
        {
          constexpr bool gok = false;
          G_STAGE(0)
          G_STAGE(1)
          wgmma_wait<0>();
          mbar_arrive_cluster_if(s_bar + B_GEMPTY + 8 * (FS - 1), etgt, lane == 0 && (warp & 3) < 2);
          fence_regs(acc);
          float lo[64], hi[64];
#pragma unroll
          for (int j = 0; j < 64; j++) {
            asm volatile("mov.b32 %0, %1;" : "=f"(lo[j]) : "f"(acc[j]));
            asm volatile("mov.b32 %0, %1;" : "=f"(hi[j]) : "f"(acc[64 + j]));
          }
#pragma unroll
          for (int s = FS; s < 4; s++) {
            mbar_wait(s_bar + B_GFULL + 8 * s, gphase);
            const uint32_t da = make_desc(DBASE + OFF_A + ((s * 16384) ^ aswz) + wg * 8192, 16);
            const uint32_t db = make_desc(DBASE + (s ^ rot) * TILE32K, 8192);
            if (s == FS) named_bar_sync(5 + wg, 256);
            wgmma_fence();
            wgmma_ss_n128_tb<0, 0>(lo, da, db, 1);
            wgmma_ss_n128_tb<2, 128>(lo, da, db, 1);
            wgmma_ss_n128_tb<4, 256>(lo, da, db, 1);
            wgmma_ss_n128_tb<6, 384>(lo, da, db, 1);
            wgmma_commit();
          }
          wgmma_fence();
#pragma unroll
          for (int s = FS; s < 4; s++) {
            const uint32_t da = make_desc(DBASE + OFF_A + ((s * 16384) ^ aswz) + wg * 8192, 16);
            const uint32_t db = make_desc(DBASE + (s ^ rot) * TILE32K, 8192);
            wgmma_ss_n128_tb<0, 1024>(hi, da, db, 1);
            wgmma_ss_n128_tb<2, 1152>(hi, da, db, 1);
            wgmma_ss_n128_tb<4, 1280>(hi, da, db, 1);
            wgmma_ss_n128_tb<6, 1408>(hi, da, db, 1);
          }
          wgmma_commit();
          named_bar_arrive_if(6, 256, wg == 0);
          gphase ^= 1;
          const uint32_t so = sbase + stg_off(opaque_tid());
          mbar_wait(s_bar + B_STGFREE, stgpar);
          mbar_wait(s_bar + B_SEMPTY + 16 * wg, 1);
          mbar_wait(s_bar + B_SEMPTY + 16 * wg + 8, 1);
#define FIN_HALF(x, base, stride, bar)                                                                                \
  fence_regs(x);                                                                                                      \
  _Pragma("unroll") for (int j = 0; j < 8; j++)                                                                       \
      stmatrix_x4(((base) ^ ((j & 3) << 5)) + (j >> 2) * (stride), pack_bf16(x[8 * j], x[8 * j + 1]),                 \
                  pack_bf16(x[8 * j + 2], x[8 * j + 3]), pack_bf16(x[8 * j + 4], x[8 * j + 5]), pack_bf16(x[8 * j + 6], x[8 * j + 7])); \
  fence_proxy_async_smem();                                                                                           \
  __syncwarp();                                                                                                       \
  mbar_arrive_elect(s_bar + (bar) + 16 * wg, true);                                                                   \
  mbar_arrive_elect(s_bar + (bar) + 16 * wg + 8, true);
          wgmma_wait<1>();
          FIN_HALF(lo, so + OFF_STG + wg * 8192, 8192, B_SFULL)
          wgmma_wait<0>();
          TRI(12, 8);
#pragma unroll
          for (int s = FS; s < 4; s++) mbar_arrive_cluster_if(s_bar + B_GEMPTY + 8 * s, etgt, lane == 0 && (warp & 3) < 2);
          FIN_HALF(hi, so + OFF_A + (32768 ^ aswz), 16384, B_SFULL2)
          TRI(12, 10);
        }
      }
      if (seg == 0 && isB && DO_ATT) {
        float o[64], s[64];
        uint32_t pa[32], pb[32];
        undef_regs(o);
        undef_regs(s);
        undef_regs(pa);
        undef_regs(pb);
        uint32_t phase = 0;
        const bool sig = (threadIdx.x & 127) == 0;
        if (wg == 1) named_bar_arrive(1, 256);

#define ISSUE_PV(pr, slot_)                                                             \
  {                                                                                     \
    const uint32_t dv = make_desc(DBASE + (slot_) * TILE32K, 16384);                    \
    if (!(pfirst && wg == HW)) {                                                        \
      wgmma_fence();                                                                    \
      _Pragma("unroll") for (int k = 0; k < 8; k++)                                     \
          wgmma_rs_n128_tb(o, pr[4 * k], pr[4 * k + 1], pr[4 * k + 2], pr[4 * k + 3], dv + k * 128, (k != 0) || !pfirst); \
      wgmma_commit();                                                                   \
    } else {                                                                            \
      wgmma_fence();                                                                    \
      _Pragma("unroll") for (int k = 0; k < 4; k++)                                     \
          wgmma_rs_n128_tb(o, pr[16 + 4 * k], pr[17 + 4 * k], pr[18 + 4 * k], pr[19 + 4 * k], dv + k * 128, k != 0); \
      wgmma_commit();                                                                   \
    }                                                                                   \
  }
#define SHIFT_S(j0_)                                            \
  if (gen) {                                                    \
    _Pragma("unroll") for (int j = (j0_); j < 16; j++) {        \
      s[4 * j] += b0;                                           \
      s[4 * j + 1] += b0;                                       \
      s[4 * j + 2] += b1;                                       \
      s[4 * j + 3] += b1;                                       \
    }                                                           \
  }
#define EPILOGUE(on_)                                                                             \
  _Pragma("unroll") for (int j = 0; j < 8; j++) {                                                 \
    const int b = j * 8;                                                                          \
    stmatrix_x4_p((st_o ^ ((j & 3) << 5)) + (j >> 2) * 16384,                                     \
                  pack_bf16(o[b] * sc0, o[b + 1] * sc0), pack_bf16(o[b + 2] * sc1, o[b + 3] * sc1),   \
                  pack_bf16(o[b + 4] * sc0, o[b + 5] * sc0), pack_bf16(o[b + 6] * sc1, o[b + 7] * sc1), on_); \
  }
#define PUBLISH_O()                                  \
  {                                                  \
    fence_proxy_async_smem();                        \
    __syncwarp();                                    \
    mbar_arrive_elect(s_bar + B_OFULL, true);        \
  }
#define FINAL_SCALE()                                  \
  {                                                    \
    float e0 = l0, e1 = l1;                            \
    e0 += __shfl_xor_sync(0xffffffffu, e0, 1);         \
    e1 += __shfl_xor_sync(0xffffffffu, e1, 1);         \
    e0 += __shfl_xor_sync(0xffffffffu, e0, 2);         \
    e1 += __shfl_xor_sync(0xffffffffu, e1, 2);         \
    sc0 = rcp(e0);             \
    sc1 = rcp(e1);                                     \
  }
        float l0 = 1.f, l1 = 1.f, b0 = 0.f, b1 = 0.f, sc0 = 0.f, sc1 = 0.f;
        bool gen = false;
        bool pfirst = true;
        bool fresh = true;
        uint32_t code = p.order[blockIdx.x - 2 * NA_CL];
        int it = 0, rem = code & 15;
        TL0(0x1000 | code);
        mbar_wait(s_bar + B_AFULL, 0);
        mbar_wait(s_bar + B_QFULL, 0);
#define MMA_PART(N_, acc_, PIN, PAR)                                                                       \
  wgmma_fence();                                                                                           \
  uint32_t cv;                                                                                             \
  bool rv;                                                                                                 \
  _Pragma("unroll") for (int k = 0; k < 8; k++) {                                                          \
    wgmma_ss_n##N_(acc_, dq + (k >> 2) * 1024 + (k & 3) * 2, dk + (k >> 2) * 1024 + (k & 3) * 2, k != 0);  \
    if (k == 1) cv = lds32(s_bar + S_CODE + 4 * ((it + 1) & 7));          \
    if (k == 3) rv = mbar_test(s_bar + B_AFULL + 8 * (3 - (PAR)), phase ^ (1 - (PAR)));                    \
  }                                                                                                        \
  wgmma_commit();                                                                                          \
  code = __reduce_or_sync(0xffffffffu, cv);                                                                \
  if (opub) PUBLISH_O();                                                                                   \
  if (N_ == 128 && fresh) FINAL_SCALE();                                                                   \
  last = rem == 0 && (code & 0x8000u);                                                                     \
  nit = it + (rem == 0 && !last);                                                                          \
  mbar_wait_rest(s_bar + B_AFULL + 8 * (3 - (PAR)), phase ^ (1 - (PAR)), rv);                              \
  ISSUE_PV(PIN, 3 - (PAR));                                                                                \
  named_bar_arrive(2 - wg, 256);                                                                           \
  TR(2);                                                                                                   \
  wgmma_wait<1>();                                                                                         \
  fence_regs(acc_);                                                                                        \
  TR(3);                                                                                                   \
  mbar_arrive_if(s_bar + B_AEMPTY + 8 * (PAR), sig);                                                       \
  mbar_arrive_if(s_bar + B_QEMPTY + 8 * (it & 1), sig && rem == 0);
#define MASK_S(rowf)                                                                                       \
  _Pragma("unroll") for (int j = 0; j < 8; j++) {                                                          \
    s[32 + 4 * j] = fmaf(__saturatef(float(8 * j) - (rowf)), -3e38f, s[32 + 4 * j]);                       \
    s[33 + 4 * j] = fmaf(__saturatef(float(8 * j + 1) - (rowf)), -3e38f, s[33 + 4 * j]);                   \
    s[34 + 4 * j] = fmaf(__saturatef(float(8 * j - 8) - (rowf)), -3e38f, s[34 + 4 * j]);                   \
    s[35 + 4 * j] = fmaf(__saturatef(float(8 * j - 7) - (rowf)), -3e38f, s[35 + 4 * j]);                   \
  }
#define BAD_SUM() (!(t0 + t1 <= SM_HI) | (t0 < lo0) | (t1 < lo1))
#define WAIT_STG() mbar_wait_rest(s_bar + B_STGFREE, ~it & 1, mbar_test(s_bar + B_STGFREE, ~it & 1) | (it == 0))
#define SECOND_HALF(POUT, PAR, BAD, ...)                                                                   \
  wgmma_wait<0>();                                                                                         \
  mbar_arrive_if(s_bar + B_AEMPTY + 8 * (3 - (PAR)), sig && ((PAR) || !fresh || it > 0));                  \
                                                                               \
  const float rdy = mbar_test2(s_bar + B_AFULL + 8 * (1 - (PAR)), phase ^ (PAR), s_bar + B_QFULL + 8 * (nit & 1), (nit >> 1) & 1); \
  TR(8);                                                                                                   \
  __VA_ARGS__;                                                                                             \
  t0 += x0 + x1;                                                                                           \
  t1 += x2 + x3;                                                                                           \
  POUT[16] = pack_bf16(x0, x1);                                                                            \
  POUT[17] = pack_bf16(x2, x3);                                                                            \
  softmax_exp<9, TPOS, false>(s, 0.f, 0.f, POUT, t0, t1);                                                  \
  t0 = addv(t0, rdy);                                                                                      \
  softmax_exp<TPOS, 16, false>(s, 0.f, 0.f, POUT, t0, t1);                                                 \
  rare = __any_sync(0xffffffffu, (BAD) | (__float_as_uint(rdy) != 0));
#define TPOS 14
#define ATT_STEP(PIN, POUT, PAR, ...)                                                                      \
  {                                                                                                        \
    const uint32_t dq = make_desc(DBASE + OFF_A + (it & 1) * TILE32K + (wg ^ HW) * 8192, 16);                \
    const uint32_t dk = make_desc(DBASE + (PAR) * TILE32K, 16);                                            \
    float t0 = fresh ? 0.f : l0, t1 = fresh ? 0.f : l1, x0, x1, x2, x3;                                    \
    bool rare, last;                                                                                       \
    int nit;                                                                                               \
    TRI(0, fresh ? 7 : 0);                                                                                 \
    named_bar_sync(1 + wg, 256);                                                                           \
    TRI(1, fresh ? 6 : 1);                                                                                 \
    if (!fresh || wg != HW) {                                                                              \
      MMA_PART(128, s, PIN, PAR)                                                                           \
      if (fresh || gen) {                                                                                  \
        SHIFT_S(0);                                                                                        \
        if (fresh) {                                                                                       \
          MASK_S(mrow);                                                                                    \
          WAIT_STG();                                                                                      \
        }                                                                                                  \
      }                                                                                                    \
      softmax_exp<0, 8, false>(s, 0.f, 0.f, POUT, t0, t1);                                                 \
      x0 = ex2v(s[32]), x1 = ex2v(s[33]), x2 = ex2v(s[34]), x3 = ex2v(s[35]);                              \
    } else {                                                                                               \
                                                     \
      float sl[32];                                                                                        \
      _Pragma("unroll") for (int j = 0; j < 32; j++) sl[j] = 0.f;                                          \
      MMA_PART(64, sl, PIN, PAR)                                                                           \
      _Pragma("unroll") for (int j = 0; j < 32; j++) asm volatile("mov.b32 %0, %1;" : "=f"(s[32 + j]) : "f"(sl[j])); \
      SHIFT_S(8);                                                                                          \
      MASK_S(mrow);                                                                                        \
      FINAL_SCALE();                                                                                       \
      WAIT_STG();                                                                                          \
      x0 = ex2v(s[32]), x1 = ex2v(s[33]), x2 = ex2v(s[34]), x3 = ex2v(s[35]);                              \
    }                                                                                                      \
    const float lo1 = fresh ? SM_LO : 0.f, lo0 = mrow < 0.f && wg == HW ? 0.f : lo1;                       \
    if (!fresh) {                                                                                          \
      SECOND_HALF(POUT, PAR, !(t0 + t1 <= SM_HI), )                                                        \
    } else {                                                                                               \
      SECOND_HALF(POUT, PAR, BAD_SUM(), fence_regs(o); EPILOGUE(it > 0))                                   \
    }                                                                                                      \
    TR(4);                                                                                                 \
    if (rare) {                                                                                            \
      if (__any_sync(0xffffffffu, BAD_SUM())) {                                      \
                       \
        if (fresh && wg == HW) { _Pragma("unroll") for (int j = 0; j < 32; j++) asm volatile("mov.b32 %0, 0xff800000;" : "=f"(s[j])); }         \
        float d0, d1;                                                                                      \
        softmax_max(s, d0, d1);                                                                            \
        if (!fresh) {                                                                                      \
          d0 = fmaxf(d0, 0.f);                                                                             \
          d1 = fmaxf(d1, 0.f);                                                                             \
        }                                                                                                  \
        const float r0 = fresh ? 1.f : ex2(-d0), r1 = fresh ? 1.f : ex2(-d1);                              \
        t0 = fresh ? 0.f : l0 * r0;                                                                        \
        t1 = fresh ? 0.f : l1 * r1;                                                                        \
        softmax_exp<0, 16, true>(s, -d0, -d1, POUT, t0, t1);                                               \
        b0 -= d0;                                                                                          \
        b1 -= d1;                                                                                          \
        gen = true;                                                                                        \
        fence_regs(o);                                                                                     \
        _Pragma("unroll") for (int j = 0; j < 16; j++) {                                                   \
          o[4 * j] *= r0;                                                                                  \
          o[4 * j + 1] *= r0;                                                                              \
          o[4 * j + 2] *= r1;                                                                              \
          o[4 * j + 3] *= r1;                                                                              \
        }                                                                                                  \
      }                                                                                                    \
      const bool rq = mbar_test(s_bar + B_QFULL + 8 * (nit & 1), (nit >> 1) & 1);                          \
      mbar_wait(s_bar + B_AFULL + 8 * (1 - (PAR)), phase ^ (PAR));                                         \
      mbar_wait_rest(s_bar + B_QFULL + 8 * (nit & 1), (nit >> 1) & 1, rq);                                 \
    }                                                                                                      \
    fence_regs(o);                                                                                         \
    TR(5);                                                                                                 \
    opub = fresh && it > 0;                                                                                \
    pfirst = fresh;                                                                                        \
    l0 = t0;                                                                                               \
    l1 = t1;                                                                                               \
    if (last) {                                                                                            \
      __VA_ARGS__;                                                                                         \
      break;                                                                                               \
    }                                                                                                      \
    fresh = rem == 0;                                                                                      \
    if (fresh) { TL0(0x1000 | code); }                                                                     \
    rem = fresh ? code & 15 : rem - 1;                                                                     \
    it = nit;                                                                                              \
  }
        bool opub = false;
        const float mrow = float((warp & 3) * 16 + (lane >> 2) - (lane & 3) * 2);
        const uint32_t st_o = sbase + OFF_STG + stg_off(opaque_tid() ^ (HW * 128));
        for (;;) {
          ATT_STEP(pa, pb, 0, rot = 1; _Pragma("unroll") for (int j = 0; j < 32; j++) asm volatile("mov.b32 %0, %1;" : "=r"(pa[j]) : "r"(pb[j])))
          ATT_STEP(pb, pa, 1, rot = 0)
          phase ^= 1;
        }
        {
          mbar_wait(s_bar + B_AFULL + 8 * (3 - rot), phase);
          TRI(12, 2);
          ISSUE_PV(pa, 3 - rot);
          if (opub) PUBLISH_O();
          FINAL_SCALE();
          mbar_wait(s_bar + B_STGFREE, it & 1);
          wgmma_wait<0>();
          fence_regs(o);
          TRI(12, 4);
          mbar_arrive_if(s_bar + B_AEMPTY + 8 * (3 - rot), sig);
          EPILOGUE(true);
          PUBLISH_O();
          TRI(12, 5);
          stgpar = ~it & 1;
          tail = tail_item(code);
          aswz = (~it & 1) * TILE32K;
          etgt = blockIdx.x & 1;
        }
      }
    }
    TL0(0xFFFF);
    TRI(15, 15);
  }
}

typedef CUresult (*EncodeFn)(CUtensorMap*, CUtensorMapDataType, cuuint32_t, void*, const cuuint64_t*,
                             const cuuint64_t*, const cuuint32_t*, const cuuint32_t*, CUtensorMapInterleave,
                             CUtensorMapSwizzle, CUtensorMapL2promotion, CUtensorMapFloatOOBfill);

EncodeFn get_encode() {
  static EncodeFn fn = nullptr;
  if (!fn) {
    void* p = nullptr;
    cudaDriverEntryPointQueryResult st;
    cudaGetDriverEntryPoint("cuTensorMapEncodeTiled", &p, cudaEnableDefault, &st);
    fn = (EncodeFn)p;
  }
  return fn;
}

void make_map(CUtensorMap* m, const void* ptr, int rows, int cols, int box_rows, int box_groups,
              CUtensorMapSwizzle swz = CU_TENSOR_MAP_SWIZZLE_128B) {
  cuuint64_t dims[3] = {64, (cuuint64_t)rows, (cuuint64_t)(cols / 64)};
  cuuint64_t strides[2] = {(cuuint64_t)cols * 2, 128};
  cuuint32_t box[3] = {64, (cuuint32_t)box_rows, (cuuint32_t)box_groups};
  cuuint32_t es[3] = {1, 1, 1};
  CUtensorMapL2promotion prom = box_groups == 1 ? CU_TENSOR_MAP_L2_PROMOTION_NONE : CU_TENSOR_MAP_L2_PROMOTION_L2_256B;
  get_encode()(m, CU_TENSOR_MAP_DATA_TYPE_BFLOAT16, 3, const_cast<void*>(ptr), dims, strides, box, es,
               CU_TENSOR_MAP_INTERLEAVE_NONE, swz, prom,
               CU_TENSOR_MAP_FLOAT_OOB_FILL_NONE);
}

#define PARAM(name, val) const int name = val
void build_schedule(Params& p) {
  PARAM(C_KB, 1028);
  PARAM(C_TILE, 10);
  PARAM(C_QX, 0);
  PARAM(C_START, 4500);
  PARAM(C_STEP, 2052);
  PARAM(C_ITEM, 300);
  PARAM(C_LAG, 8000);
  PARAM(C_SP, 5200);
  PARAM(C_TAIL, 22000);
  PARAM(C_SHORT, 0);
  PARAM(C_AT, 72);
  PARAM(C_LATE, 0);
  PARAM(C_LMASK, 0xAA0);
  PARAM(C_AM, 100);
  PARAM(C_ODD, 1300);
  PARAM(C_READY, 10000);
  auto gemm_cost = [&](int prob) {
    static const int nkb[NPROB] = {16, 8, 8, 16, 64, 16};
    return nkb[prob] * C_KB + C_TILE + (prob == 0 ? C_QX : 0);
  };
  PARAM(OPT, 0);
  p.opt = OPT;
  memset(p.g, 0xFF, sizeof(p.g));
  int n1[NCLUSTER];
  long t1[NCLUSTER];
  long ready[16];
  for (int c = 0; c < NCLUSTER; c++) { n1[c] = 0; t1[c] = C_START; }
  for (int i = 0; i < 16; i++) ready[i] = 0;
  auto add = [&](int c, int prob, int mp, int nt) {
    p.g[c][n1[c]++] = (uint16_t)((prob << 8) | (mp << 4) | nt);
    t1[c] += gemm_cost(prob);
    if (prob < 3) {
      const long r = t1[c] + C_READY;
      if (r > ready[nt]) ready[nt] = r;
    }
  };
  for (int r = 0; r < 8; r++)
    for (int c = 0; c < NA_CL; c++) {
      const int mp = c & 7, nt = 2 * r + ((c >> 3) & 1);
      for (int j = 0; j < (c < 16 ? 1 : 2); j++) {
        add(c, c < 16 ? 0 : 1 + j, mp, nt);
      }
    }
  long tA = 0;
  for (int c = 0; c < NA_CL; c++) {
    if (t1[c] > tA) tA = t1[c];
    add(c, 4, c & 7, c >> 3);
  }
  for (int i = 0; i < 96; i++) add(NA_CL + i % (NCLUSTER - NA_CL), 3, i % 8, i / 8);
  for (int c = NA_CL; c < NCLUSTER; c++) {
    p.g[c][n1[c]++] = 0x600;
    p.g[c][n1[c]++] = 0x500;
  }
  long tf[NB_CTA];
  bool done[512], started[NB_CTA];
  long fin[16];
  for (int c = 0; c < NB_CTA; c++) { tf[c] = t1[NA_CL + (c >> 1)] + 2000; started[c] = false; }
  for (int i = 0; i < 512; i++) done[i] = false;
  for (int i = 0; i < 16; i++) fin[i] = 0;
  auto alen = [&](int qt) { return (long)(qt + 1) * C_STEP + C_ITEM + (qt < 2 ? C_SHORT : 0); };
  int nq = NB_CTA;
  for (int n = 0; n < 512; n++) {
    int cb = 0;
    for (int c = 1; c < NB_CTA; c++)
      if (tf[c] < tf[cb]) cb = c;
    int best = -1;
    long bkey = 0;
    for (int i = 0; i < 512; i++) {
      if (done[i]) continue;
      const int hp = i >> 5;
      long dl = -(long)(16 - hp) * C_SP - C_LAG + ((i >> 4) & 1) * C_ODD;
      if (dl > -C_TAIL) dl = -C_TAIL;
      long key = dl - alen(i & 15) * (dl == -C_TAIL ? C_AT : C_AM) / 100;
      if ((i >> 4) == 31 && (C_LMASK >> (i & 15) & 1)) key += C_LATE;
      if (ready[hp] > tf[cb]) key += (1L << 40) + (ready[hp] - tf[cb]) * 1024;
      if (best < 0 || key < bkey) { best = i; bkey = key; }
    }
    done[best] = true;
    if (!started[cb]) { p.order[cb] = (uint16_t)best; started[cb] = true; }
    else p.order[nq++] = (uint16_t)best;
    if (ready[best >> 5] > tf[cb]) tf[cb] = ready[best >> 5];
    tf[cb] += alen(best & 15);
    if (tf[cb] + C_LAG > fin[best >> 5]) fin[best >> 5] = tf[cb] + C_LAG;
  }
}

}

extern "C" void kernel_launch(void* const* d_in, const int* in_sizes, int n_in, void* d_out, int out_size) {
  const bf16* A_x = (const bf16*)d_in[0];
  const bf16* A_c = (const bf16*)d_in[1];
  const bf16* A_wq = (const bf16*)d_in[2];
  const bf16* A_wuk = (const bf16*)d_in[3];
  const bf16* A_wuv = (const bf16*)d_in[4];
  const bf16* A_wo = (const bf16*)d_in[5];
  const bf16* B_x = (const bf16*)d_in[6];
  const bf16* B_wqkv = (const bf16*)d_in[7];
  const bf16* B_wo = (const bf16*)d_in[8];
  bf16* out = (bf16*)d_out;

  static Params p;
  static bf16 *q, *k, *v, *ctx, *qkvb, *ob;
  static bool init = false;
  if (!init) {
    cudaGetSymbolAddress((void**)&q, g_q);
    cudaGetSymbolAddress((void**)&k, g_k);
    cudaGetSymbolAddress((void**)&v, g_v);
    cudaGetSymbolAddress((void**)&ctx, g_ctx);
    cudaGetSymbolAddress((void**)&qkvb, g_qkvb);
    cudaGetSymbolAddress((void**)&ob, g_ob);
    cudaFuncSetAttribute(mega_kernel, cudaFuncAttributeMaxDynamicSharedMemorySize, SMEM_BYTES);
    build_schedule(p);
    if (p.opt & 2) ctx = q;
    init = true;
  }
  make_map(&p.ta[0], A_x, SEQ, DM, 128, 1);
  make_map(&p.tb[0], A_wq, DM, HHD, 64, 2);
  make_map(&p.tc[0], q, SEQ, HHD, 64, 1);
  make_map(&p.ta[1], A_c, SEQ, DC, 128, 1);
  make_map(&p.tb[1], A_wuk, DC, HHD, 64, 2);
  make_map(&p.tc[1], k, SEQ, HHD, 64, 1);
  make_map(&p.ta[2], A_c, SEQ, DC, 128, 1);
  make_map(&p.tb[2], A_wuv, DC, HHD, 64, 2);
  make_map(&p.tc[2], v, SEQ, HHD, 64, 1);
  make_map(&p.ta[3], B_x, SEQ, DM, 128, 1);
  make_map(&p.tb[3], B_wqkv, DM, 3 * DM, 64, 2);
  make_map(&p.tc[3], qkvb, SEQ, 3 * DM, 64, 1);
  make_map(&p.ta[4], ctx, SEQ, HHD, 128, 1);
  make_map(&p.tb[4], A_wo, HHD, DM, 64, 2);
  make_map(&p.tc[4], out, SEQ, 2 * DM, 64, 1);
  make_map(&p.ta[5], ob, SEQ, DM, 128, 1);
  make_map(&p.tb[5], B_wo, DM, DM, 64, 2);
  make_map(&p.tc[5], out, SEQ, 2 * DM, 64, 1);
  make_map(&p.tq, q, SEQ, HHD, 128, 2);
  make_map(&p.tk, k, SEQ, HHD, 128, 2);
  make_map(&p.tv, v, SEQ, HHD, 128, 2);
  make_map(&p.tl, qkvb, SEQ / 2, 6 * DM, 64, 1);
  make_map(&p.th, qkvb, SEQ / 2, 6 * DM, 72, 1);
  make_map(&p.to, ctx, SEQ, HHD, 128, 2);
  p.ob = ob;
  p.qkvb = qkvb;
  mega_kernel<<<NCTA, 384, SMEM_BYTES, cudaStreamPerThread>>>(p);
}
```

```cpp
#include <cuda_runtime.h>
#include <cuda_bf16.h>
#include <cuda.h>
#include <stdint.h>
#include <string.h>

namespace {

typedef __nv_bfloat16 bf16;

constexpr int SEQ = 2048;
constexpr int NHEAD = 32;
constexpr int HD = 128;
constexpr int DM = 1024;
constexpr int DC = 512;
constexpr int HHD = NHEAD * HD;

__device__ __align__(1024) bf16 g_q[SEQ * HHD];
__device__ __align__(1024) bf16 g_k[SEQ * HHD];
__device__ __align__(1024) bf16 g_v[SEQ * HHD];
__device__ __align__(1024) bf16 g_ctx[SEQ * HHD];
__device__ __align__(1024) bf16 g_qkvb[SEQ * 3 * DM];
__device__ __align__(1024) bf16 g_ob[SEQ * DM];
constexpr int CNT_QKV = 0, CNT_CTX = 16, CNT_QKVB = 32, CNT_DONE = 33, CNT_QUEUE = 34, CNT_OB = 35, CNT_N = 39;
__device__ uint32_t g_cnt[CNT_N * 8];

__device__ __forceinline__ uint32_t smem_u32(const void* p) {
  return static_cast<uint32_t>(__cvta_generic_to_shared(p));
}
__device__ __forceinline__ void mbar_init(uint32_t bar, uint32_t count) {
  asm volatile("mbarrier.init.shared::cta.b64 [%0], %1;" ::"r"(bar), "r"(count) : "memory");
}
__device__ __forceinline__ void mbar_expect_tx(uint32_t bar, uint32_t bytes) {
  asm volatile("mbarrier.arrive.expect_tx.shared::cta.b64 _, [%0], %1;" ::"r"(bar), "r"(bytes) : "memory");
}
__device__ __forceinline__ void mbar_arrive(uint32_t bar) {
  asm volatile("mbarrier.arrive.shared::cta.b64 _, [%0];" ::"r"(bar) : "memory");
}
__device__ __forceinline__ void mbar_arrive_if(uint32_t bar, bool on) {
  asm volatile("{\n.reg .pred p;\nsetp.ne.b32 p, %1, 0;\n@p mbarrier.arrive.shared::cta.b64 _, [%0];\n}" ::"r"(bar),
               "r"((int)on)
               : "memory");
}
__device__ __forceinline__ void mbar_arrive_cluster_if(uint32_t bar, uint32_t cta, bool on) {
  asm volatile(
      "{\n.reg .b32 ra;\n.reg .pred p;\nsetp.ne.b32 p, %2, 0;\nmapa.shared::cluster.u32 ra, %0, %1;\n"
      "@p mbarrier.arrive.shared::cluster.b64 _, [ra];\n}" ::"r"(bar),
      "r"(cta), "r"((int)on)
      : "memory");
}
__device__ __forceinline__ void mbar_arrive_cluster(uint32_t bar, uint32_t cta) {
  asm volatile(
      "{\n.reg .b32 ra;\nmapa.shared::cluster.u32 ra, %0, %1;\n"
      "mbarrier.arrive.shared::cluster.b64 _, [ra];\n}" ::"r"(bar),
      "r"(cta)
      : "memory");
}
__device__ __forceinline__ bool mbar_try_wait(uint32_t bar, uint32_t parity) {
  uint32_t ok;
  asm volatile(
      "{\n.reg .pred p;\nmbarrier.try_wait.parity.shared::cta.b64 p, [%1], %2;\nselp.u32 %0, 1, 0, p;\n}"
      : "=r"(ok)
      : "r"(bar), "r"(parity)
      : "memory");
  return ok != 0;
}
__device__ __forceinline__ bool mbar_test(uint32_t bar, uint32_t parity) {
  uint32_t ok;
  asm volatile(
      "{\n.reg .pred p;\nmbarrier.test_wait.parity.shared::cta.b64 p, [%1], %2;\nselp.u32 %0, 1, 0, p;\n}"
      : "=r"(ok)
      : "r"(bar), "r"(parity)
      : "memory");
  return ok != 0;
}
#define DBG(i, v)
__device__ __forceinline__ void mbar_wait(uint32_t bar, uint32_t parity) {
  asm volatile(
      "{\n.reg .pred p;\n.reg .u32 t;\n"
      "mbarrier.try_wait.parity.shared::cta.b64 p, [%0], %1;\n"
      "@p bra DONE;\n"
      "mov.u32 t, 0x100000;\n"
      "LAB_WAIT:\n"
      "mbarrier.try_wait.parity.shared::cta.b64 p, [%0], %1;\n"
      "@p bra DONE;\n"
      "sub.u32 t, t, 1;\n"
      "setp.ne.u32 p, t, 0;\n"
      "@p bra LAB_WAIT;\n"
      "trap;\n"
      "DONE:\n}" ::"r"(bar),
      "r"(parity)
      : "memory");
}
constexpr uint64_t EV_NORMAL = 0x1000000000000000ull, EV_FIRST = 0x12F0000000000000ull;
__device__ __forceinline__ void tma_load_3d(uint32_t dst, const CUtensorMap* map, int c0, int c1, int c2,
                                            uint32_t bar, uint64_t hint) {
  asm volatile(
      "cp.async.bulk.tensor.3d.shared::cluster.global.mbarrier::complete_tx::bytes.L2::cache_hint [%0], [%1, {%3, %4, %5}], [%2], %6;" ::"r"(dst),
      "l"(map), "r"(bar), "r"(c0), "r"(c1), "r"(c2), "l"(hint)
      : "memory");
}
__device__ __forceinline__ void tma_load_3d_mc(uint32_t dst, const CUtensorMap* map, int c0, int c1, int c2,
                                               uint32_t bar, uint16_t mask, uint64_t hint) {
  asm volatile(
      "cp.async.bulk.tensor.3d.shared::cluster.global.mbarrier::complete_tx::bytes.multicast::cluster.L2::cache_hint [%0], [%1, {%3, %4, %5}], [%2], %6, %7;" ::"r"(dst),
      "l"(map), "r"(bar), "r"(c0), "r"(c1), "r"(c2), "h"(mask), "l"(hint)
      : "memory");
}
__device__ __forceinline__ void tma_prefetch_3d(const CUtensorMap* map, int c0, int c1, int c2) {
  asm volatile("cp.async.bulk.prefetch.tensor.3d.L2.global.tile [%0, {%1, %2, %3}];" ::"l"(map), "r"(c0), "r"(c1), "r"(c2)
               : "memory");
}
__device__ __forceinline__ void tma_store_3d(const CUtensorMap* map, uint32_t src, int c0, int c1, int c2, uint64_t hint) {
  asm volatile("cp.async.bulk.tensor.3d.global.shared::cta.bulk_group.L2::cache_hint [%0, {%2, %3, %4}], [%1], %5;" ::"l"(map),
               "r"(src), "r"(c0), "r"(c1), "r"(c2), "l"(hint)
               : "memory");
}
__device__ __forceinline__ void bulk_commit() { asm volatile("cp.async.bulk.commit_group;" ::: "memory"); }
template <int N>
__device__ __forceinline__ void bulk_wait_read() {
  asm volatile("cp.async.bulk.wait_group.read %0;" ::"n"(N) : "memory");
}
template <int N>
__device__ __forceinline__ void bulk_wait() {
  asm volatile("cp.async.bulk.wait_group %0;" ::"n"(N) : "memory");
}
__device__ __forceinline__ void fence_proxy_async_smem() {
  asm volatile("fence.proxy.async.shared::cta;" ::: "memory");
}
__device__ __forceinline__ void prefetch_tmap(const CUtensorMap* map) {
  asm volatile("prefetch.tensormap [%0];" ::"l"(map) : "memory");
}
__device__ __forceinline__ void cluster_sync_all() {
  asm volatile("barrier.cluster.arrive.relaxed.aligned;\nbarrier.cluster.wait.acquire.aligned;" ::: "memory");
}
__device__ __forceinline__ uint32_t cluster_ctarank() {
  uint32_t r;
  asm volatile("mov.u32 %0, %%cluster_ctarank;" : "=r"(r));
  return r;
}
__device__ __forceinline__ bool elect_one() {
  uint32_t pred;
  asm volatile("{\n.reg .pred P;\nelect.sync _|P, 0xffffffff;\nselp.b32 %0, 1, 0, P;\n}" : "=r"(pred));
  return pred != 0;
}
__device__ __forceinline__ void named_bar_sync(int id, int n) {
  asm volatile("bar.sync %0, %1;" ::"r"(id), "r"(n) : "memory");
}
__device__ __forceinline__ void named_bar_arrive(int id, int n) {
  asm volatile("bar.arrive %0, %1;" ::"r"(id), "r"(n) : "memory");
}
__device__ __forceinline__ void named_bar_sync_if(int id, int n, bool on) {
  asm volatile("{\n.reg .pred p;\nsetp.ne.b32 p, %2, 0;\n@p bar.sync %0, %1;\n}" ::"r"(id), "r"(n), "r"((int)on) : "memory");
}
__device__ __forceinline__ void named_bar_arrive_if(int id, int n, bool on) {
  asm volatile("{\n.reg .pred p;\nsetp.ne.b32 p, %2, 0;\n@p bar.arrive %0, %1;\n}" ::"r"(id), "r"(n), "r"((int)on) : "memory");
}
template <int N>
__device__ __forceinline__ void reg_alloc() {
  asm volatile("setmaxnreg.inc.sync.aligned.u32 %0;" ::"n"(N));
}
template <int N>
__device__ __forceinline__ void reg_dealloc() {
  asm volatile("setmaxnreg.dec.sync.aligned.u32 %0;" ::"n"(N));
}
__device__ __forceinline__ void wgmma_fence() { asm volatile("wgmma.fence.sync.aligned;" ::: "memory"); }
__device__ __forceinline__ void wgmma_commit() { asm volatile("wgmma.commit_group.sync.aligned;" ::: "memory"); }
template <int N>
__device__ __forceinline__ void wgmma_wait() {
  asm volatile("wgmma.wait_group.sync.aligned %0;" ::"n"(N) : "memory");
}
template <int N>
__device__ __forceinline__ void fence_regs(float (&d)[N]) {
#pragma unroll
  for (int i = 0; i < N; i++) asm volatile("" : "+f"(d[i])::"memory");
}
__device__ __forceinline__ void fence_regs(uint32_t (&d)[32]) {
#pragma unroll
  for (int i = 0; i < 16; i++) asm volatile("" : "+r"(d[i])::"memory");
}
template <int N>
__device__ __forceinline__ void undef_regs(float (&d)[N]) {
#pragma unroll
  for (int i = 0; i < N; i++) d[i] = 0.f;
}
template <int N>
__device__ __forceinline__ void undef_regs(uint32_t (&d)[N]) {
#pragma unroll
  for (int i = 0; i < N; i++) d[i] = 0u;
}
__device__ __forceinline__ void sched_fence(float x) {
  asm volatile("{\n.reg .pred p;\nsetp.lt.f32 p, %0, 0f00000000;\n@p trap;\n}" ::"f"(x) : "memory");
}
__device__ __forceinline__ uint32_t pack_bf16(float lo, float hi) {
  uint32_t r;
  asm("cvt.rn.bf16x2.f32 %0, %1, %2;" : "=r"(r) : "f"(hi), "f"(lo));
  return r;
}
__device__ __forceinline__ void stmatrix_x4(uint32_t addr, uint32_t r0, uint32_t r1, uint32_t r2, uint32_t r3) {
  asm volatile("stmatrix.sync.aligned.m8n8.x4.shared.b16 [%0], {%1, %2, %3, %4};" ::"r"(addr), "r"(r0), "r"(r1),
               "r"(r2), "r"(r3)
               : "memory");
}
__device__ __forceinline__ void stmatrix_x4_p(uint32_t addr, uint32_t r0, uint32_t r1, uint32_t r2, uint32_t r3,
                                              bool on) {
  asm volatile("{\n.reg .pred p;\nsetp.ne.b32 p, %5, 0;\n@p stmatrix.sync.aligned.m8n8.x4.shared.b16 [%0], {%1, %2, %3, %4};\n}" ::"r"(addr),
               "r"(r0), "r"(r1), "r"(r2), "r"(r3), "r"((int)on)
               : "memory");
}
__device__ __forceinline__ float ex2(float x) {
  float y;
  asm("ex2.approx.ftz.f32 %0, %1;" : "=f"(y) : "f"(x));
  return y;
}
__device__ __forceinline__ float rcp(float x) {
  float y;
  asm("rcp.approx.ftz.f32 %0, %1;" : "=f"(y) : "f"(x));
  return y;
}
#define BBV 0
__device__ __forceinline__ float ex2v(float x) {
  float y;
  asm volatile("ex2.approx.ftz.f32 %0, %1;" : "=f"(y) : "f"(x));
  return y;
}
__device__ __forceinline__ void ex2_over(float& y, float x, uint32_t k) {
  asm volatile("{\n.reg .pred p;\nsetp.ne.u32 p, %2, 0x7fffffff;\n@p ex2.approx.ftz.f32 %0, %1;\n}" : "+f"(y) : "f"(x), "r"(k));
}
__device__ __forceinline__ float addv(float a, float b) {
  float y;
  asm volatile("add.f32 %0, %1, %2;" : "=f"(y) : "f"(a), "f"(b));
  return y;
}
__device__ __forceinline__ uint32_t packv(float lo, float hi) {
  uint32_t r;
  asm volatile("cvt.rn.bf16x2.f32 %0, %1, %2;" : "=r"(r) : "f"(hi), "f"(lo));
  return r;
}
__device__ __forceinline__ float maskv(float x, int lim, int col) {
  float y;
  asm volatile("{\n.reg .pred p;\nsetp.ge.s32 p, %2, %3;\nselp.f32 %0, %1, 0fFF800000, p;\n}" : "=f"(y) : "f"(x), "r"(lim), "r"(col));
  return y;
}
__device__ __forceinline__ void bb_split(uint32_t x, uint32_t k) {
  asm volatile("{\n.reg .pred p;\nsetp.eq.u32 p, %0, %1;\n@p trap;\n}" ::"r"(x), "r"(0x7fffff00u + k));
}
__device__ __forceinline__ void mbar_arrive_elect(uint32_t bar, bool on) {
  asm volatile("{\n.reg .pred p, q;\nelect.sync _|q, 0xffffffff;\nsetp.ne.and.b32 p, %1, 0, q;\n@p mbarrier.arrive.shared::cta.b64 _, [%0];\n}" ::"r"(bar),
               "r"((int)on)
               : "memory");
}
__device__ __forceinline__ float mbar_test2(uint32_t bar0, uint32_t par0, uint32_t bar1, uint32_t par1) {
  float f;
  asm volatile(
      "{\n.reg .pred p, q;\nmbarrier.test_wait.parity.shared::cta.b64 p, [%1], %2;\n"
      "mbarrier.test_wait.parity.shared::cta.b64 q, [%3], %4;\nand.pred p, p, q;\nselp.f32 %0, 0f00000000, 0f80000000, p;\n}"
      : "=f"(f)
      : "r"(bar0), "r"(par0), "r"(bar1), "r"(par1)
      : "memory");
  return f;
}
__device__ __forceinline__ void mbar_wait_rest(uint32_t bar, uint32_t parity, bool ok) {
  asm volatile(
      "{\n.reg .pred p;\n.reg .u32 t;\n"
      "setp.ne.b32 p, %2, 0;\n"
      "@p bra DONE;\n"
      "mov.u32 t, 0x100000;\n"
      "LAB_WAIT:\n"
      "mbarrier.try_wait.parity.shared::cta.b64 p, [%0], %1;\n"
      "@p bra DONE;\n"
      "sub.u32 t, t, 1;\n"
      "setp.ne.u32 p, t, 0;\n"
      "@p bra LAB_WAIT;\n"
      "trap;\n"
      "DONE:\n}" ::"r"(bar),
      "r"(parity), "r"((int)ok)
      : "memory");
}
__device__ __forceinline__ void cnt_signal(int idx, uint32_t inc = 1) {
  asm volatile("red.release.gpu.global.add.u32 [%0], %1;" ::"l"(g_cnt + idx * 8), "r"(inc) : "memory");
}
__device__ __forceinline__ void cnt_signal_done(int idx, uint32_t inc = 1) {
  asm volatile("red.relaxed.gpu.global.add.u32 [%0], %1;" ::"l"(g_cnt + idx * 8), "r"(inc) : "memory");
}
__device__ __forceinline__ uint32_t cnt_next(int idx) {
  uint32_t v;
  asm volatile("atom.relaxed.gpu.global.add.u32 %0, [%1], 1;" : "=r"(v) : "l"(g_cnt + idx * 8) : "memory");
  return v;
}
__device__ __forceinline__ uint32_t cnt_peek(int idx) {
  uint32_t v;
  asm volatile("ld.acquire.gpu.global.u32 %0, [%1];" : "=r"(v) : "l"(g_cnt + idx * 8) : "memory");
  return v;
}
__device__ __forceinline__ void cnt_wait(int idx, uint32_t target) {
  asm volatile(
      "{\n.reg .pred p;\n.reg .u32 v, t0, t1;\n"
      "ld.acquire.gpu.global.u32 v, [%0];\n"
      "setp.ge.u32 p, v, %1;\n"
      "@p bra DONE;\n"
      "mov.u32 t0, %%clock;\n"
      "LAB_WAIT:\n"
      "nanosleep.u32 100;\n"
      "ld.acquire.gpu.global.u32 v, [%0];\n"
      "setp.ge.u32 p, v, %1;\n"
      "@p bra DONE;\n"
      "mov.u32 t1, %%clock;\n"
      "sub.u32 t1, t1, t0;\n"
      "setp.lt.u32 p, t1, 0x80000000;\n"
      "@p bra LAB_WAIT;\n"
      "trap;\n"
      "DONE:\n}" ::"l"(g_cnt + idx * 8),
      "r"(target)
      : "memory");
}
__device__ __forceinline__ void cnt_wait_bit(int idx, uint32_t bit, uint32_t& v) {
  asm volatile(
      "{\n.reg .pred p;\n.reg .u32 x, t0, t1;\n"
      "and.b32 x, %0, %2;\n"
      "setp.ne.u32 p, x, 0;\n"
      "@p bra DONE;\n"
      "mov.u32 t0, %%clock;\n"
      "LAB_WAIT:\n"
      "ld.acquire.gpu.global.u32 %0, [%1];\n"
      "and.b32 x, %0, %2;\n"
      "setp.ne.u32 p, x, 0;\n"
      "@p bra DONE;\n"
      "nanosleep.u32 64;\n"
      "mov.u32 t1, %%clock;\n"
      "sub.u32 t1, t1, t0;\n"
      "setp.lt.u32 p, t1, 0x80000000;\n"
      "@p bra LAB_WAIT;\n"
      "trap;\n"
      "DONE:\n}" : "+r"(v) : "l"(g_cnt + idx * 8),
      "r"(bit)
      : "memory");
}
__device__ __forceinline__ bool cnt_done(uint32_t total) {
  uint32_t old;
  asm volatile("atom.acq_rel.gpu.global.add.u32 %0, [%1], 1;" : "=r"(old) : "l"(g_cnt + CNT_DONE * 8) : "memory");
  return old == total - 1;
}
__device__ __forceinline__ void cnt_rearm() {
#pragma unroll
  for (int i = 0; i < CNT_N; i++) g_cnt[i * 8] = 0;
}
__device__ __forceinline__ void fence_proxy_async_global() { asm volatile("fence.proxy.async.global;" ::: "memory"); }
__device__ __forceinline__ void mma_16816(float (&c)[4], uint32_t a0, uint32_t a1, uint32_t a2, uint32_t a3,
                                          uint32_t b0, uint32_t b1) {
  asm("mma.sync.aligned.m16n8k16.row.col.f32.bf16.bf16.f32 {%0, %1, %2, %3}, {%4, %5, %6, %7}, {%8, %9}, {%0, %1, %2, %3};"
      : "+f"(c[0]), "+f"(c[1]), "+f"(c[2]), "+f"(c[3])
      : "r"(a0), "r"(a1), "r"(a2), "r"(a3), "r"(b0), "r"(b1));
}
__device__ __forceinline__ void mma_1688(float (&c)[4], uint32_t a0, uint32_t a1, uint32_t b0) {
  asm("mma.sync.aligned.m16n8k8.row.col.f32.bf16.bf16.f32 {%0, %1, %2, %3}, {%4, %5}, {%6}, {%0, %1, %2, %3};"
      : "+f"(c[0]), "+f"(c[1]), "+f"(c[2]), "+f"(c[3])
      : "r"(a0), "r"(a1), "r"(b0));
}
__device__ __forceinline__ uint32_t movm_t(uint32_t a) {
  uint32_t d;
  asm("movmatrix.sync.aligned.m8n8.trans.b16 %0, %1;" : "=r"(d) : "r"(a));
  return d;
}
__device__ __forceinline__ uint4 ldg128(const bf16* p) {
  uint4 v;
  asm volatile("ld.global.v4.u32 {%0, %1, %2, %3}, [%4];" : "=r"(v.x), "=r"(v.y), "=r"(v.z), "=r"(v.w) : "l"(p) : "memory");
  return v;
}
#define TL(role, code)
#define TL0(code)
#define TL_DECL
#define TR_DECL
#define TR(code)
#define TRI(id, code)
#define TW_DECL
#define TW(w, stmt) stmt
#define TW_FLUSH()
#define TW_END()

__device__ __forceinline__ uint32_t make_desc(uint32_t addr, uint32_t lbo_bytes) {
  return (addr >> 4) + ((lbo_bytes >> 4) << 16);
}

__device__ __forceinline__ void wgmma_ss_n256_tb(float (&d)[128], uint32_t da, uint32_t db, int scale_d) {
  asm volatile("{\n.reg .pred p;\n.reg .b64 a, b;\nsetp.ne.b32 p, %130, 0;\nmov.b64 a, {%128, 0x40000040};\nmov.b64 b, {%129, 0x40000040};\n"
    "wgmma.mma_async.sync.aligned.m64n256k16.f32.bf16.bf16 {%0, %1, %2, %3, %4, %5, %6, %7, %8, %9, %10, %11, %12, %13, %14, %15, %16, %17, %18, %19, %20, %21, %22, %23, %24, %25, %26, %27, %28, %29, %30, %31, %32, %33, %34, %35, %36, %37, %38, %39, %40, %41, %42, %43, %44, %45, %46, %47, %48, %49, %50, %51, %52, %53, %54, %55, %56, %57, %58, %59, %60, %61, %62, %63, %64, %65, %66, %67, %68, %69, %70, %71, %72, %73, %74, %75, %76, %77, %78, %79, %80, %81, %82, %83, %84, %85, %86, %87, %88, %89, %90, %91, %92, %93, %94, %95, %96, %97, %98, %99, %100, %101, %102, %103, %104, %105, %106, %107, %108, %109, %110, %111, %112, %113, %114, %115, %116, %117, %118, %119, %120, %121, %122, %123, %124, %125, %126, %127}, a, b, p, 1, 1, 0, 1;\n}\n"
    : "+f"(d[0]), "+f"(d[1]), "+f"(d[2]), "+f"(d[3]), "+f"(d[4]), "+f"(d[5]), "+f"(d[6]), "+f"(d[7]), "+f"(d[8]), "+f"(d[9]), "+f"(d[10]), "+f"(d[11]), "+f"(d[12]), "+f"(d[13]), "+f"(d[14]), "+f"(d[15]), "+f"(d[16]), "+f"(d[17]), "+f"(d[18]), "+f"(d[19]), "+f"(d[20]), "+f"(d[21]), "+f"(d[22]), "+f"(d[23]), "+f"(d[24]), "+f"(d[25]), "+f"(d[26]), "+f"(d[27]), "+f"(d[28]), "+f"(d[29]), "+f"(d[30]), "+f"(d[31]), "+f"(d[32]), "+f"(d[33]), "+f"(d[34]), "+f"(d[35]), "+f"(d[36]), "+f"(d[37]), "+f"(d[38]), "+f"(d[39]), "+f"(d[40]), "+f"(d[41]), "+f"(d[42]), "+f"(d[43]), "+f"(d[44]), "+f"(d[45]), "+f"(d[46]), "+f"(d[47]), "+f"(d[48]), "+f"(d[49]), "+f"(d[50]), "+f"(d[51]), "+f"(d[52]), "+f"(d[53]), "+f"(d[54]), "+f"(d[55]), "+f"(d[56]), "+f"(d[57]), "+f"(d[58]), "+f"(d[59]), "+f"(d[60]), "+f"(d[61]), "+f"(d[62]), "+f"(d[63]), "+f"(d[64]), "+f"(d[65]), "+f"(d[66]), "+f"(d[67]), "+f"(d[68]), "+f"(d[69]), "+f"(d[70]), "+f"(d[71]), "+f"(d[72]), "+f"(d[73]), "+f"(d[74]), "+f"(d[75]), "+f"(d[76]), "+f"(d[77]), "+f"(d[78]), "+f"(d[79]), "+f"(d[80]), "+f"(d[81]), "+f"(d[82]), "+f"(d[83]), "+f"(d[84]), "+f"(d[85]), "+f"(d[86]), "+f"(d[87]), "+f"(d[88]), "+f"(d[89]), "+f"(d[90]), "+f"(d[91]), "+f"(d[92]), "+f"(d[93]), "+f"(d[94]), "+f"(d[95]), "+f"(d[96]), "+f"(d[97]), "+f"(d[98]), "+f"(d[99]), "+f"(d[100]), "+f"(d[101]), "+f"(d[102]), "+f"(d[103]), "+f"(d[104]), "+f"(d[105]), "+f"(d[106]), "+f"(d[107]), "+f"(d[108]), "+f"(d[109]), "+f"(d[110]), "+f"(d[111]), "+f"(d[112]), "+f"(d[113]), "+f"(d[114]), "+f"(d[115]), "+f"(d[116]), "+f"(d[117]), "+f"(d[118]), "+f"(d[119]), "+f"(d[120]), "+f"(d[121]), "+f"(d[122]), "+f"(d[123]), "+f"(d[124]), "+f"(d[125]), "+f"(d[126]), "+f"(d[127])
    : "r"(da), "r"(db), "r"(scale_d));
}
__device__ __forceinline__ void wgmma_ss_n128(float (&d)[64], uint32_t da, uint32_t db, int scale_d) {
  asm volatile("{\n.reg .pred p;\n.reg .b64 a, b;\nsetp.ne.b32 p, %66, 0;\nmov.b64 a, {%64, 0x40000040};\nmov.b64 b, {%65, 0x40000040};\n"
    "wgmma.mma_async.sync.aligned.m64n128k16.f32.bf16.bf16 {%0, %1, %2, %3, %4, %5, %6, %7, %8, %9, %10, %11, %12, %13, %14, %15, %16, %17, %18, %19, %20, %21, %22, %23, %24, %25, %26, %27, %28, %29, %30, %31, %32, %33, %34, %35, %36, %37, %38, %39, %40, %41, %42, %43, %44, %45, %46, %47, %48, %49, %50, %51, %52, %53, %54, %55, %56, %57, %58, %59, %60, %61, %62, %63}, a, b, p, 1, 1, 0, 0;\n}\n"
    : "+f"(d[0]), "+f"(d[1]), "+f"(d[2]), "+f"(d[3]), "+f"(d[4]), "+f"(d[5]), "+f"(d[6]), "+f"(d[7]), "+f"(d[8]), "+f"(d[9]), "+f"(d[10]), "+f"(d[11]), "+f"(d[12]), "+f"(d[13]), "+f"(d[14]), "+f"(d[15]), "+f"(d[16]), "+f"(d[17]), "+f"(d[18]), "+f"(d[19]), "+f"(d[20]), "+f"(d[21]), "+f"(d[22]), "+f"(d[23]), "+f"(d[24]), "+f"(d[25]), "+f"(d[26]), "+f"(d[27]), "+f"(d[28]), "+f"(d[29]), "+f"(d[30]), "+f"(d[31]), "+f"(d[32]), "+f"(d[33]), "+f"(d[34]), "+f"(d[35]), "+f"(d[36]), "+f"(d[37]), "+f"(d[38]), "+f"(d[39]), "+f"(d[40]), "+f"(d[41]), "+f"(d[42]), "+f"(d[43]), "+f"(d[44]), "+f"(d[45]), "+f"(d[46]), "+f"(d[47]), "+f"(d[48]), "+f"(d[49]), "+f"(d[50]), "+f"(d[51]), "+f"(d[52]), "+f"(d[53]), "+f"(d[54]), "+f"(d[55]), "+f"(d[56]), "+f"(d[57]), "+f"(d[58]), "+f"(d[59]), "+f"(d[60]), "+f"(d[61]), "+f"(d[62]), "+f"(d[63])
    : "r"(da), "r"(db), "r"(scale_d));
}
__device__ __forceinline__ void wgmma_ss_n64(float (&d)[32], uint32_t da, uint32_t db, int scale_d) {
  asm volatile("{\n.reg .pred p;\n.reg .b64 a, b;\nsetp.ne.b32 p, %34, 0;\nmov.b64 a, {%32, 0x40000040};\nmov.b64 b, {%33, 0x40000040};\n"
    "wgmma.mma_async.sync.aligned.m64n64k16.f32.bf16.bf16 {%0, %1, %2, %3, %4, %5, %6, %7, %8, %9, %10, %11, %12, %13, %14, %15, %16, %17, %18, %19, %20, %21, %22, %23, %24, %25, %26, %27, %28, %29, %30, %31}, a, b, p, 1, 1, 0, 0;\n}\n"
    : "+f"(d[0]), "+f"(d[1]), "+f"(d[2]), "+f"(d[3]), "+f"(d[4]), "+f"(d[5]), "+f"(d[6]), "+f"(d[7]), "+f"(d[8]), "+f"(d[9]), "+f"(d[10]), "+f"(d[11]), "+f"(d[12]), "+f"(d[13]), "+f"(d[14]), "+f"(d[15]), "+f"(d[16]), "+f"(d[17]), "+f"(d[18]), "+f"(d[19]), "+f"(d[20]), "+f"(d[21]), "+f"(d[22]), "+f"(d[23]), "+f"(d[24]), "+f"(d[25]), "+f"(d[26]), "+f"(d[27]), "+f"(d[28]), "+f"(d[29]), "+f"(d[30]), "+f"(d[31])
    : "r"(da), "r"(db), "r"(scale_d));
}
__device__ __forceinline__ void wgmma_rs_n128_tb(float (&d)[64], uint32_t a0, uint32_t a1, uint32_t a2, uint32_t a3, uint32_t db, int scale_d) {
  asm volatile("{\n.reg .pred p;\n.reg .b64 b;\nsetp.ne.b32 p, %69, 0;\nmov.b64 b, {%68, 0x40000040};\n"
    "wgmma.mma_async.sync.aligned.m64n128k16.f32.bf16.bf16 {%0, %1, %2, %3, %4, %5, %6, %7, %8, %9, %10, %11, %12, %13, %14, %15, %16, %17, %18, %19, %20, %21, %22, %23, %24, %25, %26, %27, %28, %29, %30, %31, %32, %33, %34, %35, %36, %37, %38, %39, %40, %41, %42, %43, %44, %45, %46, %47, %48, %49, %50, %51, %52, %53, %54, %55, %56, %57, %58, %59, %60, %61, %62, %63}, {%64, %65, %66, %67}, b, p, 1, 1, 1;\n}\n"
    : "+f"(d[0]), "+f"(d[1]), "+f"(d[2]), "+f"(d[3]), "+f"(d[4]), "+f"(d[5]), "+f"(d[6]), "+f"(d[7]), "+f"(d[8]), "+f"(d[9]), "+f"(d[10]), "+f"(d[11]), "+f"(d[12]), "+f"(d[13]), "+f"(d[14]), "+f"(d[15]), "+f"(d[16]), "+f"(d[17]), "+f"(d[18]), "+f"(d[19]), "+f"(d[20]), "+f"(d[21]), "+f"(d[22]), "+f"(d[23]), "+f"(d[24]), "+f"(d[25]), "+f"(d[26]), "+f"(d[27]), "+f"(d[28]), "+f"(d[29]), "+f"(d[30]), "+f"(d[31]), "+f"(d[32]), "+f"(d[33]), "+f"(d[34]), "+f"(d[35]), "+f"(d[36]), "+f"(d[37]), "+f"(d[38]), "+f"(d[39]), "+f"(d[40]), "+f"(d[41]), "+f"(d[42]), "+f"(d[43]), "+f"(d[44]), "+f"(d[45]), "+f"(d[46]), "+f"(d[47]), "+f"(d[48]), "+f"(d[49]), "+f"(d[50]), "+f"(d[51]), "+f"(d[52]), "+f"(d[53]), "+f"(d[54]), "+f"(d[55]), "+f"(d[56]), "+f"(d[57]), "+f"(d[58]), "+f"(d[59]), "+f"(d[60]), "+f"(d[61]), "+f"(d[62]), "+f"(d[63])
    : "r"(a0), "r"(a1), "r"(a2), "r"(a3), "r"(db), "r"(scale_d));
}
__device__ __forceinline__ void wgmma_ss_n72_init(float (&d)[36], uint32_t da, uint32_t db) {
  asm volatile("{\n.reg .pred p;\n.reg .b64 a, b;\nsetp.ne.b32 p, 0, 0;\nmov.b64 a, {%36, 0x40000040};\nmov.b64 b, {%37, 0x40000040};\n"
    "wgmma.mma_async.sync.aligned.m64n72k16.f32.bf16.bf16 {%0, %1, %2, %3, %4, %5, %6, %7, %8, %9, %10, %11, %12, %13, %14, %15, %16, %17, %18, %19, %20, %21, %22, %23, %24, %25, %26, %27, %28, %29, %30, %31, %32, %33, %34, %35}, a, b, p, 1, 1, 0, 0;\n}\n"
    : "=f"(d[0]), "=f"(d[1]), "=f"(d[2]), "=f"(d[3]), "=f"(d[4]), "=f"(d[5]), "=f"(d[6]), "=f"(d[7]), "=f"(d[8]), "=f"(d[9]), "=f"(d[10]), "=f"(d[11]), "=f"(d[12]), "=f"(d[13]), "=f"(d[14]), "=f"(d[15]), "=f"(d[16]), "=f"(d[17]), "=f"(d[18]), "=f"(d[19]), "=f"(d[20]), "=f"(d[21]), "=f"(d[22]), "=f"(d[23]), "=f"(d[24]), "=f"(d[25]), "=f"(d[26]), "=f"(d[27]), "=f"(d[28]), "=f"(d[29]), "=f"(d[30]), "=f"(d[31]), "=f"(d[32]), "=f"(d[33]), "=f"(d[34]), "=f"(d[35])
    : "r"(da), "r"(db));
}
__device__ __forceinline__ void wgmma_ss_n72(float (&d)[36], uint32_t da, uint32_t db, int scale_d) {
  asm volatile("{\n.reg .pred p;\n.reg .b64 a, b;\nsetp.ne.b32 p, %38, 0;\nmov.b64 a, {%36, 0x40000040};\nmov.b64 b, {%37, 0x40000040};\n"
    "wgmma.mma_async.sync.aligned.m64n72k16.f32.bf16.bf16 {%0, %1, %2, %3, %4, %5, %6, %7, %8, %9, %10, %11, %12, %13, %14, %15, %16, %17, %18, %19, %20, %21, %22, %23, %24, %25, %26, %27, %28, %29, %30, %31, %32, %33, %34, %35}, a, b, p, 1, 1, 0, 0;\n}\n"
    : "+f"(d[0]), "+f"(d[1]), "+f"(d[2]), "+f"(d[3]), "+f"(d[4]), "+f"(d[5]), "+f"(d[6]), "+f"(d[7]), "+f"(d[8]), "+f"(d[9]), "+f"(d[10]), "+f"(d[11]), "+f"(d[12]), "+f"(d[13]), "+f"(d[14]), "+f"(d[15]), "+f"(d[16]), "+f"(d[17]), "+f"(d[18]), "+f"(d[19]), "+f"(d[20]), "+f"(d[21]), "+f"(d[22]), "+f"(d[23]), "+f"(d[24]), "+f"(d[25]), "+f"(d[26]), "+f"(d[27]), "+f"(d[28]), "+f"(d[29]), "+f"(d[30]), "+f"(d[31]), "+f"(d[32]), "+f"(d[33]), "+f"(d[34]), "+f"(d[35])
    : "r"(da), "r"(db), "r"(scale_d));
}
__device__ __forceinline__ void wgmma_rs_n32_tb_init(float (&d)[16], uint32_t a0, uint32_t a1, uint32_t a2, uint32_t a3, uint32_t db) {
  asm volatile("{\n.reg .pred p;\n.reg .b64 b;\nsetp.ne.b32 p, 0, 0;\nmov.b64 b, {%20, 0x40000040};\n"
    "wgmma.mma_async.sync.aligned.m64n32k16.f32.bf16.bf16 {%0, %1, %2, %3, %4, %5, %6, %7, %8, %9, %10, %11, %12, %13, %14, %15}, {%16, %17, %18, %19}, b, p, 1, 1, 1;\n}\n"
    : "=f"(d[0]), "=f"(d[1]), "=f"(d[2]), "=f"(d[3]), "=f"(d[4]), "=f"(d[5]), "=f"(d[6]), "=f"(d[7]), "=f"(d[8]), "=f"(d[9]), "=f"(d[10]), "=f"(d[11]), "=f"(d[12]), "=f"(d[13]), "=f"(d[14]), "=f"(d[15])
    : "r"(a0), "r"(a1), "r"(a2), "r"(a3), "r"(db));
}
__device__ __forceinline__ void wgmma_rs_n32_tb(float (&d)[16], uint32_t a0, uint32_t a1, uint32_t a2, uint32_t a3, uint32_t db, int scale_d) {
  asm volatile("{\n.reg .pred p;\n.reg .b64 b;\nsetp.ne.b32 p, %21, 0;\nmov.b64 b, {%20, 0x40000040};\n"
    "wgmma.mma_async.sync.aligned.m64n32k16.f32.bf16.bf16 {%0, %1, %2, %3, %4, %5, %6, %7, %8, %9, %10, %11, %12, %13, %14, %15}, {%16, %17, %18, %19}, b, p, 1, 1, 1;\n}\n"
    : "+f"(d[0]), "+f"(d[1]), "+f"(d[2]), "+f"(d[3]), "+f"(d[4]), "+f"(d[5]), "+f"(d[6]), "+f"(d[7]), "+f"(d[8]), "+f"(d[9]), "+f"(d[10]), "+f"(d[11]), "+f"(d[12]), "+f"(d[13]), "+f"(d[14]), "+f"(d[15])
    : "r"(a0), "r"(a1), "r"(a2), "r"(a3), "r"(db), "r"(scale_d));
}
template <int OA, int OB>
__device__ __forceinline__ void wgmma_ss_n128_tb(float (&d)[64], uint32_t da, uint32_t db, int scale_d) {
  asm volatile("{\n.reg .pred p;\n.reg .b64 a, b;\n.reg .b32 x, y;\nsetp.ne.b32 p, %66, 0;\nadd.u32 x, %64, %67;\nadd.u32 y, %65, %68;\nmov.b64 a, {x, 0x40000040};\nmov.b64 b, {y, 0x40000040};\n"
    "wgmma.mma_async.sync.aligned.m64n128k16.f32.bf16.bf16 {%0, %1, %2, %3, %4, %5, %6, %7, %8, %9, %10, %11, %12, %13, %14, %15, %16, %17, %18, %19, %20, %21, %22, %23, %24, %25, %26, %27, %28, %29, %30, %31, %32, %33, %34, %35, %36, %37, %38, %39, %40, %41, %42, %43, %44, %45, %46, %47, %48, %49, %50, %51, %52, %53, %54, %55, %56, %57, %58, %59, %60, %61, %62, %63}, a, b, p, 1, 1, 0, 1;\n}\n"
    : "+f"(d[0]), "+f"(d[1]), "+f"(d[2]), "+f"(d[3]), "+f"(d[4]), "+f"(d[5]), "+f"(d[6]), "+f"(d[7]), "+f"(d[8]), "+f"(d[9]), "+f"(d[10]), "+f"(d[11]), "+f"(d[12]), "+f"(d[13]), "+f"(d[14]), "+f"(d[15]), "+f"(d[16]), "+f"(d[17]), "+f"(d[18]), "+f"(d[19]), "+f"(d[20]), "+f"(d[21]), "+f"(d[22]), "+f"(d[23]), "+f"(d[24]), "+f"(d[25]), "+f"(d[26]), "+f"(d[27]), "+f"(d[28]), "+f"(d[29]), "+f"(d[30]), "+f"(d[31]), "+f"(d[32]), "+f"(d[33]), "+f"(d[34]), "+f"(d[35]), "+f"(d[36]), "+f"(d[37]), "+f"(d[38]), "+f"(d[39]), "+f"(d[40]), "+f"(d[41]), "+f"(d[42]), "+f"(d[43]), "+f"(d[44]), "+f"(d[45]), "+f"(d[46]), "+f"(d[47]), "+f"(d[48]), "+f"(d[49]), "+f"(d[50]), "+f"(d[51]), "+f"(d[52]), "+f"(d[53]), "+f"(d[54]), "+f"(d[55]), "+f"(d[56]), "+f"(d[57]), "+f"(d[58]), "+f"(d[59]), "+f"(d[60]), "+f"(d[61]), "+f"(d[62]), "+f"(d[63])
    : "r"(da), "r"(db), "r"(scale_d), "n"(OA), "n"(OB));
}
template <int OA, int OB>
__device__ __forceinline__ void wgmma_ss_n256_tbo(float (&d)[128], uint32_t da, uint32_t db, int scale_d) {
  asm volatile("{\n.reg .pred p;\n.reg .b64 a, b;\n.reg .b32 x, y;\nsetp.ne.b32 p, %130, 0;\nadd.u32 x, %128, %131;\nadd.u32 y, %129, %132;\nmov.b64 a, {x, 0x40000040};\nmov.b64 b, {y, 0x40000040};\n"
    "wgmma.mma_async.sync.aligned.m64n256k16.f32.bf16.bf16 {%0, %1, %2, %3, %4, %5, %6, %7, %8, %9, %10, %11, %12, %13, %14, %15, %16, %17, %18, %19, %20, %21, %22, %23, %24, %25, %26, %27, %28, %29, %30, %31, %32, %33, %34, %35, %36, %37, %38, %39, %40, %41, %42, %43, %44, %45, %46, %47, %48, %49, %50, %51, %52, %53, %54, %55, %56, %57, %58, %59, %60, %61, %62, %63, %64, %65, %66, %67, %68, %69, %70, %71, %72, %73, %74, %75, %76, %77, %78, %79, %80, %81, %82, %83, %84, %85, %86, %87, %88, %89, %90, %91, %92, %93, %94, %95, %96, %97, %98, %99, %100, %101, %102, %103, %104, %105, %106, %107, %108, %109, %110, %111, %112, %113, %114, %115, %116, %117, %118, %119, %120, %121, %122, %123, %124, %125, %126, %127}, a, b, p, 1, 1, 0, 1;\n}\n"
    : "+f"(d[0]), "+f"(d[1]), "+f"(d[2]), "+f"(d[3]), "+f"(d[4]), "+f"(d[5]), "+f"(d[6]), "+f"(d[7]), "+f"(d[8]), "+f"(d[9]), "+f"(d[10]), "+f"(d[11]), "+f"(d[12]), "+f"(d[13]), "+f"(d[14]), "+f"(d[15]), "+f"(d[16]), "+f"(d[17]), "+f"(d[18]), "+f"(d[19]), "+f"(d[20]), "+f"(d[21]), "+f"(d[22]), "+f"(d[23]), "+f"(d[24]), "+f"(d[25]), "+f"(d[26]), "+f"(d[27]), "+f"(d[28]), "+f"(d[29]), "+f"(d[30]), "+f"(d[31]), "+f"(d[32]), "+f"(d[33]), "+f"(d[34]), "+f"(d[35]), "+f"(d[36]), "+f"(d[37]), "+f"(d[38]), "+f"(d[39]), "+f"(d[40]), "+f"(d[41]), "+f"(d[42]), "+f"(d[43]), "+f"(d[44]), "+f"(d[45]), "+f"(d[46]), "+f"(d[47]), "+f"(d[48]), "+f"(d[49]), "+f"(d[50]), "+f"(d[51]), "+f"(d[52]), "+f"(d[53]), "+f"(d[54]), "+f"(d[55]), "+f"(d[56]), "+f"(d[57]), "+f"(d[58]), "+f"(d[59]), "+f"(d[60]), "+f"(d[61]), "+f"(d[62]), "+f"(d[63]), "+f"(d[64]), "+f"(d[65]), "+f"(d[66]), "+f"(d[67]), "+f"(d[68]), "+f"(d[69]), "+f"(d[70]), "+f"(d[71]), "+f"(d[72]), "+f"(d[73]), "+f"(d[74]), "+f"(d[75]), "+f"(d[76]), "+f"(d[77]), "+f"(d[78]), "+f"(d[79]), "+f"(d[80]), "+f"(d[81]), "+f"(d[82]), "+f"(d[83]), "+f"(d[84]), "+f"(d[85]), "+f"(d[86]), "+f"(d[87]), "+f"(d[88]), "+f"(d[89]), "+f"(d[90]), "+f"(d[91]), "+f"(d[92]), "+f"(d[93]), "+f"(d[94]), "+f"(d[95]), "+f"(d[96]), "+f"(d[97]), "+f"(d[98]), "+f"(d[99]), "+f"(d[100]), "+f"(d[101]), "+f"(d[102]), "+f"(d[103]), "+f"(d[104]), "+f"(d[105]), "+f"(d[106]), "+f"(d[107]), "+f"(d[108]), "+f"(d[109]), "+f"(d[110]), "+f"(d[111]), "+f"(d[112]), "+f"(d[113]), "+f"(d[114]), "+f"(d[115]), "+f"(d[116]), "+f"(d[117]), "+f"(d[118]), "+f"(d[119]), "+f"(d[120]), "+f"(d[121]), "+f"(d[122]), "+f"(d[123]), "+f"(d[124]), "+f"(d[125]), "+f"(d[126]), "+f"(d[127])
    : "r"(da), "r"(db), "r"(scale_d), "n"(OA), "n"(OB));
}

constexpr int NCTA = 132;
constexpr int NCLUSTER = 66;
constexpr int NPROB = 6;
#define DO_LOCAL true
#define DO_ATT true
#define NA_CL_ 32
#define NITEMS 512
constexpr int G1_MAX = 24, NA_CL = NA_CL_, NB_CTA = NCTA - 2 * NA_CL;
constexpr int TILE32K = 32768;
constexpr uint32_t DBASE = 1024;
constexpr int OFF_STG = 4 * TILE32K;
constexpr int OFF_A = 5 * TILE32K;
constexpr int OFF_BAR = 7 * TILE32K;
constexpr int L_K = 8192, L_V = L_K + 9216, L_P = L_V + 9216;
constexpr int SMEM_BYTES = OFF_BAR + 1024;
constexpr int B_GFULL = 0, B_GEMPTY = 32, B_AFULL = 64, B_AEMPTY = 104, B_QFULL = 144, B_QEMPTY = 160,
              B_SFULL = 176, B_SEMPTY = 208, B_OFULL = 240, B_STGFREE = 256, S_CODE = 272, B_SFULL2 = 304;
#define ASL 4
constexpr int A_SLOTS = ASL;
#define FS 2
#define HW 1
#define YPUB 1
#define REG_C 232
#define REG_P 40

struct Params {
  CUtensorMap ta[NPROB];
  CUtensorMap tb[NPROB];
  CUtensorMap tc[NPROB];
  CUtensorMap tq, tk, tv, to, tl, th;
  bf16* ob;
  const bf16* qkvb;
  int opt;
  uint16_t g[NCLUSTER][G1_MAX];
  uint16_t order[512];
};
__device__ __forceinline__ uint32_t tail_item(uint32_t code) {
  return (code & 0x7FFF) < 64 ? (5u << 8) | ((code & 4) << 4) | (code & 0x33) : 0xFFFFu;
}
#define HM 0x39383F30
#define HINT(b) ((HM >> (b) & 1) ? EV_FIRST : EV_NORMAL)
__device__ __forceinline__ uint32_t lds32(uint32_t a) {
  uint32_t v;
  asm volatile("ld.shared.u32 %0, [%1];" : "=r"(v) : "r"(a) : "memory");
  return v;
}
__device__ __forceinline__ uint4 lds128(uint32_t a) {
  uint4 v;
  asm volatile("ld.shared.v4.u32 {%0, %1, %2, %3}, [%4];" : "=r"(v.x), "=r"(v.y), "=r"(v.z), "=r"(v.w) : "r"(a) : "memory");
  return v;
}
__device__ __forceinline__ void sts64(uint32_t a, float x, float y) {
  asm volatile("st.shared.v2.f32 [%0], {%1, %2};" ::"r"(a), "f"(x), "f"(y) : "memory");
}
__device__ __forceinline__ void sts32(uint32_t a, uint32_t v) {
  asm volatile("st.shared.u32 [%0], %1;" ::"r"(a), "r"(v) : "memory");
}
__device__ __forceinline__ uint32_t opaque_tid() {
  uint32_t t;
  asm volatile("mov.u32 %0, %%tid.x;" : "=r"(t));
  return t;
}
__device__ __forceinline__ uint32_t stg_off(uint32_t tid) {
  return (tid >> 5) * 2048 + (tid & 15) * 128 + ((((tid >> 4) & 1) ^ (tid & 7)) << 4);
}
__device__ __forceinline__ int prob_nkb4(int prob) { return (0x4F4224 >> (prob * 4) & 15) + (prob == 4); }

constexpr float SM_C = 0.08838834764831845f * 1.4426950408889634f;
constexpr float SM_HI = 1099511627776.0f;
constexpr float SM_LO = 8.673617379884035e-19f;
__device__ __forceinline__ void softmax_max(const float (&s)[64], float& a0, float& a1) {
  a0 = fmaxf(s[0], s[1]);
  a1 = fmaxf(s[2], s[3]);
#pragma unroll
  for (int j = 1; j < 16; j++) {
    a0 = fmaxf(a0, fmaxf(s[4 * j], s[4 * j + 1]));
    a1 = fmaxf(a1, fmaxf(s[4 * j + 2], s[4 * j + 3]));
  }
  a0 = fmaxf(a0, __shfl_xor_sync(0xffffffffu, a0, 1));
  a1 = fmaxf(a1, __shfl_xor_sync(0xffffffffu, a1, 1));
  a0 = fmaxf(a0, __shfl_xor_sync(0xffffffffu, a0, 2));
  a1 = fmaxf(a1, __shfl_xor_sync(0xffffffffu, a1, 2));
}
template <int J0, int J1, bool OFS, int N>
__device__ __forceinline__ void softmax_exp(const float (&s)[64], float b0, float b1, uint32_t (&out)[N], float& t0,
                                            float& t1) {
#pragma unroll
  for (int j = J0; j < J1; j++) {
    const float e0 = ex2(OFS ? s[4 * j] + b0 : s[4 * j]);
    const float e1 = ex2(OFS ? s[4 * j + 1] + b0 : s[4 * j + 1]);
    const float e2 = ex2(OFS ? s[4 * j + 2] + b1 : s[4 * j + 2]);
    const float e3 = ex2(OFS ? s[4 * j + 3] + b1 : s[4 * j + 3]);
    t0 += e0 + e1;
    t1 += e2 + e3;
    out[2 * j] = pack_bf16(e0, e1);
    out[2 * j + 1] = pack_bf16(e2, e3);
  }
}

__device__ __forceinline__ uint32_t scale_q(uint32_t x) {
  uint32_t t, y;
  asm("mul.rn.bf16x2 %0, %1, %2;" : "=r"(t) : "r"(x), "r"(0xb9d8b9d8u));
  asm("fma.rn.bf16x2 %0, %1, %2, %3;" : "=r"(y) : "r"(x), "r"(0x3e033e03u), "r"(t));
  return y;
}

__global__ void __cluster_dims__(2, 1, 1) __launch_bounds__(384, 1) mega_kernel(const __grid_constant__ Params p) {
  extern __shared__ __align__(1024) uint8_t smem_raw[];
  const uint32_t sbase = smem_u32(smem_raw);
  if ((sbase & 0x3FFFFu) != DBASE) __trap();
  const uint32_t s_bar = sbase + OFF_BAR;
  const int warp0 = __shfl_sync(0xffffffffu, threadIdx.x >> 5, 0);
  const int cluster_id = blockIdx.x >> 1;
  const bool isB = cluster_id >= NA_CL;
#define EARLY 1
  auto early = [&](int s0, int s1) {
    const int prob = isB ? 3 : cluster_id >> 4;
    const int ng = (isB ? (cluster_id - NA_CL) >> 3 : (cluster_id >> 3) & 1) * 4;
    const uint32_t t0 = clock();
#pragma unroll 1
    for (int s = s0; s < s1; s++) {
      const uint32_t full = s_bar + B_GFULL + 8 * s;
      mbar_expect_tx(full, 49152);
      while ((uint32_t)clock() - t0 < s * 850u) {}
      tma_load_3d(sbase + OFF_A + s * 16384, &p.ta[prob], 0, (blockIdx.x & 15) * 128, s, full, EV_NORMAL);
      tma_load_3d(sbase + s * TILE32K, &p.tb[prob], 0, s * 64, ng, full, EV_NORMAL);
      tma_load_3d(sbase + s * TILE32K + 16384, &p.tb[prob], 0, s * 64, ng + 2, full, EV_NORMAL);
    }
  };
  if (threadIdx.x == 256) {
    for (int s = 0; s < 4; s++) mbar_init(s_bar + B_GFULL + 8 * s, 1);
    asm volatile("fence.mbarrier_init.release.cluster;" ::: "memory");
  }
  if (threadIdx.x == 0) {
    for (int s = 0; s < 4; s++) {
      mbar_init(s_bar + B_GEMPTY + 8 * s, 4);
      mbar_init(s_bar + B_SFULL + 8 * s, 4);
      mbar_init(s_bar + B_SFULL2 + 8 * s, 4);
      mbar_init(s_bar + B_SEMPTY + 8 * s, 1);
    }
    for (int s = 0; s < A_SLOTS; s++) {
      mbar_init(s_bar + B_AFULL + 8 * s, 1);
      mbar_init(s_bar + B_AEMPTY + 8 * s, s == 1 && !isB ? 8 : 2);
    }
    for (int s = 0; s < 2; s++) {
      mbar_init(s_bar + B_QFULL + 8 * s, 1);
      mbar_init(s_bar + B_QEMPTY + 8 * s, 2);
    }
    mbar_init(s_bar + B_OFULL, 8);
    mbar_init(s_bar + B_STGFREE, 1);
    asm volatile("fence.mbarrier_init.release.cluster;" ::: "memory");
  }
  if (threadIdx.x == 320) sts32(s_bar + S_CODE, 0);
  __syncwarp();
  asm volatile("barrier.cluster.arrive.relaxed.aligned;" ::: "memory");
  if (warp0 >= 8) reg_dealloc<REG_P>();
  if (threadIdx.x == 288) prefetch_tmap(&p.tb[isB ? 3 : cluster_id >> 4]);
  if (EARLY && warp0 == 8 && elect_one()) early(0, 4);
  __syncwarp();
  asm volatile("barrier.cluster.wait.acquire.aligned;" ::: "memory");

  if (warp0 >= 8) {
    const int lane = threadIdx.x & 31;
    const uint32_t rank = blockIdx.x & 1;
    if (warp0 == 8) {
      if (elect_one()) {
        TL_DECL;
        uint32_t gphase = 1 - EARLY;
        uint32_t tail = 0;
        int gi = 0;
        uint32_t rsel = rank, aswz = 0, lastq = 0, n = 0;
        for (int seg = 0; seg < 2; seg++) {
          for (;;) {
            uint32_t item = p.g[cluster_id][gi++];
            if (item == 0x500u) item = tail;
            if (item >= 0x600u) break;
            const int prob = item >> 8;
            const int rt = ((item >> 4) & 15) * 2 + rsel;
            const int ngrp0 = (item & 15) * 4;
            const int nkb4 = prob_nkb4(prob);
            const CUtensorMap* ta = &p.ta[prob];
            const CUtensorMap* tb = &p.tb[prob];
            TL(1, item);
            if (prob == 5) {
              uint32_t seen = 0;
              cnt_wait_bit(CNT_OB + (rt >> 2), 32u << (rt & 3) * 8, seen);
              fence_proxy_async_global();
            }
            for (int kb4 = EARLY && gi == 1; kb4 < nkb4; kb4++) {
              uint32_t seen = 0;
#pragma unroll 1
              for (int s = 0; s < 4; s++) {
                const int bs = s ^ (n & 1);
                if (prob == 4 && !(s & 1)) {
                  cnt_wait_bit(CNT_CTX + kb4, 16u << (s * 8), seen);
                  fence_proxy_async_global();
                }
                if (prob == 5 && kb4 == 0) {
                  mbar_wait(s_bar + B_AEMPTY + 8 * bs, (~(n + (s & 1)) >> 1) & 1);
                  if (s == 2) mbar_wait(s_bar + B_QEMPTY + (aswz ? 0 : 8), lastq);
                }
                mbar_wait(s_bar + B_GEMPTY + 8 * s, gphase);
                const uint32_t full = s_bar + B_GFULL + 8 * s;
                mbar_expect_tx(full, 49152);
                tma_load_3d(sbase + OFF_A + ((s * 16384) ^ aswz), ta, 0, rt * 128, kb4 * 4 + s, full, HINT(prob));
                if (prob == 5) {
                  tma_load_3d(sbase + bs * TILE32K, tb, 0, (kb4 * 4 + s) * 64, ngrp0, full, HINT(8 + prob));
                  tma_load_3d(sbase + bs * TILE32K + 16384, tb, 0, (kb4 * 4 + s) * 64, ngrp0 + 2, full, HINT(8 + prob));
                } else {
                  tma_load_3d_mc(sbase + s * TILE32K + rank * 16384, tb, 0, (kb4 * 4 + s) * 64, ngrp0 + rank * 2, full,
                                 (uint16_t)3, HINT(8 + prob));
                }
              }
              gphase ^= 1;
            }
          }
          if (seg == 0 && isB && DO_ATT) {
            int pv_row = 0, pv_col = 0;
            uint64_t pv_hint = 0;
#define ACQ_SLOT(slot, n)                                                              \
  {                                                                                    \
    if ((n) < 2) mbar_wait(s_bar + B_GEMPTY + 8 * (slot), gphase);                     \
    mbar_wait(s_bar + B_AEMPTY + 8 * (slot), (~(n) >> 1) & 1);                         \
  }
#define LOAD_V()                                                                       \
  {                                                                                    \
    const uint32_t vs = 3 - (n & 1);                                                   \
    ACQ_SLOT(vs, n - 1);                                                               \
    mbar_expect_tx(s_bar + B_AFULL + 8 * vs, TILE32K);                                 \
    tma_load_3d(sbase + vs * TILE32K, &p.tv, 0, pv_row, pv_col, s_bar + B_AFULL + 8 * vs, pv_hint); \
  }
#define NEXT_CODE() (nxt < 512 ? p.order[nxt] : nxt + (0x8000u - 512))
            uint32_t code = p.order[blockIdx.x - 2 * NA_CL];
            int it = 0;
            uint32_t seen = 0;
            for (;; it++) {
              if (it == 1) mbar_wait(s_bar + B_STGFREE, 0);
              if (code & 0x8000u) break;
              const int head = code >> 4;
              const int qt = code & 15;
              uint32_t nxt = 0;
              TL(1, 0x1000 | code);
              if (seen < 48) cnt_wait(CNT_QKV + (head >> 1), 48);
              fence_proxy_async_global();
              {
                const int b = it & 1;
                if (it < 2) {
                  mbar_wait(s_bar + B_GEMPTY + 16 * b, gphase);
                  mbar_wait(s_bar + B_GEMPTY + 16 * b + 8, gphase);
                }
                mbar_wait(s_bar + B_QEMPTY + 8 * b, ((it >> 1) & 1) ^ 1);
                mbar_expect_tx(s_bar + B_QFULL + 8 * b, TILE32K);
                tma_load_3d(sbase + OFF_A + b * TILE32K, &p.tq, 0, qt * 128, head * 2, s_bar + B_QFULL + 8 * b, HINT(24));
              }
#pragma unroll 1
              for (int t = qt; t >= 0; t--) {
                if (t == min(qt, 1)) nxt = cnt_next(CNT_QUEUE) + NB_CTA;
                if (t == 0) {
                  code = NEXT_CODE();
                  sts32(s_bar + S_CODE + 4 * ((it + 1) & 7), code);
                  seen = cnt_peek(CNT_QKV + ((code >> 5) & 15));
                }
                ACQ_SLOT(n & 1, n);
                mbar_expect_tx(s_bar + B_AFULL + 8 * (n & 1), TILE32K);
                tma_load_3d(sbase + (n & 1) * TILE32K, &p.tk, 0, t * 128, head * 2, s_bar + B_AFULL + 8 * (n & 1), HINT(t == qt ? 29 : 25));
                if (n) LOAD_V();
                n++;
                pv_row = t * 128;
                pv_col = head * 2;
                pv_hint = HINT(t == qt ? 29 : 26);
              }
            }
            ACQ_SLOT(n & 1, n);
            mbar_arrive(s_bar + B_AFULL + 8 * (n & 1));
            LOAD_V();
            tail = tail_item(code);
            aswz = (it & 1) * TILE32K;
            mbar_wait(s_bar + B_QEMPTY + 8 * (it & 1), ((it >> 1) & 1) ^ 1);
            rsel = (code >> 3) & 1;
            lastq = ((it - 1) >> 1) & 1;
          }
        }
        if (cnt_done(NCTA * 2)) cnt_rearm();
#pragma unroll 1
        for (int s = 0; s < 4; s++) mbar_wait(s_bar + B_GEMPTY + 8 * s, gphase);
        TL(1, 0xFFFF);
      }
    } else if (warp0 == 9) {
      if (elect_one()) {
        TL_DECL;
        uint32_t tail = 0;
        int gi = 0;
        uint32_t rsel = rank, aswz = 0;
        bool rearm = false;
        for (int seg = 0; seg < 2; seg++) {
          for (;;) {
            uint32_t item = p.g[cluster_id][gi++];
            if (item == 0x500u) item = tail;
            if (item >= 0x600u) break;
            const int prob = item >> 8;
            const int rt = ((item >> 4) & 15) * 2 + rsel;
            const int cg = (item & 15) * 4 + (prob == 5 ? 16 : 0);
            const CUtensorMap* tc = &p.tc[prob];
            const int nl = (p.g[cluster_id][gi] >> 8) == 4 && DO_LOCAL ? 8 : 1;
            const int grp = ((blockIdx.x >> 4) & 1) * 48 + (blockIdx.x & 15), r0 = (blockIdx.x >> 5) * 512;
            if (nl > 1) {
              cnt_wait(CNT_QKVB, 192);
              fence_proxy_async_global();
              sts32(s_bar + S_CODE, 2);
            }
            if (prob >= 4) rearm = cnt_done(NCTA * 2);
            const bool lastt = p.g[cluster_id][gi] >= 0x600u;
#pragma unroll 1
            for (int c = 0; c < 8; c++) {
              const int q = lastt ? c & 3 : c >> 1, w = lastt ? c >> 2 : c & 1;
              const int idx = w * 2 + (q & 1);
              const bool alt = lastt && q >= 2;
              mbar_wait(s_bar + (alt ? B_SFULL2 : B_SFULL) + 8 * idx, lastt ? seg : q >> 1);
              tma_store_3d(tc, sbase + (alt ? OFF_A + ((q * 16384) ^ aswz) + w * 8192 : OFF_STG + idx * 8192), 0,
                           rt * 128 + w * 64, cg + q, HINT(16 + prob));
              bulk_commit();
              if (c > 0 && !lastt) {
                bulk_wait_read<1>();
                mbar_arrive(s_bar + B_SEMPTY + 8 * ((w ^ 1) * 2 + (((c - 1) >> 1) & 1)));
              }
            }
            bulk_wait_read<0>();
            mbar_arrive(s_bar + (lastt ? B_STGFREE : B_SEMPTY + 8 * 3));
#pragma unroll 1
            for (int c = 0; c < nl; c++) {
              if (nl > 1) {
                mbar_wait(s_bar + B_AEMPTY, (c & 1) ^ 1);
                mbar_expect_tx(s_bar + B_AFULL, L_V);
                tma_load_3d(sbase + OFF_STG, &p.tl, 0, r0 + c * 64, grp, s_bar + B_AFULL, HINT(28));
                tma_load_3d(sbase + OFF_STG + L_K, &p.th, 0, r0 + c * 64 - 8, 16 + grp, s_bar + B_AFULL, HINT(28));
                mbar_wait(s_bar + B_AEMPTY + 8, (c & 1) ^ 1);
                mbar_expect_tx(s_bar + B_AFULL + 8, 9216);
                tma_load_3d(sbase + OFF_STG + L_V, &p.th, 0, r0 + c * 64 - 8, 32 + grp, s_bar + B_AFULL + 8, HINT(28));
                sts32(s_bar + S_CODE, c + 3);
              }
              if (c) {
                mbar_wait(s_bar + B_OFULL, ~c & 1);
                cnt_signal(CNT_OB + (blockIdx.x >> 5) * 2 + ((c - 1) >> 2), 1u << ((c - 1) & 3) * 8);
              } else if (prob < 4) {
                bulk_wait<0>();
                cnt_signal_done(prob == 3 ? CNT_QKVB : CNT_QKV + (item & 15));
                TL(2, item);
              }
            }
            if (nl > 1) {
              mbar_wait(s_bar + B_OFULL, 1);
              cnt_signal(CNT_OB + (blockIdx.x >> 5) * 2 + 1, 1u << 24);
              TL(2, 0x600);
            }
          }
          if (seg == 0 && isB && DO_ATT) {
            uint32_t code = p.order[blockIdx.x - 2 * NA_CL];
            for (int it = 0; !(code & 0x8000u); it++) {
              aswz = (~it & 1) * TILE32K;
              mbar_wait(s_bar + B_OFULL, it & 1);
              tma_store_3d(&p.to, sbase + OFF_STG, 0, (code & 15) * 128, (code >> 4) * 2, HINT(27));
              bulk_commit();
              const uint32_t nxt = lds32(s_bar + S_CODE + 4 * ((it + 1) & 7));
              bulk_wait_read<0>();
              mbar_arrive(s_bar + B_STGFREE);
              bulk_wait<0>();
              cnt_signal_done(CNT_CTX + (code >> 5), 1u << (code & 16));
              TL(2, 0x1000 | code);
              code = nxt;
            }
            tail = tail_item(code);
            rsel = (code >> 3) & 1;
            if (tail == 0xFFFFu) rearm = cnt_done(NCTA * 2);
          }
        }
        if (rearm) cnt_rearm();
        TL(2, 0xFFFF);
      }
    } else if (warp0 == 10 && !isB && DO_LOCAL) {
      const char* src = reinterpret_cast<const char*>(p.qkvb) + (((blockIdx.x >> 4) & 1) * 48 + (blockIdx.x & 15)) * 128;
      int spin = 0;
#pragma unroll 1
      for (int c = 0; c < 8; c++) {
        while (lds32(s_bar + S_CODE) <= c && ++spin < 100000) __nanosleep(256);
#pragma unroll 1
        for (int r = c ? 8 + lane : lane; r < 72; r += 32) {
          const int row = max((int)(blockIdx.x >> 5) * 512 + c * 64 - 8 + r, 0);
#pragma unroll
          for (int j = 0; j < 3; j++) asm volatile("prefetch.global.L2 [%0];" ::"l"(src + (size_t)row * 12288 + j * 2048));
        }
      }
    }
  } else {
    reg_alloc<REG_C>();
    const int warp = __shfl_sync(0xffffffffu, opaque_tid() >> 5, 0);
    const int wg = warp >> 2;
    const int lane = threadIdx.x & 31;
    TL_DECL;
    TR_DECL;
    uint32_t gphase = 0;
    uint32_t tail = 0, aswz = 0, rot = 0, etgt = warp & 1, stgpar = 1;
    int gi = 0;
    for (int seg = 0; seg < 2; seg++) {
      uint32_t item = p.g[cluster_id][gi++];
      if (item == 0x500u) item = tail;
      if (item < 0x600u) {
        float acc[128];
        uint32_t pk[64];
        int have = 0;
#define G_STORE_CHUNK(q)                                                                               \
  {                                                                                                    \
    const uint32_t st_base = sbase + OFF_STG + wg * 8192 + stg_off(opaque_tid());                      \
    if (have == 2) { _Pragma("unroll") for (int j = 0; j < 16; j++) pk[(q) * 16 + j] = scale_q(pk[(q) * 16 + j]); } \
    mbar_wait(s_bar + B_SEMPTY + 8 * (wg * 2 + ((q) & 1)), (((q) >> 1) & 1) ^ 1);                      \
    _Pragma("unroll") for (int j = 0; j < 4; j++)                                                      \
        stmatrix_x4((st_base ^ (j << 5)) + ((q) & 1) * 8192, pk[(q) * 16 + j * 4],                     \
                    pk[(q) * 16 + j * 4 + 1], pk[(q) * 16 + j * 4 + 2], pk[(q) * 16 + j * 4 + 3]);     \
    fence_proxy_async_smem();                                                                          \
    __syncwarp();                                                                                      \
    mbar_arrive_elect(s_bar + B_SFULL + 8 * (wg * 2 + ((q) & 1)), true);                              \
  }
#define G_STAGE(s) G_STAGE_Y(s, false, false, )
#define G_STAGE_X(s, ...) G_STAGE_Y(s, false, false, __VA_ARGS__)
#define G_STAGE_Y(s, first, last, ...)                                                                    \
  {                                                                                                       \
    mbar_wait_rest(s_bar + B_GFULL + 8 * (s), gphase, gok && (first));                                    \
    TR(9);                                                                                                \
    const uint32_t da = make_desc(DBASE + OFF_A + (((s) * 16384) ^ aswz) + wg * 8192, 16);                \
    const uint32_t db = make_desc(DBASE + ((s) ^ rot) * TILE32K, 8192);                                   \
    named_bar_sync_if(5 + wg, 256, !(first));                                                             \
    wgmma_fence();                                                                                        \
    _Pragma("unroll") for (int k = 0; k < 5; k++) {                                                       \
      __VA_ARGS__;                                                                                        \
      if (k == 0) wgmma_ss_n256_tbo<0, 0>(acc, da, db, !(first));                                         \
      if (k == 1) wgmma_ss_n256_tbo<2, 128>(acc, da, db, 1);                                              \
      if (k == 2) wgmma_ss_n256_tbo<4, 256>(acc, da, db, 1);                                              \
      if (k == 3) wgmma_ss_n256_tbo<6, 384>(acc, da, db, 1);                                              \
    }                                                                                                     \
    wgmma_commit();                                                                                       \
    named_bar_arrive_if(6 - wg, 256, !(wg ? (last) : (first)));                                           \
    if (!(first)) {                                                                                       \
      wgmma_wait<1>();                                                                                    \
      mbar_arrive_cluster_if(s_bar + B_GEMPTY + 8 * (((s) + 3) & 3), etgt, lane == 0 && (warp & 3) < 2);  \
    }                                                                                                     \
  }
        TL0(item);
        undef_regs(acc);
        {
          constexpr bool gok = false;
          G_STAGE_Y(0, true, false, )
        }
        undef_regs(pk);
        for (;;) {
          constexpr bool gok = false;
          const int nkb4 = prob_nkb4(item >> 8);
          const uint32_t next = p.g[cluster_id][gi++];
          if (have) G_STORE_CHUNK(0)
          G_STAGE(1)
          G_STAGE(2)
          if (have) G_STORE_CHUNK(1)
          G_STAGE(3)
          gphase ^= 1;
          G_STAGE(0)
          if (have) G_STORE_CHUNK(2)
          G_STAGE(1)
          G_STAGE(2)
          if (have) G_STORE_CHUNK(3)
          G_STAGE_Y(3, false, nkb4 == 2, )
          gphase ^= 1;
          int kb4 = 2;
          if (nkb4 == 16 && DO_LOCAL) {
            constexpr uint32_t aswz = 0, rot = 0;
            G_STAGE(0)
            G_STAGE(1)
            for (; kb4 < 10; kb4++) {
              float ls[36];
              TR(10);
              mbar_wait(s_bar + B_AFULL, kb4 & 1);
              TR(11);
              {
                const uint32_t dq = make_desc(DBASE + OFF_STG + wg * 64, 16);
                G_STAGE_X(2, if (k == 1) wgmma_ss_n72_init(ls, dq, dq + L_K / 16); if (k == 3) wgmma_ss_n72(ls, dq + 2, dq + L_K / 16 + 2, 1))
              }
              mbar_wait(s_bar + B_AFULL + 8, kb4 & 1);
              const int tid = opaque_tid();
              uint32_t vw[16];
              uint4 pw[8];
              {
                const uint32_t va = sbase + OFF_STG + L_V + ((tid >> 4) & 7) * 1024 + wg * 64 + (tid & 15) * 4;
#pragma unroll
                for (int j = 1; j < 16; j++) vw[j] = lds32((va ^ ((j & 7) << 4)) + j * 128);
              }
              G_STAGE(3)
              gphase ^= 1;
              fence_regs(ls);
              mbar_arrive_if(s_bar + B_AEMPTY, (threadIdx.x & 127) == 0);
              {
                const int d = (tid & 3) * 2 - ((tid >> 2) & 7);
                const bool p0 = d > 0, p1 = d >= 0;
                const int w = warp & 3;
                float x0, x1, y0, y1;
#define L_PICK(w_)                                   \
  {                                                  \
    x0 = p0 ? ls[8 * (w_)] : ls[8 * (w_) + 4];       \
    x1 = p1 ? ls[8 * (w_) + 1] : ls[8 * (w_) + 5];   \
    y0 = p0 ? ls[8 * (w_) + 6] : ls[8 * (w_) + 10];  \
    y1 = p1 ? ls[8 * (w_) + 7] : ls[8 * (w_) + 11];  \
  }
                if (w == 0) {
                  if (kb4 == 2 && blockIdx.x < 32) ls[0] = ls[1] = -INFINITY;
                  L_PICK(0)
                } else if (w == 1) L_PICK(1)
                else if (w == 2) L_PICK(2)
                else L_PICK(3)
                constexpr float C = 0.17677669529663687f * 1.4426950408889634f;
                float mx = fmaxf(x0, x1), my = fmaxf(y0, y1);
                mx = fmaxf(mx, __shfl_xor_sync(0xffffffffu, mx, 1));
                my = fmaxf(my, __shfl_xor_sync(0xffffffffu, my, 1));
                mx = -C * fmaxf(mx, __shfl_xor_sync(0xffffffffu, mx, 2));
                my = -C * fmaxf(my, __shfl_xor_sync(0xffffffffu, my, 2));
                x0 = ex2(fmaf(x0, C, mx));
                x1 = ex2(fmaf(x1, C, mx));
                y0 = ex2(fmaf(y0, C, my));
                y1 = ex2(fmaf(y1, C, my));
                float sx = x0 + x1, sy = y0 + y1;
                sx += __shfl_xor_sync(0xffffffffu, sx, 1);
                sy += __shfl_xor_sync(0xffffffffu, sy, 1);
                sx += __shfl_xor_sync(0xffffffffu, sx, 2);
                sy += __shfl_xor_sync(0xffffffffu, sy, 2);
                sx = rcp(sx);
                sy = rcp(sy);
                const uint32_t pa = sbase + OFF_STG + L_P + (tid >> 5) * 512 + (tid & 31) * 8;
                sts64(pa, x0 * sx, x1 * sx);
                sts64(pa + 256, y0 * sy, y1 * sy);
                __syncwarp();
              }
              const uint32_t pr = sbase + OFF_STG + L_P + (tid >> 4) * 256;
              uint32_t* dst = reinterpret_cast<uint32_t*>(p.ob) + (blockIdx.x & 15) * 32 + wg * 16 + (tid & 15) +
                              (((blockIdx.x >> 5) * 512 + (kb4 - 2) * 64 + ((tid >> 4) & 7) * 8) * 2 + ((blockIdx.x >> 4) & 1)) * 512;
#define L_PV(g0)                                                                                       \
  _Pragma("unroll") for (int g = (g0); g < (g0) + 4; g++) {                                            \
    const uint4 a = pw[2 * (g & 3)], b = pw[2 * (g & 3) + 1];                                          \
    const uint32_t w[8] = {a.x, a.y, a.z, a.w, b.x, b.y, b.z, b.w};                                    \
    float o0 = 0.f, o1 = 0.f;                                                                          \
    _Pragma("unroll") for (int c = 0; c < 8; c++) {                                                    \
      const uint32_t u = vw[c > g ? c : c + 8];                                                        \
      o0 = fmaf(__uint_as_float(w[c]), __uint_as_float(u << 16), o0);                                  \
      o1 = fmaf(__uint_as_float(w[c]), __uint_as_float(u & 0xFFFF0000u), o1);                          \
    }                                                                                                  \
    dst[g * 1024] = pack_bf16(o0, o1);                                                                 \
  }
#pragma unroll
              for (int j = 0; j < 8; j++) pw[j] = lds128(pr + j * 16);
              mbar_arrive_elect(s_bar + B_AEMPTY + 8, true);
              G_STAGE(0)
              L_PV(0)
#pragma unroll
              for (int j = 0; j < 8; j++) pw[j] = lds128(pr + 128 + j * 16);
              G_STAGE(1)
              L_PV(4)
              __syncwarp();
              mbar_arrive_elect(s_bar + B_OFULL, true);
            }
            G_STAGE(2)
            G_STAGE(3)
            gphase ^= 1;
            kb4++;
          }
          const bool fin = next >= 0x600u;
          for (; kb4 < nkb4 - fin; kb4++) {
            G_STAGE(0)
            G_STAGE(1)
            G_STAGE(2)
            G_STAGE_Y(3, false, kb4 + 1 == nkb4, )
            gphase ^= 1;
          }
          if (fin) break;
          wgmma_wait<0>();
          mbar_arrive_cluster_if(s_bar + B_GEMPTY + 8 * 3, etgt, lane == 0 && (warp & 3) < 2);
          {
            const bool gok = mbar_test(s_bar + B_GFULL, gphase);
            fence_regs(acc);
#pragma unroll
            for (int j = 0; j < 64; j++) pk[j] = pack_bf16(acc[2 * j], acc[2 * j + 1]);
            have = item < 0x100u ? 2 : 1;
            item = next;
            TL0(item);
            G_STAGE_Y(0, true, false, )
          }
        }
        {
          constexpr bool gok = false;
          G_STAGE(0)
          G_STAGE(1)
          wgmma_wait<0>();
          mbar_arrive_cluster_if(s_bar + B_GEMPTY + 8 * (FS - 1), etgt, lane == 0 && (warp & 3) < 2);
          fence_regs(acc);
          float lo[64], hi[64];
#pragma unroll
          for (int j = 0; j < 64; j++) {
            asm volatile("mov.b32 %0, %1;" : "=f"(lo[j]) : "f"(acc[j]));
            asm volatile("mov.b32 %0, %1;" : "=f"(hi[j]) : "f"(acc[64 + j]));
          }
#pragma unroll
          for (int s = FS; s < 4; s++) {
            mbar_wait(s_bar + B_GFULL + 8 * s, gphase);
            const uint32_t da = make_desc(DBASE + OFF_A + ((s * 16384) ^ aswz) + wg * 8192, 16);
            const uint32_t db = make_desc(DBASE + (s ^ rot) * TILE32K, 8192);
            if (s == FS) named_bar_sync(5 + wg, 256);
            wgmma_fence();
            wgmma_ss_n128_tb<0, 0>(lo, da, db, 1);
            wgmma_ss_n128_tb<2, 128>(lo, da, db, 1);
            wgmma_ss_n128_tb<4, 256>(lo, da, db, 1);
            wgmma_ss_n128_tb<6, 384>(lo, da, db, 1);
            wgmma_commit();
          }
          wgmma_fence();
#pragma unroll
          for (int s = FS; s < 4; s++) {
            const uint32_t da = make_desc(DBASE + OFF_A + ((s * 16384) ^ aswz) + wg * 8192, 16);
            const uint32_t db = make_desc(DBASE + (s ^ rot) * TILE32K, 8192);
            wgmma_ss_n128_tb<0, 1024>(hi, da, db, 1);
            wgmma_ss_n128_tb<2, 1152>(hi, da, db, 1);
            wgmma_ss_n128_tb<4, 1280>(hi, da, db, 1);
            wgmma_ss_n128_tb<6, 1408>(hi, da, db, 1);
          }
          wgmma_commit();
          named_bar_arrive_if(6, 256, wg == 0);
          gphase ^= 1;
          const uint32_t so = sbase + stg_off(opaque_tid());
          mbar_wait(s_bar + B_STGFREE, stgpar);
          mbar_wait(s_bar + B_SEMPTY + 16 * wg, 1);
          mbar_wait(s_bar + B_SEMPTY + 16 * wg + 8, 1);
#define FIN_HALF(x, base, stride, bar)                                                                                \
  fence_regs(x);                                                                                                      \
  _Pragma("unroll") for (int j = 0; j < 8; j++)                                                                       \
      stmatrix_x4(((base) ^ ((j & 3) << 5)) + (j >> 2) * (stride), pack_bf16(x[8 * j], x[8 * j + 1]),                 \
                  pack_bf16(x[8 * j + 2], x[8 * j + 3]), pack_bf16(x[8 * j + 4], x[8 * j + 5]), pack_bf16(x[8 * j + 6], x[8 * j + 7])); \
  fence_proxy_async_smem();                                                                                           \
  __syncwarp();                                                                                                       \
  mbar_arrive_elect(s_bar + (bar) + 16 * wg, true);                                                                   \
  mbar_arrive_elect(s_bar + (bar) + 16 * wg + 8, true);
          wgmma_wait<1>();
          FIN_HALF(lo, so + OFF_STG + wg * 8192, 8192, B_SFULL)
          wgmma_wait<0>();
          TRI(12, 8);
#pragma unroll
          for (int s = FS; s < 4; s++) mbar_arrive_cluster_if(s_bar + B_GEMPTY + 8 * s, etgt, lane == 0 && (warp & 3) < 2);
          FIN_HALF(hi, so + OFF_A + (32768 ^ aswz), 16384, B_SFULL2)
          TRI(12, 10);
        }
      }
      if (seg == 0 && isB && DO_ATT) {
        float o[64], s[64];
        uint32_t pa[32], pb[32];
        undef_regs(o);
        undef_regs(s);
        undef_regs(pa);
        undef_regs(pb);
        uint32_t phase = 0;
        const bool sig = (threadIdx.x & 127) == 0;
        if (wg == 1) named_bar_arrive(1, 256);

#define ISSUE_PV(pr, slot_)                                                             \
  {                                                                                     \
    const uint32_t dv = make_desc(DBASE + (slot_) * TILE32K, 16384);                    \
    if (!(pfirst && wg == HW)) {                                                        \
      wgmma_fence();                                                                    \
      _Pragma("unroll") for (int k = 0; k < 8; k++)                                     \
          wgmma_rs_n128_tb(o, pr[4 * k], pr[4 * k + 1], pr[4 * k + 2], pr[4 * k + 3], dv + k * 128, (k != 0) || !pfirst); \
      wgmma_commit();                                                                   \
    } else {                                                                            \
      wgmma_fence();                                                                    \
      _Pragma("unroll") for (int k = 0; k < 4; k++)                                     \
          wgmma_rs_n128_tb(o, pr[16 + 4 * k], pr[17 + 4 * k], pr[18 + 4 * k], pr[19 + 4 * k], dv + k * 128, k != 0); \
      wgmma_commit();                                                                   \
    }                                                                                   \
  }
#define EPILOGUE(on_)                                                                             \
  _Pragma("unroll") for (int j = 0; j < 8; j++) {                                                 \
    const int b = j * 8;                                                                          \
    stmatrix_x4_p((st_o ^ ((j & 3) << 5)) + (j >> 2) * 16384,                                     \
                  pack_bf16(o[b] * sc0, o[b + 1] * sc0), pack_bf16(o[b + 2] * sc1, o[b + 3] * sc1),   \
                  pack_bf16(o[b + 4] * sc0, o[b + 5] * sc0), pack_bf16(o[b + 6] * sc1, o[b + 7] * sc1), on_); \
  }
#define PUBLISH_O()                                  \
  {                                                  \
    fence_proxy_async_smem();                        \
    __syncwarp();                                    \
    mbar_arrive_elect(s_bar + B_OFULL, true);        \
  }
#define FINAL_SCALE()                                  \
  {                                                    \
    float e0 = l0, e1 = l1;                            \
    e0 += __shfl_xor_sync(0xffffffffu, e0, 1);         \
    e1 += __shfl_xor_sync(0xffffffffu, e1, 1);         \
    e0 += __shfl_xor_sync(0xffffffffu, e0, 2);         \
    e1 += __shfl_xor_sync(0xffffffffu, e1, 2);         \
    sc0 = rcp(e0);             \
    sc1 = rcp(e1);                                     \
  }
        float l0 = 1.f, l1 = 1.f, b0 = 0.f, b1 = 0.f, sc0 = 0.f, sc1 = 0.f;
        bool gen = false;
        bool pfirst = true;
        bool fresh = true;
        uint32_t code = p.order[blockIdx.x - 2 * NA_CL];
        int it = 0, rem = code & 15;
        TL0(0x1000 | code);
        mbar_wait(s_bar + B_AFULL, 0);
        mbar_wait(s_bar + B_QFULL, 0);
#define MMA_PART(N_, acc_, PIN, PAR)                                                                       \
  wgmma_fence();                                                                                           \
  uint32_t cv;                                                                                             \
  bool rv;                                                                                                 \
  _Pragma("unroll") for (int k = 0; k < 8; k++) {                                                          \
    wgmma_ss_n##N_(acc_, dq + (k >> 2) * 1024 + (k & 3) * 2, dk + (k >> 2) * 1024 + (k & 3) * 2, k != 0 || N_ == 64 || fresh || gen); \
    if (k == 1) cv = lds32(s_bar + S_CODE + 4 * ((it + 1) & 7));          \
    if (k == 3) rv = mbar_test(s_bar + B_AFULL + 8 * (3 - (PAR)), phase ^ (1 - (PAR)));                    \
  }                                                                                                        \
  wgmma_commit();                                                                                          \
  code = __reduce_or_sync(0xffffffffu, cv);                                                                \
  if (!(YPUB && N_ == 64) && opub) PUBLISH_O();                                                            \
  if (N_ == 128 && fresh) FINAL_SCALE();                                                                   \
  last = rem == 0 && (code & 0x8000u);                                                                     \
  nit = it + (rem == 0 && !last);                                                                          \
  mbar_wait_rest(s_bar + B_AFULL + 8 * (3 - (PAR)), phase ^ (1 - (PAR)), rv);                              \
  ISSUE_PV(PIN, 3 - (PAR));                                                                                \
  named_bar_arrive(2 - wg, 256);                                                                           \
  TR(2);                                                                                                   \
  wgmma_wait<1>();                                                                                         \
  fence_regs(acc_);                                                                                        \
  TR(3);                                                                                                   \
  mbar_arrive_if(s_bar + B_AEMPTY + 8 * (PAR), sig);                                                       \
  mbar_arrive_if(s_bar + B_QEMPTY + 8 * (it & 1), sig && rem == 0);                                        \
  rs = mbar_test(s_bar + B_STGFREE, ~it & 1) | (it == 0);
#define PRESET_S()                                                                                         \
  if (fresh || gen) {                                                                                      \
    const float rowf = fresh ? mrow : 64.f;                                                                \
    _Pragma("unroll") for (int j = 0; j < 8; j++) {                                                        \
      s[4 * j] = s[4 * j + 1] = b0;                                                                        \
      s[4 * j + 2] = s[4 * j + 3] = b1;                                                                    \
      s[32 + 4 * j] = fmaf(__saturatef(float(8 * j) - rowf), -3e38f, b0);                                  \
      s[33 + 4 * j] = fmaf(__saturatef(float(8 * j + 1) - rowf), -3e38f, b0);                              \
      s[34 + 4 * j] = fmaf(__saturatef(float(8 * j - 8) - rowf), -3e38f, b1);                              \
      s[35 + 4 * j] = fmaf(__saturatef(float(8 * j - 7) - rowf), -3e38f, b1);                              \
    }                                                                                                      \
  }
#define BAD_SUM() (!(t0 + t1 <= SM_HI) | (t0 < lo0) | (t1 < lo1))
#define SECOND_HALF(POUT, PAR, BAD, ...)                                                                   \
  wgmma_wait<0>();                                                                                         \
  mbar_arrive_if(s_bar + B_AEMPTY + 8 * (3 - (PAR)), sig && ((PAR) || !fresh || it > 0));                  \
                                                                               \
  const float rdy = mbar_test2(s_bar + B_AFULL + 8 * (1 - (PAR)), phase ^ (PAR), s_bar + B_QFULL + 8 * (nit & 1), (nit >> 1) & 1); \
  TR(8);                                                                                                   \
  __VA_ARGS__;                                                                                             \
  t0 += x0 + x1;                                                                                           \
  t1 += x2 + x3;                                                                                           \
  POUT[16] = pack_bf16(x0, x1);                                                                            \
  POUT[17] = pack_bf16(x2, x3);                                                                            \
  softmax_exp<9, TPOS, false>(s, 0.f, 0.f, POUT, t0, t1);                                                  \
  t0 = addv(t0, rdy);                                                                                      \
  softmax_exp<TPOS, 16, false>(s, 0.f, 0.f, POUT, t0, t1);                                                 \
  rare = __any_sync(0xffffffffu, (BAD) | (__float_as_uint(rdy) != 0));
#define TPOS 14
#define ATT_STEP(PIN, POUT, PAR, ...)                                                                      \
  {                                                                                                        \
    const uint32_t dq = make_desc(DBASE + OFF_A + (it & 1) * TILE32K + (wg ^ HW) * 8192, 16);                \
    const uint32_t dk = make_desc(DBASE + (PAR) * TILE32K, 16);                                            \
    float t0 = fresh ? 0.f : l0, t1 = fresh ? 0.f : l1, x0, x1, x2, x3;                                    \
    bool rare, last, rs;                                                                                   \
    int nit;                                                                                               \
    TRI(0, fresh ? 7 : 0);                                                                                 \
    named_bar_sync(1 + wg, 256);                                                                           \
    TRI(1, fresh ? 6 : 1);                                                                                 \
    if (!fresh || wg != HW) {                                                                              \
      MMA_PART(128, s, PIN, PAR)                                                                           \
      softmax_exp<0, 8, false>(s, 0.f, 0.f, POUT, t0, t1);                                                 \
      x0 = ex2v(s[32]), x1 = ex2v(s[33]), x2 = ex2v(s[34]), x3 = ex2v(s[35]);                              \
    } else {                                                                                               \
                                                     \
      float sl[32];                                                                                        \
      _Pragma("unroll") for (int j = 0; j < 32; j++) asm volatile("mov.b32 %0, %1;" : "=f"(sl[j]) : "f"(s[32 + j])); \
      MMA_PART(64, sl, PIN, PAR)                                                                           \
      _Pragma("unroll") for (int j = 0; j < 32; j++) asm volatile("mov.b32 %0, %1;" : "=f"(s[32 + j]) : "f"(sl[j])); \
      FINAL_SCALE();                                                                                       \
      x0 = ex2v(s[32]), x1 = ex2v(s[33]), x2 = ex2v(s[34]), x3 = ex2v(s[35]);                              \
    }                                                                                                      \
    const float lo1 = fresh ? SM_LO : 0.f, lo0 = mrow < 0.f && wg == HW ? 0.f : lo1;                       \
    if (!fresh) {                                                                                          \
      SECOND_HALF(POUT, PAR, !(t0 + t1 <= SM_HI), )                                                        \
    } else {                                                                                               \
      mbar_wait_rest(s_bar + B_STGFREE, ~it & 1, rs);                                                      \
      SECOND_HALF(POUT, PAR, BAD_SUM(), fence_regs(o); EPILOGUE(it > 0))                                   \
      if (YPUB && wg == HW && it > 0) PUBLISH_O();                           \
    }                                                                                                      \
    TR(4);                                                                                                 \
    if (rare) {                                                                                            \
      if (__any_sync(0xffffffffu, BAD_SUM())) {                                      \
                       \
        if (fresh && wg == HW) { _Pragma("unroll") for (int j = 0; j < 32; j++) asm volatile("mov.b32 %0, 0xff800000;" : "=f"(s[j])); }         \
        float d0, d1;                                                                                      \
        softmax_max(s, d0, d1);                                                                            \
        if (!fresh) {                                                                                      \
          d0 = fmaxf(d0, 0.f);                                                                             \
          d1 = fmaxf(d1, 0.f);                                                                             \
        }                                                                                                  \
        const float r0 = fresh ? 1.f : ex2(-d0), r1 = fresh ? 1.f : ex2(-d1);                              \
        t0 = fresh ? 0.f : l0 * r0;                                                                        \
        t1 = fresh ? 0.f : l1 * r1;                                                                        \
        softmax_exp<0, 16, true>(s, -d0, -d1, POUT, t0, t1);                                               \
        b0 -= d0;                                                                                          \
        b1 -= d1;                                                                                          \
        gen = true;                                                                                        \
        fence_regs(o);                                                                                     \
        _Pragma("unroll") for (int j = 0; j < 16; j++) {                                                   \
          o[4 * j] *= r0;                                                                                  \
          o[4 * j + 1] *= r0;                                                                              \
          o[4 * j + 2] *= r1;                                                                              \
          o[4 * j + 3] *= r1;                                                                              \
        }                                                                                                  \
      }                                                                                                    \
      const bool rq = mbar_test(s_bar + B_QFULL + 8 * (nit & 1), (nit >> 1) & 1);                          \
      mbar_wait(s_bar + B_AFULL + 8 * (1 - (PAR)), phase ^ (PAR));                                         \
      mbar_wait_rest(s_bar + B_QFULL + 8 * (nit & 1), (nit >> 1) & 1, rq);                                 \
    }                                                                                                      \
    fence_regs(o);                                                                                         \
    TR(5);                                                                                                 \
    opub = fresh && it > 0 && !(YPUB && wg == HW);                                                         \
    pfirst = fresh;                                                                                        \
    l0 = t0;                                                                                               \
    l1 = t1;                                                                                               \
    if (last) {                                                                                            \
      __VA_ARGS__;                                                                                         \
      break;                                                                                               \
    }                                                                                                      \
    fresh = rem == 0;                                                                                      \
    if (fresh) { TL0(0x1000 | code); }                                                                     \
    rem = fresh ? code & 15 : rem - 1;                                                                     \
    it = nit;                                                                                              \
    PRESET_S()                                                                                             \
  }
        bool opub = false;
        const float mrow = float((warp & 3) * 16 + (lane >> 2) - (lane & 3) * 2);
        const uint32_t st_o = sbase + OFF_STG + stg_off(opaque_tid() ^ (HW * 128));
        PRESET_S()
        for (;;) {
          ATT_STEP(pa, pb, 0, rot = 1; _Pragma("unroll") for (int j = 0; j < 32; j++) asm volatile("mov.b32 %0, %1;" : "=r"(pa[j]) : "r"(pb[j])))
          ATT_STEP(pb, pa, 1, rot = 0)
          phase ^= 1;
        }
        {
          mbar_wait(s_bar + B_AFULL + 8 * (3 - rot), phase);
          TRI(12, 2);
          ISSUE_PV(pa, 3 - rot);
          if (opub) PUBLISH_O();
          FINAL_SCALE();
          mbar_wait(s_bar + B_STGFREE, it & 1);
          wgmma_wait<0>();
          fence_regs(o);
          TRI(12, 4);
          mbar_arrive_if(s_bar + B_AEMPTY + 8 * (3 - rot), sig);
          EPILOGUE(true);
          PUBLISH_O();
          TRI(12, 5);
          stgpar = ~it & 1;
          tail = tail_item(code);
          aswz = (~it & 1) * TILE32K;
          etgt = blockIdx.x & 1;
        }
      }
    }
    TL0(0xFFFF);
    TRI(15, 15);
  }
}

typedef CUresult (*EncodeFn)(CUtensorMap*, CUtensorMapDataType, cuuint32_t, void*, const cuuint64_t*,
                             const cuuint64_t*, const cuuint32_t*, const cuuint32_t*, CUtensorMapInterleave,
                             CUtensorMapSwizzle, CUtensorMapL2promotion, CUtensorMapFloatOOBfill);

EncodeFn get_encode() {
  static EncodeFn fn = nullptr;
  if (!fn) {
    void* p = nullptr;
    cudaDriverEntryPointQueryResult st;
    cudaGetDriverEntryPoint("cuTensorMapEncodeTiled", &p, cudaEnableDefault, &st);
    fn = (EncodeFn)p;
  }
  return fn;
}

void make_map(CUtensorMap* m, const void* ptr, int rows, int cols, int box_rows, int box_groups,
              CUtensorMapSwizzle swz = CU_TENSOR_MAP_SWIZZLE_128B) {
  cuuint64_t dims[3] = {64, (cuuint64_t)rows, (cuuint64_t)(cols / 64)};
  cuuint64_t strides[2] = {(cuuint64_t)cols * 2, 128};
  cuuint32_t box[3] = {64, (cuuint32_t)box_rows, (cuuint32_t)box_groups};
  cuuint32_t es[3] = {1, 1, 1};
  CUtensorMapL2promotion prom = box_groups == 1 ? CU_TENSOR_MAP_L2_PROMOTION_NONE : CU_TENSOR_MAP_L2_PROMOTION_L2_256B;
  get_encode()(m, CU_TENSOR_MAP_DATA_TYPE_BFLOAT16, 3, const_cast<void*>(ptr), dims, strides, box, es,
               CU_TENSOR_MAP_INTERLEAVE_NONE, swz, prom,
               CU_TENSOR_MAP_FLOAT_OOB_FILL_NONE);
}

#define PARAM(name, val) const int name = val
void build_schedule(Params& p) {
  PARAM(C_KB, 1028);
  PARAM(C_TILE, 10);
  PARAM(C_QX, 0);
  PARAM(C_START, 4500);
  PARAM(C_STEP, 2052);
  PARAM(C_ITEM, 300);
  PARAM(C_LAG, 8000);
  PARAM(C_SP, 5200);
  PARAM(C_TAIL, 22000);
  PARAM(C_SHORT, 0);
  PARAM(C_AT, 72);
  PARAM(C_LATE, 0);
  PARAM(C_LMASK, 0xAA0);
  PARAM(C_AM, 100);
  PARAM(C_ODD, 1300);
  PARAM(C_READY, 10000);
  auto gemm_cost = [&](int prob) {
    static const int nkb[NPROB] = {16, 8, 8, 16, 64, 16};
    return nkb[prob] * C_KB + C_TILE + (prob == 0 ? C_QX : 0);
  };
  PARAM(OPT, 0);
  p.opt = OPT;
  memset(p.g, 0xFF, sizeof(p.g));
  int n1[NCLUSTER];
  long t1[NCLUSTER];
  long ready[16];
  for (int c = 0; c < NCLUSTER; c++) { n1[c] = 0; t1[c] = C_START; }
  for (int i = 0; i < 16; i++) ready[i] = 0;
  auto add = [&](int c, int prob, int mp, int nt) {
    p.g[c][n1[c]++] = (uint16_t)((prob << 8) | (mp << 4) | nt);
    t1[c] += gemm_cost(prob);
    if (prob < 3) {
      const long r = t1[c] + C_READY;
      if (r > ready[nt]) ready[nt] = r;
    }
  };
  for (int r = 0; r < 8; r++)
    for (int c = 0; c < NA_CL; c++) {
      const int mp = c & 7, nt = 2 * r + ((c >> 3) & 1);
      for (int j = 0; j < (c < 16 ? 1 : 2); j++) {
        add(c, c < 16 ? 0 : 1 + j, mp, nt);
      }
    }
  long tA = 0;
  for (int c = 0; c < NA_CL; c++) {
    if (t1[c] > tA) tA = t1[c];
    add(c, 4, c & 7, c >> 3);
  }
  for (int i = 0; i < 96; i++) add(NA_CL + i % (NCLUSTER - NA_CL), 3, i % 8, i / 8);
  for (int c = NA_CL; c < NCLUSTER; c++) {
    p.g[c][n1[c]++] = 0x600;
    p.g[c][n1[c]++] = 0x500;
  }
  long tf[NB_CTA];
  bool done[512], started[NB_CTA];
  long fin[16];
  for (int c = 0; c < NB_CTA; c++) { tf[c] = t1[NA_CL + (c >> 1)] + 2000; started[c] = false; }
  for (int i = 0; i < 512; i++) done[i] = false;
  for (int i = 0; i < 16; i++) fin[i] = 0;
  auto alen = [&](int qt) { return (long)(qt + 1) * C_STEP + C_ITEM + (qt < 2 ? C_SHORT : 0); };
  int nq = NB_CTA;
  for (int n = 0; n < 512; n++) {
    int cb = 0;
    for (int c = 1; c < NB_CTA; c++)
      if (tf[c] < tf[cb]) cb = c;
    int best = -1;
    long bkey = 0;
    for (int i = 0; i < 512; i++) {
      if (done[i]) continue;
      const int hp = i >> 5;
      long dl = -(long)(16 - hp) * C_SP - C_LAG + ((i >> 4) & 1) * C_ODD;
      if (dl > -C_TAIL) dl = -C_TAIL;
      long key = dl - alen(i & 15) * (dl == -C_TAIL ? C_AT : C_AM) / 100;
      if ((i >> 4) == 31 && (C_LMASK >> (i & 15) & 1)) key += C_LATE;
      if (ready[hp] > tf[cb]) key += (1L << 40) + (ready[hp] - tf[cb]) * 1024;
      if (best < 0 || key < bkey) { best = i; bkey = key; }
    }
    done[best] = true;
    if (!started[cb]) { p.order[cb] = (uint16_t)best; started[cb] = true; }
    else p.order[nq++] = (uint16_t)best;
    if (ready[best >> 5] > tf[cb]) tf[cb] = ready[best >> 5];
    tf[cb] += alen(best & 15);
    if (tf[cb] + C_LAG > fin[best >> 5]) fin[best >> 5] = tf[cb] + C_LAG;
  }
}

}

extern "C" void kernel_launch(void* const* d_in, const int* in_sizes, int n_in, void* d_out, int out_size) {
  const bf16* A_x = (const bf16*)d_in[0];
  const bf16* A_c = (const bf16*)d_in[1];
  const bf16* A_wq = (const bf16*)d_in[2];
  const bf16* A_wuk = (const bf16*)d_in[3];
  const bf16* A_wuv = (const bf16*)d_in[4];
  const bf16* A_wo = (const bf16*)d_in[5];
  const bf16* B_x = (const bf16*)d_in[6];
  const bf16* B_wqkv = (const bf16*)d_in[7];
  const bf16* B_wo = (const bf16*)d_in[8];
  bf16* out = (bf16*)d_out;

  static Params p;
  static bf16 *q, *k, *v, *ctx, *qkvb, *ob;
  static bool init = false;
  if (!init) {
    cudaGetSymbolAddress((void**)&q, g_q);
    cudaGetSymbolAddress((void**)&k, g_k);
    cudaGetSymbolAddress((void**)&v, g_v);
    cudaGetSymbolAddress((void**)&ctx, g_ctx);
    cudaGetSymbolAddress((void**)&qkvb, g_qkvb);
    cudaGetSymbolAddress((void**)&ob, g_ob);
    cudaFuncSetAttribute(mega_kernel, cudaFuncAttributeMaxDynamicSharedMemorySize, SMEM_BYTES);
    build_schedule(p);
    if (p.opt & 2) ctx = q;
    init = true;
  }
  make_map(&p.ta[0], A_x, SEQ, DM, 128, 1);
  make_map(&p.tb[0], A_wq, DM, HHD, 64, 2);
  make_map(&p.tc[0], q, SEQ, HHD, 64, 1);
  make_map(&p.ta[1], A_c, SEQ, DC, 128, 1);
  make_map(&p.tb[1], A_wuk, DC, HHD, 64, 2);
  make_map(&p.tc[1], k, SEQ, HHD, 64, 1);
  make_map(&p.ta[2], A_c, SEQ, DC, 128, 1);
  make_map(&p.tb[2], A_wuv, DC, HHD, 64, 2);
  make_map(&p.tc[2], v, SEQ, HHD, 64, 1);
  make_map(&p.ta[3], B_x, SEQ, DM, 128, 1);
  make_map(&p.tb[3], B_wqkv, DM, 3 * DM, 64, 2);
  make_map(&p.tc[3], qkvb, SEQ, 3 * DM, 64, 1);
  make_map(&p.ta[4], ctx, SEQ, HHD, 128, 1);
  make_map(&p.tb[4], A_wo, HHD, DM, 64, 2);
  make_map(&p.tc[4], out, SEQ, 2 * DM, 64, 1);
  make_map(&p.ta[5], ob, SEQ, DM, 128, 1);
  make_map(&p.tb[5], B_wo, DM, DM, 64, 2);
  make_map(&p.tc[5], out, SEQ, 2 * DM, 64, 1);
  make_map(&p.tq, q, SEQ, HHD, 128, 2);
  make_map(&p.tk, k, SEQ, HHD, 128, 2);
  make_map(&p.tv, v, SEQ, HHD, 128, 2);
  make_map(&p.tl, qkvb, SEQ / 2, 6 * DM, 64, 1);
  make_map(&p.th, qkvb, SEQ / 2, 6 * DM, 72, 1);
  make_map(&p.to, ctx, SEQ, HHD, 128, 2);
  p.ob = ob;
  p.qkvb = qkvb;
  mega_kernel<<<NCTA, 384, SMEM_BYTES, cudaStreamPerThread>>>(p);
}
```

```cpp
#include <cuda_runtime.h>
#include <cuda_bf16.h>
#include <cuda.h>
#include <stdint.h>
#include <string.h>

namespace {

typedef __nv_bfloat16 bf16;

constexpr int SEQ = 2048;
constexpr int NHEAD = 32;
constexpr int HD = 128;
constexpr int DM = 1024;
constexpr int DC = 512;
constexpr int HHD = NHEAD * HD;

__device__ __align__(1024) bf16 g_q[SEQ * HHD];
__device__ __align__(1024) bf16 g_k[SEQ * HHD];
__device__ __align__(1024) bf16 g_v[SEQ * HHD];
__device__ __align__(1024) bf16 g_ctx[SEQ * HHD];
__device__ __align__(1024) bf16 g_qkvb[SEQ * 3 * DM];
__device__ __align__(1024) bf16 g_ob[SEQ * DM];
constexpr int CNT_QKV = 0, CNT_CTX = 16, CNT_QKVB = 32, CNT_DONE = 33, CNT_QUEUE = 34, CNT_OB = 35, CNT_N = 39;
__device__ uint32_t g_cnt[CNT_N * 8];

__device__ __forceinline__ uint32_t smem_u32(const void* p) {
  return static_cast<uint32_t>(__cvta_generic_to_shared(p));
}
__device__ __forceinline__ void mbar_init(uint32_t bar, uint32_t count) {
  asm volatile("mbarrier.init.shared::cta.b64 [%0], %1;" ::"r"(bar), "r"(count) : "memory");
}
__device__ __forceinline__ void mbar_expect_tx(uint32_t bar, uint32_t bytes) {
  asm volatile("mbarrier.arrive.expect_tx.shared::cta.b64 _, [%0], %1;" ::"r"(bar), "r"(bytes) : "memory");
}
__device__ __forceinline__ void mbar_arrive(uint32_t bar) {
  asm volatile("mbarrier.arrive.shared::cta.b64 _, [%0];" ::"r"(bar) : "memory");
}
__device__ __forceinline__ void mbar_arrive_if(uint32_t bar, bool on) {
  asm volatile("{\n.reg .pred p;\nsetp.ne.b32 p, %1, 0;\n@p mbarrier.arrive.shared::cta.b64 _, [%0];\n}" ::"r"(bar),
               "r"((int)on)
               : "memory");
}
__device__ __forceinline__ void mbar_arrive_cluster_if(uint32_t bar, uint32_t cta, bool on) {
  asm volatile(
      "{\n.reg .b32 ra;\n.reg .pred p;\nsetp.ne.b32 p, %2, 0;\nmapa.shared::cluster.u32 ra, %0, %1;\n"
      "@p mbarrier.arrive.shared::cluster.b64 _, [ra];\n}" ::"r"(bar),
      "r"(cta), "r"((int)on)
      : "memory");
}
__device__ __forceinline__ void mbar_arrive_cluster(uint32_t bar, uint32_t cta) {
  asm volatile(
      "{\n.reg .b32 ra;\nmapa.shared::cluster.u32 ra, %0, %1;\n"
      "mbarrier.arrive.shared::cluster.b64 _, [ra];\n}" ::"r"(bar),
      "r"(cta)
      : "memory");
}
__device__ __forceinline__ bool mbar_try_wait(uint32_t bar, uint32_t parity) {
  uint32_t ok;
  asm volatile(
      "{\n.reg .pred p;\nmbarrier.try_wait.parity.shared::cta.b64 p, [%1], %2;\nselp.u32 %0, 1, 0, p;\n}"
      : "=r"(ok)
      : "r"(bar), "r"(parity)
      : "memory");
  return ok != 0;
}
__device__ __forceinline__ bool mbar_test(uint32_t bar, uint32_t parity) {
  uint32_t ok;
  asm volatile(
      "{\n.reg .pred p;\nmbarrier.test_wait.parity.shared::cta.b64 p, [%1], %2;\nselp.u32 %0, 1, 0, p;\n}"
      : "=r"(ok)
      : "r"(bar), "r"(parity)
      : "memory");
  return ok != 0;
}
#define DBG(i, v)
__device__ __forceinline__ void mbar_wait(uint32_t bar, uint32_t parity) {
  asm volatile(
      "{\n.reg .pred p;\n.reg .u32 t;\n"
      "mbarrier.try_wait.parity.shared::cta.b64 p, [%0], %1;\n"
      "@p bra DONE;\n"
      "mov.u32 t, 0x100000;\n"
      "LAB_WAIT:\n"
      "mbarrier.try_wait.parity.shared::cta.b64 p, [%0], %1;\n"
      "@p bra DONE;\n"
      "sub.u32 t, t, 1;\n"
      "setp.ne.u32 p, t, 0;\n"
      "@p bra LAB_WAIT;\n"
      "trap;\n"
      "DONE:\n}" ::"r"(bar),
      "r"(parity)
      : "memory");
}
constexpr uint64_t EV_NORMAL = 0x1000000000000000ull, EV_FIRST = 0x12F0000000000000ull;
__device__ __forceinline__ void tma_load_3d(uint32_t dst, const CUtensorMap* map, int c0, int c1, int c2,
                                            uint32_t bar, uint64_t hint) {
  asm volatile(
      "cp.async.bulk.tensor.3d.shared::cluster.global.mbarrier::complete_tx::bytes.L2::cache_hint [%0], [%1, {%3, %4, %5}], [%2], %6;" ::"r"(dst),
      "l"(map), "r"(bar), "r"(c0), "r"(c1), "r"(c2), "l"(hint)
      : "memory");
}
__device__ __forceinline__ void tma_load_3d_mc(uint32_t dst, const CUtensorMap* map, int c0, int c1, int c2,
                                               uint32_t bar, uint16_t mask, uint64_t hint) {
  asm volatile(
      "cp.async.bulk.tensor.3d.shared::cluster.global.mbarrier::complete_tx::bytes.multicast::cluster.L2::cache_hint [%0], [%1, {%3, %4, %5}], [%2], %6, %7;" ::"r"(dst),
      "l"(map), "r"(bar), "r"(c0), "r"(c1), "r"(c2), "h"(mask), "l"(hint)
      : "memory");
}
__device__ __forceinline__ void tma_prefetch_3d(const CUtensorMap* map, int c0, int c1, int c2) {
  asm volatile("cp.async.bulk.prefetch.tensor.3d.L2.global.tile [%0, {%1, %2, %3}];" ::"l"(map), "r"(c0), "r"(c1), "r"(c2)
               : "memory");
}
__device__ __forceinline__ void tma_store_3d(const CUtensorMap* map, uint32_t src, int c0, int c1, int c2, uint64_t hint) {
  asm volatile("cp.async.bulk.tensor.3d.global.shared::cta.bulk_group.L2::cache_hint [%0, {%2, %3, %4}], [%1], %5;" ::"l"(map),
               "r"(src), "r"(c0), "r"(c1), "r"(c2), "l"(hint)
               : "memory");
}
__device__ __forceinline__ void bulk_commit() { asm volatile("cp.async.bulk.commit_group;" ::: "memory"); }
template <int N>
__device__ __forceinline__ void bulk_wait_read() {
  asm volatile("cp.async.bulk.wait_group.read %0;" ::"n"(N) : "memory");
}
template <int N>
__device__ __forceinline__ void bulk_wait() {
  asm volatile("cp.async.bulk.wait_group %0;" ::"n"(N) : "memory");
}
__device__ __forceinline__ void fence_proxy_async_smem() {
  asm volatile("fence.proxy.async.shared::cta;" ::: "memory");
}
__device__ __forceinline__ void prefetch_tmap(const CUtensorMap* map) {
  asm volatile("prefetch.tensormap [%0];" ::"l"(map) : "memory");
}
__device__ __forceinline__ void cluster_sync_all() {
  asm volatile("barrier.cluster.arrive.relaxed.aligned;\nbarrier.cluster.wait.acquire.aligned;" ::: "memory");
}
__device__ __forceinline__ uint32_t cluster_ctarank() {
  uint32_t r;
  asm volatile("mov.u32 %0, %%cluster_ctarank;" : "=r"(r));
  return r;
}
__device__ __forceinline__ bool elect_one() {
  uint32_t pred;
  asm volatile("{\n.reg .pred P;\nelect.sync _|P, 0xffffffff;\nselp.b32 %0, 1, 0, P;\n}" : "=r"(pred));
  return pred != 0;
}
__device__ __forceinline__ void named_bar_sync(int id, int n) {
  asm volatile("bar.sync %0, %1;" ::"r"(id), "r"(n) : "memory");
}
__device__ __forceinline__ void named_bar_arrive(int id, int n) {
  asm volatile("bar.arrive %0, %1;" ::"r"(id), "r"(n) : "memory");
}
__device__ __forceinline__ void named_bar_sync_if(int id, int n, bool on) {
  asm volatile("{\n.reg .pred p;\nsetp.ne.b32 p, %2, 0;\n@p bar.sync %0, %1;\n}" ::"r"(id), "r"(n), "r"((int)on) : "memory");
}
__device__ __forceinline__ void named_bar_arrive_if(int id, int n, bool on) {
  asm volatile("{\n.reg .pred p;\nsetp.ne.b32 p, %2, 0;\n@p bar.arrive %0, %1;\n}" ::"r"(id), "r"(n), "r"((int)on) : "memory");
}
template <int N>
__device__ __forceinline__ void reg_alloc() {
  asm volatile("setmaxnreg.inc.sync.aligned.u32 %0;" ::"n"(N));
}
template <int N>
__device__ __forceinline__ void reg_dealloc() {
  asm volatile("setmaxnreg.dec.sync.aligned.u32 %0;" ::"n"(N));
}
__device__ __forceinline__ void wgmma_fence() { asm volatile("wgmma.fence.sync.aligned;" ::: "memory"); }
__device__ __forceinline__ void wgmma_commit() { asm volatile("wgmma.commit_group.sync.aligned;" ::: "memory"); }
template <int N>
__device__ __forceinline__ void wgmma_wait() {
  asm volatile("wgmma.wait_group.sync.aligned %0;" ::"n"(N) : "memory");
}
template <int N>
__device__ __forceinline__ void fence_regs(float (&d)[N]) {
#pragma unroll
  for (int i = 0; i < N; i++) asm volatile("" : "+f"(d[i])::"memory");
}
__device__ __forceinline__ void fence_regs(uint32_t (&d)[32]) {
#pragma unroll
  for (int i = 0; i < 16; i++) asm volatile("" : "+r"(d[i])::"memory");
}
template <int N>
__device__ __forceinline__ void undef_regs(float (&d)[N]) {
#pragma unroll
  for (int i = 0; i < N; i++) d[i] = 0.f;
}
template <int N>
__device__ __forceinline__ void undef_regs(uint32_t (&d)[N]) {
#pragma unroll
  for (int i = 0; i < N; i++) d[i] = 0u;
}
__device__ __forceinline__ void sched_fence(float x) {
  asm volatile("{\n.reg .pred p;\nsetp.lt.f32 p, %0, 0f00000000;\n@p trap;\n}" ::"f"(x) : "memory");
}
__device__ __forceinline__ uint32_t pack_bf16(float lo, float hi) {
  uint32_t r;
  asm("cvt.rn.bf16x2.f32 %0, %1, %2;" : "=r"(r) : "f"(hi), "f"(lo));
  return r;
}
__device__ __forceinline__ void stmatrix_x4(uint32_t addr, uint32_t r0, uint32_t r1, uint32_t r2, uint32_t r3) {
  asm volatile("stmatrix.sync.aligned.m8n8.x4.shared.b16 [%0], {%1, %2, %3, %4};" ::"r"(addr), "r"(r0), "r"(r1),
               "r"(r2), "r"(r3)
               : "memory");
}
__device__ __forceinline__ void stmatrix_x4_p(uint32_t addr, uint32_t r0, uint32_t r1, uint32_t r2, uint32_t r3,
                                              bool on) {
  asm volatile("{\n.reg .pred p;\nsetp.ne.b32 p, %5, 0;\n@p stmatrix.sync.aligned.m8n8.x4.shared.b16 [%0], {%1, %2, %3, %4};\n}" ::"r"(addr),
               "r"(r0), "r"(r1), "r"(r2), "r"(r3), "r"((int)on)
               : "memory");
}
__device__ __forceinline__ float ex2(float x) {
  float y;
  asm("ex2.approx.ftz.f32 %0, %1;" : "=f"(y) : "f"(x));
  return y;
}
__device__ __forceinline__ float rcp(float x) {
  float y;
  asm("rcp.approx.ftz.f32 %0, %1;" : "=f"(y) : "f"(x));
  return y;
}
#define BBV 0
__device__ __forceinline__ float ex2v(float x) {
  float y;
  asm volatile("ex2.approx.ftz.f32 %0, %1;" : "=f"(y) : "f"(x));
  return y;
}
__device__ __forceinline__ void ex2_over(float& y, float x, uint32_t k) {
  asm volatile("{\n.reg .pred p;\nsetp.ne.u32 p, %2, 0x7fffffff;\n@p ex2.approx.ftz.f32 %0, %1;\n}" : "+f"(y) : "f"(x), "r"(k));
}
__device__ __forceinline__ float addv(float a, float b) {
  float y;
  asm volatile("add.f32 %0, %1, %2;" : "=f"(y) : "f"(a), "f"(b));
  return y;
}
__device__ __forceinline__ uint32_t packv(float lo, float hi) {
  uint32_t r;
  asm volatile("cvt.rn.bf16x2.f32 %0, %1, %2;" : "=r"(r) : "f"(hi), "f"(lo));
  return r;
}
__device__ __forceinline__ float maskv(float x, int lim, int col) {
  float y;
  asm volatile("{\n.reg .pred p;\nsetp.ge.s32 p, %2, %3;\nselp.f32 %0, %1, 0fFF800000, p;\n}" : "=f"(y) : "f"(x), "r"(lim), "r"(col));
  return y;
}
__device__ __forceinline__ void bb_split(uint32_t x, uint32_t k) {
  asm volatile("{\n.reg .pred p;\nsetp.eq.u32 p, %0, %1;\n@p trap;\n}" ::"r"(x), "r"(0x7fffff00u + k));
}
__device__ __forceinline__ void mbar_arrive_elect(uint32_t bar, bool on) {
  asm volatile("{\n.reg .pred p, q;\nelect.sync _|q, 0xffffffff;\nsetp.ne.and.b32 p, %1, 0, q;\n@p mbarrier.arrive.shared::cta.b64 _, [%0];\n}" ::"r"(bar),
               "r"((int)on)
               : "memory");
}
__device__ __forceinline__ float mbar_test2(uint32_t bar0, uint32_t par0, uint32_t bar1, uint32_t par1) {
  float f;
  asm volatile(
      "{\n.reg .pred p, q;\nmbarrier.test_wait.parity.shared::cta.b64 p, [%1], %2;\n"
      "mbarrier.test_wait.parity.shared::cta.b64 q, [%3], %4;\nand.pred p, p, q;\nselp.f32 %0, 0f00000000, 0f80000000, p;\n}"
      : "=f"(f)
      : "r"(bar0), "r"(par0), "r"(bar1), "r"(par1)
      : "memory");
  return f;
}
__device__ __forceinline__ void mbar_wait_rest(uint32_t bar, uint32_t parity, bool ok) {
  asm volatile(
      "{\n.reg .pred p;\n.reg .u32 t;\n"
      "setp.ne.b32 p, %2, 0;\n"
      "@p bra DONE;\n"
      "mov.u32 t, 0x100000;\n"
      "LAB_WAIT:\n"
      "mbarrier.try_wait.parity.shared::cta.b64 p, [%0], %1;\n"
      "@p bra DONE;\n"
      "sub.u32 t, t, 1;\n"
      "setp.ne.u32 p, t, 0;\n"
      "@p bra LAB_WAIT;\n"
      "trap;\n"
      "DONE:\n}" ::"r"(bar),
      "r"(parity), "r"((int)ok)
      : "memory");
}
__device__ __forceinline__ void cnt_signal(int idx, uint32_t inc = 1) {
  asm volatile("red.release.gpu.global.add.u32 [%0], %1;" ::"l"(g_cnt + idx * 8), "r"(inc) : "memory");
}
__device__ __forceinline__ void cnt_signal_done(int idx, uint32_t inc = 1) {
  asm volatile("red.relaxed.gpu.global.add.u32 [%0], %1;" ::"l"(g_cnt + idx * 8), "r"(inc) : "memory");
}
__device__ __forceinline__ uint32_t cnt_next(int idx) {
  uint32_t v;
  asm volatile("atom.relaxed.gpu.global.add.u32 %0, [%1], 1;" : "=r"(v) : "l"(g_cnt + idx * 8) : "memory");
  return v;
}
__device__ __forceinline__ uint32_t cnt_peek(int idx) {
  uint32_t v;
  asm volatile("ld.acquire.gpu.global.u32 %0, [%1];" : "=r"(v) : "l"(g_cnt + idx * 8) : "memory");
  return v;
}
__device__ __forceinline__ void cnt_wait(int idx, uint32_t target) {
  asm volatile(
      "{\n.reg .pred p;\n.reg .u32 v, t0, t1;\n"
      "ld.acquire.gpu.global.u32 v, [%0];\n"
      "setp.ge.u32 p, v, %1;\n"
      "@p bra DONE;\n"
      "mov.u32 t0, %%clock;\n"
      "LAB_WAIT:\n"
      "nanosleep.u32 100;\n"
      "ld.acquire.gpu.global.u32 v, [%0];\n"
      "setp.ge.u32 p, v, %1;\n"
      "@p bra DONE;\n"
      "mov.u32 t1, %%clock;\n"
      "sub.u32 t1, t1, t0;\n"
      "setp.lt.u32 p, t1, 0x80000000;\n"
      "@p bra LAB_WAIT;\n"
      "trap;\n"
      "DONE:\n}" ::"l"(g_cnt + idx * 8),
      "r"(target)
      : "memory");
}
__device__ __forceinline__ void cnt_wait_bit(int idx, uint32_t bit, uint32_t& v) {
  asm volatile(
      "{\n.reg .pred p;\n.reg .u32 x, t0, t1;\n"
      "and.b32 x, %0, %2;\n"
      "setp.ne.u32 p, x, 0;\n"
      "@p bra DONE;\n"
      "mov.u32 t0, %%clock;\n"
      "LAB_WAIT:\n"
      "ld.acquire.gpu.global.u32 %0, [%1];\n"
      "and.b32 x, %0, %2;\n"
      "setp.ne.u32 p, x, 0;\n"
      "@p bra DONE;\n"
      "nanosleep.u32 64;\n"
      "mov.u32 t1, %%clock;\n"
      "sub.u32 t1, t1, t0;\n"
      "setp.lt.u32 p, t1, 0x80000000;\n"
      "@p bra LAB_WAIT;\n"
      "trap;\n"
      "DONE:\n}" : "+r"(v) : "l"(g_cnt + idx * 8),
      "r"(bit)
      : "memory");
}
__device__ __forceinline__ bool cnt_done(uint32_t total) {
  uint32_t old;
  asm volatile("atom.acq_rel.gpu.global.add.u32 %0, [%1], 1;" : "=r"(old) : "l"(g_cnt + CNT_DONE * 8) : "memory");
  return old == total - 1;
}
__device__ __forceinline__ void cnt_rearm() {
#pragma unroll
  for (int i = 0; i < CNT_N; i++) g_cnt[i * 8] = 0;
}
__device__ __forceinline__ void fence_proxy_async_global() { asm volatile("fence.proxy.async.global;" ::: "memory"); }
__device__ __forceinline__ void mma_16816(float (&c)[4], uint32_t a0, uint32_t a1, uint32_t a2, uint32_t a3,
                                          uint32_t b0, uint32_t b1) {
  asm("mma.sync.aligned.m16n8k16.row.col.f32.bf16.bf16.f32 {%0, %1, %2, %3}, {%4, %5, %6, %7}, {%8, %9}, {%0, %1, %2, %3};"
      : "+f"(c[0]), "+f"(c[1]), "+f"(c[2]), "+f"(c[3])
      : "r"(a0), "r"(a1), "r"(a2), "r"(a3), "r"(b0), "r"(b1));
}
__device__ __forceinline__ void mma_1688(float (&c)[4], uint32_t a0, uint32_t a1, uint32_t b0) {
  asm("mma.sync.aligned.m16n8k8.row.col.f32.bf16.bf16.f32 {%0, %1, %2, %3}, {%4, %5}, {%6}, {%0, %1, %2, %3};"
      : "+f"(c[0]), "+f"(c[1]), "+f"(c[2]), "+f"(c[3])
      : "r"(a0), "r"(a1), "r"(b0));
}
__device__ __forceinline__ uint32_t movm_t(uint32_t a) {
  uint32_t d;
  asm("movmatrix.sync.aligned.m8n8.trans.b16 %0, %1;" : "=r"(d) : "r"(a));
  return d;
}
__device__ __forceinline__ uint4 ldg128(const bf16* p) {
  uint4 v;
  asm volatile("ld.global.v4.u32 {%0, %1, %2, %3}, [%4];" : "=r"(v.x), "=r"(v.y), "=r"(v.z), "=r"(v.w) : "l"(p) : "memory");
  return v;
}
#define TL(role, code)
#define TL0(code)
#define TL_DECL
#define TR_DECL
#define TR(code)
#define TRI(id, code)
#define TW_DECL
#define TW(w, stmt) stmt
#define TW_FLUSH()
#define TW_END()

__device__ __forceinline__ uint32_t make_desc(uint32_t addr, uint32_t lbo_bytes) {
  return (addr >> 4) + ((lbo_bytes >> 4) << 16);
}

__device__ __forceinline__ void wgmma_ss_n256_tb(float (&d)[128], uint32_t da, uint32_t db, int scale_d) {
  asm volatile("{\n.reg .pred p;\n.reg .b64 a, b;\nsetp.ne.b32 p, %130, 0;\nmov.b64 a, {%128, 0x40000040};\nmov.b64 b, {%129, 0x40000040};\n"
    "wgmma.mma_async.sync.aligned.m64n256k16.f32.bf16.bf16 {%0, %1, %2, %3, %4, %5, %6, %7, %8, %9, %10, %11, %12, %13, %14, %15, %16, %17, %18, %19, %20, %21, %22, %23, %24, %25, %26, %27, %28, %29, %30, %31, %32, %33, %34, %35, %36, %37, %38, %39, %40, %41, %42, %43, %44, %45, %46, %47, %48, %49, %50, %51, %52, %53, %54, %55, %56, %57, %58, %59, %60, %61, %62, %63, %64, %65, %66, %67, %68, %69, %70, %71, %72, %73, %74, %75, %76, %77, %78, %79, %80, %81, %82, %83, %84, %85, %86, %87, %88, %89, %90, %91, %92, %93, %94, %95, %96, %97, %98, %99, %100, %101, %102, %103, %104, %105, %106, %107, %108, %109, %110, %111, %112, %113, %114, %115, %116, %117, %118, %119, %120, %121, %122, %123, %124, %125, %126, %127}, a, b, p, 1, 1, 0, 1;\n}\n"
    : "+f"(d[0]), "+f"(d[1]), "+f"(d[2]), "+f"(d[3]), "+f"(d[4]), "+f"(d[5]), "+f"(d[6]), "+f"(d[7]), "+f"(d[8]), "+f"(d[9]), "+f"(d[10]), "+f"(d[11]), "+f"(d[12]), "+f"(d[13]), "+f"(d[14]), "+f"(d[15]), "+f"(d[16]), "+f"(d[17]), "+f"(d[18]), "+f"(d[19]), "+f"(d[20]), "+f"(d[21]), "+f"(d[22]), "+f"(d[23]), "+f"(d[24]), "+f"(d[25]), "+f"(d[26]), "+f"(d[27]), "+f"(d[28]), "+f"(d[29]), "+f"(d[30]), "+f"(d[31]), "+f"(d[32]), "+f"(d[33]), "+f"(d[34]), "+f"(d[35]), "+f"(d[36]), "+f"(d[37]), "+f"(d[38]), "+f"(d[39]), "+f"(d[40]), "+f"(d[41]), "+f"(d[42]), "+f"(d[43]), "+f"(d[44]), "+f"(d[45]), "+f"(d[46]), "+f"(d[47]), "+f"(d[48]), "+f"(d[49]), "+f"(d[50]), "+f"(d[51]), "+f"(d[52]), "+f"(d[53]), "+f"(d[54]), "+f"(d[55]), "+f"(d[56]), "+f"(d[57]), "+f"(d[58]), "+f"(d[59]), "+f"(d[60]), "+f"(d[61]), "+f"(d[62]), "+f"(d[63]), "+f"(d[64]), "+f"(d[65]), "+f"(d[66]), "+f"(d[67]), "+f"(d[68]), "+f"(d[69]), "+f"(d[70]), "+f"(d[71]), "+f"(d[72]), "+f"(d[73]), "+f"(d[74]), "+f"(d[75]), "+f"(d[76]), "+f"(d[77]), "+f"(d[78]), "+f"(d[79]), "+f"(d[80]), "+f"(d[81]), "+f"(d[82]), "+f"(d[83]), "+f"(d[84]), "+f"(d[85]), "+f"(d[86]), "+f"(d[87]), "+f"(d[88]), "+f"(d[89]), "+f"(d[90]), "+f"(d[91]), "+f"(d[92]), "+f"(d[93]), "+f"(d[94]), "+f"(d[95]), "+f"(d[96]), "+f"(d[97]), "+f"(d[98]), "+f"(d[99]), "+f"(d[100]), "+f"(d[101]), "+f"(d[102]), "+f"(d[103]), "+f"(d[104]), "+f"(d[105]), "+f"(d[106]), "+f"(d[107]), "+f"(d[108]), "+f"(d[109]), "+f"(d[110]), "+f"(d[111]), "+f"(d[112]), "+f"(d[113]), "+f"(d[114]), "+f"(d[115]), "+f"(d[116]), "+f"(d[117]), "+f"(d[118]), "+f"(d[119]), "+f"(d[120]), "+f"(d[121]), "+f"(d[122]), "+f"(d[123]), "+f"(d[124]), "+f"(d[125]), "+f"(d[126]), "+f"(d[127])
    : "r"(da), "r"(db), "r"(scale_d));
}
__device__ __forceinline__ void wgmma_ss_n128(float (&d)[64], uint32_t da, uint32_t db, int scale_d) {
  asm volatile("{\n.reg .pred p;\n.reg .b64 a, b;\nsetp.ne.b32 p, %66, 0;\nmov.b64 a, {%64, 0x40000040};\nmov.b64 b, {%65, 0x40000040};\n"
    "wgmma.mma_async.sync.aligned.m64n128k16.f32.bf16.bf16 {%0, %1, %2, %3, %4, %5, %6, %7, %8, %9, %10, %11, %12, %13, %14, %15, %16, %17, %18, %19, %20, %21, %22, %23, %24, %25, %26, %27, %28, %29, %30, %31, %32, %33, %34, %35, %36, %37, %38, %39, %40, %41, %42, %43, %44, %45, %46, %47, %48, %49, %50, %51, %52, %53, %54, %55, %56, %57, %58, %59, %60, %61, %62, %63}, a, b, p, 1, 1, 0, 0;\n}\n"
    : "+f"(d[0]), "+f"(d[1]), "+f"(d[2]), "+f"(d[3]), "+f"(d[4]), "+f"(d[5]), "+f"(d[6]), "+f"(d[7]), "+f"(d[8]), "+f"(d[9]), "+f"(d[10]), "+f"(d[11]), "+f"(d[12]), "+f"(d[13]), "+f"(d[14]), "+f"(d[15]), "+f"(d[16]), "+f"(d[17]), "+f"(d[18]), "+f"(d[19]), "+f"(d[20]), "+f"(d[21]), "+f"(d[22]), "+f"(d[23]), "+f"(d[24]), "+f"(d[25]), "+f"(d[26]), "+f"(d[27]), "+f"(d[28]), "+f"(d[29]), "+f"(d[30]), "+f"(d[31]), "+f"(d[32]), "+f"(d[33]), "+f"(d[34]), "+f"(d[35]), "+f"(d[36]), "+f"(d[37]), "+f"(d[38]), "+f"(d[39]), "+f"(d[40]), "+f"(d[41]), "+f"(d[42]), "+f"(d[43]), "+f"(d[44]), "+f"(d[45]), "+f"(d[46]), "+f"(d[47]), "+f"(d[48]), "+f"(d[49]), "+f"(d[50]), "+f"(d[51]), "+f"(d[52]), "+f"(d[53]), "+f"(d[54]), "+f"(d[55]), "+f"(d[56]), "+f"(d[57]), "+f"(d[58]), "+f"(d[59]), "+f"(d[60]), "+f"(d[61]), "+f"(d[62]), "+f"(d[63])
    : "r"(da), "r"(db), "r"(scale_d));
}
__device__ __forceinline__ void wgmma_ss_n64(float (&d)[32], uint32_t da, uint32_t db, int scale_d) {
  asm volatile("{\n.reg .pred p;\n.reg .b64 a, b;\nsetp.ne.b32 p, %34, 0;\nmov.b64 a, {%32, 0x40000040};\nmov.b64 b, {%33, 0x40000040};\n"
    "wgmma.mma_async.sync.aligned.m64n64k16.f32.bf16.bf16 {%0, %1, %2, %3, %4, %5, %6, %7, %8, %9, %10, %11, %12, %13, %14, %15, %16, %17, %18, %19, %20, %21, %22, %23, %24, %25, %26, %27, %28, %29, %30, %31}, a, b, p, 1, 1, 0, 0;\n}\n"
    : "+f"(d[0]), "+f"(d[1]), "+f"(d[2]), "+f"(d[3]), "+f"(d[4]), "+f"(d[5]), "+f"(d[6]), "+f"(d[7]), "+f"(d[8]), "+f"(d[9]), "+f"(d[10]), "+f"(d[11]), "+f"(d[12]), "+f"(d[13]), "+f"(d[14]), "+f"(d[15]), "+f"(d[16]), "+f"(d[17]), "+f"(d[18]), "+f"(d[19]), "+f"(d[20]), "+f"(d[21]), "+f"(d[22]), "+f"(d[23]), "+f"(d[24]), "+f"(d[25]), "+f"(d[26]), "+f"(d[27]), "+f"(d[28]), "+f"(d[29]), "+f"(d[30]), "+f"(d[31])
    : "r"(da), "r"(db), "r"(scale_d));
}
__device__ __forceinline__ void wgmma_rs_n128_tb(float (&d)[64], uint32_t a0, uint32_t a1, uint32_t a2, uint32_t a3, uint32_t db, int scale_d) {
  asm volatile("{\n.reg .pred p;\n.reg .b64 b;\nsetp.ne.b32 p, %69, 0;\nmov.b64 b, {%68, 0x40000040};\n"
    "wgmma.mma_async.sync.aligned.m64n128k16.f32.bf16.bf16 {%0, %1, %2, %3, %4, %5, %6, %7, %8, %9, %10, %11, %12, %13, %14, %15, %16, %17, %18, %19, %20, %21, %22, %23, %24, %25, %26, %27, %28, %29, %30, %31, %32, %33, %34, %35, %36, %37, %38, %39, %40, %41, %42, %43, %44, %45, %46, %47, %48, %49, %50, %51, %52, %53, %54, %55, %56, %57, %58, %59, %60, %61, %62, %63}, {%64, %65, %66, %67}, b, p, 1, 1, 1;\n}\n"
    : "+f"(d[0]), "+f"(d[1]), "+f"(d[2]), "+f"(d[3]), "+f"(d[4]), "+f"(d[5]), "+f"(d[6]), "+f"(d[7]), "+f"(d[8]), "+f"(d[9]), "+f"(d[10]), "+f"(d[11]), "+f"(d[12]), "+f"(d[13]), "+f"(d[14]), "+f"(d[15]), "+f"(d[16]), "+f"(d[17]), "+f"(d[18]), "+f"(d[19]), "+f"(d[20]), "+f"(d[21]), "+f"(d[22]), "+f"(d[23]), "+f"(d[24]), "+f"(d[25]), "+f"(d[26]), "+f"(d[27]), "+f"(d[28]), "+f"(d[29]), "+f"(d[30]), "+f"(d[31]), "+f"(d[32]), "+f"(d[33]), "+f"(d[34]), "+f"(d[35]), "+f"(d[36]), "+f"(d[37]), "+f"(d[38]), "+f"(d[39]), "+f"(d[40]), "+f"(d[41]), "+f"(d[42]), "+f"(d[43]), "+f"(d[44]), "+f"(d[45]), "+f"(d[46]), "+f"(d[47]), "+f"(d[48]), "+f"(d[49]), "+f"(d[50]), "+f"(d[51]), "+f"(d[52]), "+f"(d[53]), "+f"(d[54]), "+f"(d[55]), "+f"(d[56]), "+f"(d[57]), "+f"(d[58]), "+f"(d[59]), "+f"(d[60]), "+f"(d[61]), "+f"(d[62]), "+f"(d[63])
    : "r"(a0), "r"(a1), "r"(a2), "r"(a3), "r"(db), "r"(scale_d));
}
__device__ __forceinline__ void wgmma_ss_n72_init(float (&d)[36], uint32_t da, uint32_t db) {
  asm volatile("{\n.reg .pred p;\n.reg .b64 a, b;\nsetp.ne.b32 p, 0, 0;\nmov.b64 a, {%36, 0x40000040};\nmov.b64 b, {%37, 0x40000040};\n"
    "wgmma.mma_async.sync.aligned.m64n72k16.f32.bf16.bf16 {%0, %1, %2, %3, %4, %5, %6, %7, %8, %9, %10, %11, %12, %13, %14, %15, %16, %17, %18, %19, %20, %21, %22, %23, %24, %25, %26, %27, %28, %29, %30, %31, %32, %33, %34, %35}, a, b, p, 1, 1, 0, 0;\n}\n"
    : "=f"(d[0]), "=f"(d[1]), "=f"(d[2]), "=f"(d[3]), "=f"(d[4]), "=f"(d[5]), "=f"(d[6]), "=f"(d[7]), "=f"(d[8]), "=f"(d[9]), "=f"(d[10]), "=f"(d[11]), "=f"(d[12]), "=f"(d[13]), "=f"(d[14]), "=f"(d[15]), "=f"(d[16]), "=f"(d[17]), "=f"(d[18]), "=f"(d[19]), "=f"(d[20]), "=f"(d[21]), "=f"(d[22]), "=f"(d[23]), "=f"(d[24]), "=f"(d[25]), "=f"(d[26]), "=f"(d[27]), "=f"(d[28]), "=f"(d[29]), "=f"(d[30]), "=f"(d[31]), "=f"(d[32]), "=f"(d[33]), "=f"(d[34]), "=f"(d[35])
    : "r"(da), "r"(db));
}
__device__ __forceinline__ void wgmma_ss_n72(float (&d)[36], uint32_t da, uint32_t db, int scale_d) {
  asm volatile("{\n.reg .pred p;\n.reg .b64 a, b;\nsetp.ne.b32 p, %38, 0;\nmov.b64 a, {%36, 0x40000040};\nmov.b64 b, {%37, 0x40000040};\n"
    "wgmma.mma_async.sync.aligned.m64n72k16.f32.bf16.bf16 {%0, %1, %2, %3, %4, %5, %6, %7, %8, %9, %10, %11, %12, %13, %14, %15, %16, %17, %18, %19, %20, %21, %22, %23, %24, %25, %26, %27, %28, %29, %30, %31, %32, %33, %34, %35}, a, b, p, 1, 1, 0, 0;\n}\n"
    : "+f"(d[0]), "+f"(d[1]), "+f"(d[2]), "+f"(d[3]), "+f"(d[4]), "+f"(d[5]), "+f"(d[6]), "+f"(d[7]), "+f"(d[8]), "+f"(d[9]), "+f"(d[10]), "+f"(d[11]), "+f"(d[12]), "+f"(d[13]), "+f"(d[14]), "+f"(d[15]), "+f"(d[16]), "+f"(d[17]), "+f"(d[18]), "+f"(d[19]), "+f"(d[20]), "+f"(d[21]), "+f"(d[22]), "+f"(d[23]), "+f"(d[24]), "+f"(d[25]), "+f"(d[26]), "+f"(d[27]), "+f"(d[28]), "+f"(d[29]), "+f"(d[30]), "+f"(d[31]), "+f"(d[32]), "+f"(d[33]), "+f"(d[34]), "+f"(d[35])
    : "r"(da), "r"(db), "r"(scale_d));
}
__device__ __forceinline__ void wgmma_rs_n32_tb_init(float (&d)[16], uint32_t a0, uint32_t a1, uint32_t a2, uint32_t a3, uint32_t db) {
  asm volatile("{\n.reg .pred p;\n.reg .b64 b;\nsetp.ne.b32 p, 0, 0;\nmov.b64 b, {%20, 0x40000040};\n"
    "wgmma.mma_async.sync.aligned.m64n32k16.f32.bf16.bf16 {%0, %1, %2, %3, %4, %5, %6, %7, %8, %9, %10, %11, %12, %13, %14, %15}, {%16, %17, %18, %19}, b, p, 1, 1, 1;\n}\n"
    : "=f"(d[0]), "=f"(d[1]), "=f"(d[2]), "=f"(d[3]), "=f"(d[4]), "=f"(d[5]), "=f"(d[6]), "=f"(d[7]), "=f"(d[8]), "=f"(d[9]), "=f"(d[10]), "=f"(d[11]), "=f"(d[12]), "=f"(d[13]), "=f"(d[14]), "=f"(d[15])
    : "r"(a0), "r"(a1), "r"(a2), "r"(a3), "r"(db));
}
__device__ __forceinline__ void wgmma_rs_n32_tb(float (&d)[16], uint32_t a0, uint32_t a1, uint32_t a2, uint32_t a3, uint32_t db, int scale_d) {
  asm volatile("{\n.reg .pred p;\n.reg .b64 b;\nsetp.ne.b32 p, %21, 0;\nmov.b64 b, {%20, 0x40000040};\n"
    "wgmma.mma_async.sync.aligned.m64n32k16.f32.bf16.bf16 {%0, %1, %2, %3, %4, %5, %6, %7, %8, %9, %10, %11, %12, %13, %14, %15}, {%16, %17, %18, %19}, b, p, 1, 1, 1;\n}\n"
    : "+f"(d[0]), "+f"(d[1]), "+f"(d[2]), "+f"(d[3]), "+f"(d[4]), "+f"(d[5]), "+f"(d[6]), "+f"(d[7]), "+f"(d[8]), "+f"(d[9]), "+f"(d[10]), "+f"(d[11]), "+f"(d[12]), "+f"(d[13]), "+f"(d[14]), "+f"(d[15])
    : "r"(a0), "r"(a1), "r"(a2), "r"(a3), "r"(db), "r"(scale_d));
}
template <int OA, int OB>
__device__ __forceinline__ void wgmma_ss_n128_tb(float (&d)[64], uint32_t da, uint32_t db, int scale_d) {
  asm volatile("{\n.reg .pred p;\n.reg .b64 a, b;\n.reg .b32 x, y;\nsetp.ne.b32 p, %66, 0;\nadd.u32 x, %64, %67;\nadd.u32 y, %65, %68;\nmov.b64 a, {x, 0x40000040};\nmov.b64 b, {y, 0x40000040};\n"
    "wgmma.mma_async.sync.aligned.m64n128k16.f32.bf16.bf16 {%0, %1, %2, %3, %4, %5, %6, %7, %8, %9, %10, %11, %12, %13, %14, %15, %16, %17, %18, %19, %20, %21, %22, %23, %24, %25, %26, %27, %28, %29, %30, %31, %32, %33, %34, %35, %36, %37, %38, %39, %40, %41, %42, %43, %44, %45, %46, %47, %48, %49, %50, %51, %52, %53, %54, %55, %56, %57, %58, %59, %60, %61, %62, %63}, a, b, p, 1, 1, 0, 1;\n}\n"
    : "+f"(d[0]), "+f"(d[1]), "+f"(d[2]), "+f"(d[3]), "+f"(d[4]), "+f"(d[5]), "+f"(d[6]), "+f"(d[7]), "+f"(d[8]), "+f"(d[9]), "+f"(d[10]), "+f"(d[11]), "+f"(d[12]), "+f"(d[13]), "+f"(d[14]), "+f"(d[15]), "+f"(d[16]), "+f"(d[17]), "+f"(d[18]), "+f"(d[19]), "+f"(d[20]), "+f"(d[21]), "+f"(d[22]), "+f"(d[23]), "+f"(d[24]), "+f"(d[25]), "+f"(d[26]), "+f"(d[27]), "+f"(d[28]), "+f"(d[29]), "+f"(d[30]), "+f"(d[31]), "+f"(d[32]), "+f"(d[33]), "+f"(d[34]), "+f"(d[35]), "+f"(d[36]), "+f"(d[37]), "+f"(d[38]), "+f"(d[39]), "+f"(d[40]), "+f"(d[41]), "+f"(d[42]), "+f"(d[43]), "+f"(d[44]), "+f"(d[45]), "+f"(d[46]), "+f"(d[47]), "+f"(d[48]), "+f"(d[49]), "+f"(d[50]), "+f"(d[51]), "+f"(d[52]), "+f"(d[53]), "+f"(d[54]), "+f"(d[55]), "+f"(d[56]), "+f"(d[57]), "+f"(d[58]), "+f"(d[59]), "+f"(d[60]), "+f"(d[61]), "+f"(d[62]), "+f"(d[63])
    : "r"(da), "r"(db), "r"(scale_d), "n"(OA), "n"(OB));
}
template <int OA, int OB>
__device__ __forceinline__ void wgmma_ss_n256_tbo(float (&d)[128], uint32_t da, uint32_t db, int scale_d) {
  asm volatile("{\n.reg .pred p;\n.reg .b64 a, b;\n.reg .b32 x, y;\nsetp.ne.b32 p, %130, 0;\nadd.u32 x, %128, %131;\nadd.u32 y, %129, %132;\nmov.b64 a, {x, 0x40000040};\nmov.b64 b, {y, 0x40000040};\n"
    "wgmma.mma_async.sync.aligned.m64n256k16.f32.bf16.bf16 {%0, %1, %2, %3, %4, %5, %6, %7, %8, %9, %10, %11, %12, %13, %14, %15, %16, %17, %18, %19, %20, %21, %22, %23, %24, %25, %26, %27, %28, %29, %30, %31, %32, %33, %34, %35, %36, %37, %38, %39, %40, %41, %42, %43, %44, %45, %46, %47, %48, %49, %50, %51, %52, %53, %54, %55, %56, %57, %58, %59, %60, %61, %62, %63, %64, %65, %66, %67, %68, %69, %70, %71, %72, %73, %74, %75, %76, %77, %78, %79, %80, %81, %82, %83, %84, %85, %86, %87, %88, %89, %90, %91, %92, %93, %94, %95, %96, %97, %98, %99, %100, %101, %102, %103, %104, %105, %106, %107, %108, %109, %110, %111, %112, %113, %114, %115, %116, %117, %118, %119, %120, %121, %122, %123, %124, %125, %126, %127}, a, b, p, 1, 1, 0, 1;\n}\n"
    : "+f"(d[0]), "+f"(d[1]), "+f"(d[2]), "+f"(d[3]), "+f"(d[4]), "+f"(d[5]), "+f"(d[6]), "+f"(d[7]), "+f"(d[8]), "+f"(d[9]), "+f"(d[10]), "+f"(d[11]), "+f"(d[12]), "+f"(d[13]), "+f"(d[14]), "+f"(d[15]), "+f"(d[16]), "+f"(d[17]), "+f"(d[18]), "+f"(d[19]), "+f"(d[20]), "+f"(d[21]), "+f"(d[22]), "+f"(d[23]), "+f"(d[24]), "+f"(d[25]), "+f"(d[26]), "+f"(d[27]), "+f"(d[28]), "+f"(d[29]), "+f"(d[30]), "+f"(d[31]), "+f"(d[32]), "+f"(d[33]), "+f"(d[34]), "+f"(d[35]), "+f"(d[36]), "+f"(d[37]), "+f"(d[38]), "+f"(d[39]), "+f"(d[40]), "+f"(d[41]), "+f"(d[42]), "+f"(d[43]), "+f"(d[44]), "+f"(d[45]), "+f"(d[46]), "+f"(d[47]), "+f"(d[48]), "+f"(d[49]), "+f"(d[50]), "+f"(d[51]), "+f"(d[52]), "+f"(d[53]), "+f"(d[54]), "+f"(d[55]), "+f"(d[56]), "+f"(d[57]), "+f"(d[58]), "+f"(d[59]), "+f"(d[60]), "+f"(d[61]), "+f"(d[62]), "+f"(d[63]), "+f"(d[64]), "+f"(d[65]), "+f"(d[66]), "+f"(d[67]), "+f"(d[68]), "+f"(d[69]), "+f"(d[70]), "+f"(d[71]), "+f"(d[72]), "+f"(d[73]), "+f"(d[74]), "+f"(d[75]), "+f"(d[76]), "+f"(d[77]), "+f"(d[78]), "+f"(d[79]), "+f"(d[80]), "+f"(d[81]), "+f"(d[82]), "+f"(d[83]), "+f"(d[84]), "+f"(d[85]), "+f"(d[86]), "+f"(d[87]), "+f"(d[88]), "+f"(d[89]), "+f"(d[90]), "+f"(d[91]), "+f"(d[92]), "+f"(d[93]), "+f"(d[94]), "+f"(d[95]), "+f"(d[96]), "+f"(d[97]), "+f"(d[98]), "+f"(d[99]), "+f"(d[100]), "+f"(d[101]), "+f"(d[102]), "+f"(d[103]), "+f"(d[104]), "+f"(d[105]), "+f"(d[106]), "+f"(d[107]), "+f"(d[108]), "+f"(d[109]), "+f"(d[110]), "+f"(d[111]), "+f"(d[112]), "+f"(d[113]), "+f"(d[114]), "+f"(d[115]), "+f"(d[116]), "+f"(d[117]), "+f"(d[118]), "+f"(d[119]), "+f"(d[120]), "+f"(d[121]), "+f"(d[122]), "+f"(d[123]), "+f"(d[124]), "+f"(d[125]), "+f"(d[126]), "+f"(d[127])
    : "r"(da), "r"(db), "r"(scale_d), "n"(OA), "n"(OB));
}

constexpr int NCTA = 132;
constexpr int NCLUSTER = 66;
constexpr int NPROB = 6;
#define DO_LOCAL true
#define DO_ATT true
#define NA_CL_ 32
#define NITEMS 512
constexpr int G1_MAX = 24, NA_CL = NA_CL_, NB_CTA = NCTA - 2 * NA_CL;
constexpr int TILE32K = 32768;
constexpr uint32_t DBASE = 1024;
constexpr int OFF_STG = 4 * TILE32K;
constexpr int OFF_A = 5 * TILE32K;
constexpr int OFF_BAR = 7 * TILE32K;
constexpr int L_K = 8192, L_V = L_K + 9216, L_P = L_V + 9216;
constexpr int SMEM_BYTES = OFF_BAR + 1024;
constexpr int B_GFULL = 0, B_GEMPTY = 32, B_AFULL = 64, B_AEMPTY = 104, B_QFULL = 144, B_QEMPTY = 160,
              B_SFULL = 176, B_SEMPTY = 208, B_OFULL = 240, B_STGFREE = 256, S_CODE = 272, B_SFULL2 = 304;
#define ASL 4
constexpr int A_SLOTS = ASL;
#define FS 2
#define HW 1
#define PACE 900u
#define REG_C 232
#define REG_P 40

struct Params {
  CUtensorMap ta[NPROB];
  CUtensorMap tb[NPROB];
  CUtensorMap tc[NPROB];
  CUtensorMap tq, tk, tv, to, tl, th;
  bf16* ob;
  const bf16* qkvb;
  int opt;
  uint16_t g[NCLUSTER][G1_MAX];
  uint16_t order[512];
};
__device__ __forceinline__ uint32_t tail_item(uint32_t code) {
  return (code & 0x7FFF) < 64 ? (5u << 8) | ((code & 4) << 4) | (code & 0x33) : 0xFFFFu;
}
#define HM 0x39383F30
#define HINT(b) ((HM >> (b) & 1) ? EV_FIRST : EV_NORMAL)
__device__ __forceinline__ uint32_t lds32(uint32_t a) {
  uint32_t v;
  asm volatile("ld.shared.u32 %0, [%1];" : "=r"(v) : "r"(a) : "memory");
  return v;
}
__device__ __forceinline__ uint4 lds128(uint32_t a) {
  uint4 v;
  asm volatile("ld.shared.v4.u32 {%0, %1, %2, %3}, [%4];" : "=r"(v.x), "=r"(v.y), "=r"(v.z), "=r"(v.w) : "r"(a) : "memory");
  return v;
}
__device__ __forceinline__ void sts64(uint32_t a, float x, float y) {
  asm volatile("st.shared.v2.f32 [%0], {%1, %2};" ::"r"(a), "f"(x), "f"(y) : "memory");
}
__device__ __forceinline__ void sts32(uint32_t a, uint32_t v) {
  asm volatile("st.shared.u32 [%0], %1;" ::"r"(a), "r"(v) : "memory");
}
__device__ __forceinline__ uint32_t opaque_tid() {
  uint32_t t;
  asm volatile("mov.u32 %0, %%tid.x;" : "=r"(t));
  return t;
}
__device__ __forceinline__ uint32_t stg_off(uint32_t tid) {
  return (tid >> 5) * 2048 + (tid & 15) * 128 + ((((tid >> 4) & 1) ^ (tid & 7)) << 4);
}
__device__ __forceinline__ int prob_nkb4(int prob) { return (0x4F4224 >> (prob * 4) & 15) + (prob == 4); }

constexpr float SM_C = 0.08838834764831845f * 1.4426950408889634f;
constexpr float SM_HI = 1099511627776.0f;
constexpr float SM_LO = 8.673617379884035e-19f;
__device__ __forceinline__ void softmax_max(const float (&s)[64], float& a0, float& a1) {
  a0 = fmaxf(s[0], s[1]);
  a1 = fmaxf(s[2], s[3]);
#pragma unroll
  for (int j = 1; j < 16; j++) {
    a0 = fmaxf(a0, fmaxf(s[4 * j], s[4 * j + 1]));
    a1 = fmaxf(a1, fmaxf(s[4 * j + 2], s[4 * j + 3]));
  }
  a0 = fmaxf(a0, __shfl_xor_sync(0xffffffffu, a0, 1));
  a1 = fmaxf(a1, __shfl_xor_sync(0xffffffffu, a1, 1));
  a0 = fmaxf(a0, __shfl_xor_sync(0xffffffffu, a0, 2));
  a1 = fmaxf(a1, __shfl_xor_sync(0xffffffffu, a1, 2));
}
template <int J0, int J1, bool OFS, int N>
__device__ __forceinline__ void softmax_exp(const float (&s)[64], float b0, float b1, uint32_t (&out)[N], float& t0,
                                            float& t1) {
#pragma unroll
  for (int j = J0; j < J1; j++) {
    const float e0 = ex2(OFS ? s[4 * j] + b0 : s[4 * j]);
    const float e1 = ex2(OFS ? s[4 * j + 1] + b0 : s[4 * j + 1]);
    const float e2 = ex2(OFS ? s[4 * j + 2] + b1 : s[4 * j + 2]);
    const float e3 = ex2(OFS ? s[4 * j + 3] + b1 : s[4 * j + 3]);
    t0 += e0 + e1;
    t1 += e2 + e3;
    out[2 * j] = pack_bf16(e0, e1);
    out[2 * j + 1] = pack_bf16(e2, e3);
  }
}

__device__ __forceinline__ uint32_t scale_q(uint32_t x) {
  uint32_t t, y;
  asm("mul.rn.bf16x2 %0, %1, %2;" : "=r"(t) : "r"(x), "r"(0xb9d8b9d8u));
  asm("fma.rn.bf16x2 %0, %1, %2, %3;" : "=r"(y) : "r"(x), "r"(0x3e033e03u), "r"(t));
  return y;
}

__global__ void __cluster_dims__(2, 1, 1) __launch_bounds__(384, 1) mega_kernel(const __grid_constant__ Params p) {
  extern __shared__ __align__(1024) uint8_t smem_raw[];
  const uint32_t sbase = smem_u32(smem_raw);
  const uint32_t s_bar = sbase + OFF_BAR;
  const int cluster_id = blockIdx.x >> 1;
  const bool isB = cluster_id >= NA_CL;
#define EARLY 1
  const int prob0 = isB ? 3 : cluster_id >> 4;
  const int ng0 = (isB ? (cluster_id - NA_CL) >> 3 : (cluster_id >> 3) & 1) * 4;
  const uint32_t t0 = clock();
  auto early = [&](int s) {
    const uint32_t full = s_bar + B_GFULL + 8 * s;
    mbar_expect_tx(full, 49152);
    tma_load_3d(sbase + OFF_A + s * 16384, &p.ta[prob0], 0, (blockIdx.x & 15) * 128, s, full, EV_NORMAL);
    tma_load_3d(sbase + s * TILE32K, &p.tb[prob0], 0, s * 64, ng0, full, EV_NORMAL);
    tma_load_3d(sbase + s * TILE32K + 16384, &p.tb[prob0], 0, s * 64, ng0 + 2, full, EV_NORMAL);
  };
  if ((threadIdx.x >> 5) == 8) {
    if (elect_one()) {
      mbar_init(s_bar + B_GFULL, 1);
      if (EARLY) early(0);
      for (int s = 1; s < 4; s++) mbar_init(s_bar + B_GFULL + 8 * s, 1);
      asm volatile("fence.mbarrier_init.release.cluster;" ::: "memory");
    }
    __syncwarp();
    named_bar_arrive(7, 288);
  }
  const int warp0 = __shfl_sync(0xffffffffu, threadIdx.x >> 5, 0);
  if (warp0 >= 8) reg_dealloc<REG_P>();
#define CLUSTER_ARRIVE() asm volatile("barrier.cluster.arrive.relaxed.aligned;" ::: "memory")
#define CLUSTER_WAIT() asm volatile("barrier.cluster.wait.acquire.aligned;" ::: "memory")

  if (warp0 >= 8) {
    if (warp0 == 10 && elect_one()) {
      if ((sbase & 0x3FFFFu) != DBASE) __trap();
      for (int s = 0; s < 4; s++) {
        mbar_init(s_bar + B_GEMPTY + 8 * s, 4);
        mbar_init(s_bar + B_SFULL + 8 * s, 4);
        mbar_init(s_bar + B_SFULL2 + 8 * s, 4);
        mbar_init(s_bar + B_SEMPTY + 8 * s, 1);
        mbar_init(s_bar + B_AFULL + 8 * s, 1);
        mbar_init(s_bar + B_AEMPTY + 8 * s, s == 1 && !isB ? 8 : 2);
      }
      for (int s = 0; s < 2; s++) {
        mbar_init(s_bar + B_QFULL + 8 * s, 1);
        mbar_init(s_bar + B_QEMPTY + 8 * s, 2);
      }
      mbar_init(s_bar + B_OFULL, 8);
      mbar_init(s_bar + B_STGFREE, 1);
      sts32(s_bar + S_CODE, 0);
      asm volatile("fence.mbarrier_init.release.cluster;" ::: "memory");
    }
    __syncwarp();
    CLUSTER_ARRIVE();
    if (EARLY && warp0 == 8 && elect_one()) {
#pragma unroll 1
      for (int s = 1; s < 4; s++) {
        while ((uint32_t)clock() - t0 < s * PACE) {}
        early(s);
      }
    }
    __syncwarp();
    CLUSTER_WAIT();
    const int lane = threadIdx.x & 31;
    const uint32_t rank = blockIdx.x & 1;
    if (warp0 == 8) {
      if (elect_one()) {
        TL_DECL;
        uint32_t gphase = 1 - EARLY;
        uint32_t tail = 0;
        int gi = 0;
        uint32_t rsel = rank, aswz = 0, lastq = 0, n = 0;
        for (int seg = 0; seg < 2; seg++) {
          for (;;) {
            uint32_t item = p.g[cluster_id][gi++];
            if (item == 0x500u) item = tail;
            if (item >= 0x600u) break;
            const int prob = item >> 8;
            const int rt = ((item >> 4) & 15) * 2 + rsel;
            const int ngrp0 = (item & 15) * 4;
            const int nkb4 = prob_nkb4(prob);
            const CUtensorMap* ta = &p.ta[prob];
            const CUtensorMap* tb = &p.tb[prob];
            TL(1, item);
            if (prob == 5) {
              uint32_t seen = 0;
              cnt_wait_bit(CNT_OB + (rt >> 2), 32u << (rt & 3) * 8, seen);
              fence_proxy_async_global();
            }
            for (int kb4 = EARLY && gi == 1; kb4 < nkb4; kb4++) {
              uint32_t seen = 0;
#pragma unroll 1
              for (int s = 0; s < 4; s++) {
                const int bs = s ^ (n & 1);
                if (prob == 4 && !(s & 1)) {
                  cnt_wait_bit(CNT_CTX + kb4, 16u << (s * 8), seen);
                  fence_proxy_async_global();
                }
                if (prob == 5 && kb4 == 0) {
                  mbar_wait(s_bar + B_AEMPTY + 8 * bs, (~(n + (s & 1)) >> 1) & 1);
                  if (s == 2) mbar_wait(s_bar + B_QEMPTY + (aswz ? 0 : 8), lastq);
                }
                mbar_wait(s_bar + B_GEMPTY + 8 * s, gphase);
                const uint32_t full = s_bar + B_GFULL + 8 * s;
                mbar_expect_tx(full, 49152);
                tma_load_3d(sbase + OFF_A + ((s * 16384) ^ aswz), ta, 0, rt * 128, kb4 * 4 + s, full, HINT(prob));
                if (prob == 5) {
                  tma_load_3d(sbase + bs * TILE32K, tb, 0, (kb4 * 4 + s) * 64, ngrp0, full, HINT(8 + prob));
                  tma_load_3d(sbase + bs * TILE32K + 16384, tb, 0, (kb4 * 4 + s) * 64, ngrp0 + 2, full, HINT(8 + prob));
                } else {
                  tma_load_3d_mc(sbase + s * TILE32K + rank * 16384, tb, 0, (kb4 * 4 + s) * 64, ngrp0 + rank * 2, full,
                                 (uint16_t)3, HINT(8 + prob));
                }
              }
              gphase ^= 1;
            }
          }
          if (seg == 0 && isB && DO_ATT) {
            int pv_row = 0, pv_col = 0;
            uint64_t pv_hint = 0;
#define ACQ_SLOT(slot, n)                                                              \
  {                                                                                    \
    if ((n) < 2) mbar_wait(s_bar + B_GEMPTY + 8 * (slot), gphase);                     \
    mbar_wait(s_bar + B_AEMPTY + 8 * (slot), (~(n) >> 1) & 1);                         \
  }
#define LOAD_V()                                                                       \
  {                                                                                    \
    const uint32_t vs = 3 - (n & 1);                                                   \
    ACQ_SLOT(vs, n - 1);                                                               \
    mbar_expect_tx(s_bar + B_AFULL + 8 * vs, TILE32K);                                 \
    tma_load_3d(sbase + vs * TILE32K, &p.tv, 0, pv_row, pv_col, s_bar + B_AFULL + 8 * vs, pv_hint); \
  }
#define NEXT_CODE() (nxt < 512 ? p.order[nxt] : nxt + (0x8000u - 512))
            uint32_t code = p.order[blockIdx.x - 2 * NA_CL];
            int it = 0;
            uint32_t seen = 0;
            for (;; it++) {
              if (it == 1) mbar_wait(s_bar + B_STGFREE, 0);
              if (code & 0x8000u) break;
              const int head = code >> 4;
              const int qt = code & 15;
              uint32_t nxt = 0;
              TL(1, 0x1000 | code);
              if (seen < 48) cnt_wait(CNT_QKV + (head >> 1), 48);
              fence_proxy_async_global();
              {
                const int b = it & 1;
                if (it < 2) {
                  mbar_wait(s_bar + B_GEMPTY + 16 * b, gphase);
                  mbar_wait(s_bar + B_GEMPTY + 16 * b + 8, gphase);
                }
                mbar_wait(s_bar + B_QEMPTY + 8 * b, ((it >> 1) & 1) ^ 1);
                mbar_expect_tx(s_bar + B_QFULL + 8 * b, TILE32K);
                tma_load_3d(sbase + OFF_A + b * TILE32K, &p.tq, 0, qt * 128, head * 2, s_bar + B_QFULL + 8 * b, HINT(24));
              }
#pragma unroll 1
              for (int t = qt; t >= 0; t--) {
                if (t == min(qt, 1)) nxt = cnt_next(CNT_QUEUE) + NB_CTA;
                if (t == 0) {
                  code = NEXT_CODE();
                  sts32(s_bar + S_CODE + 4 * ((it + 1) & 7), code);
                  seen = cnt_peek(CNT_QKV + ((code >> 5) & 15));
                }
                ACQ_SLOT(n & 1, n);
                mbar_expect_tx(s_bar + B_AFULL + 8 * (n & 1), TILE32K);
                tma_load_3d(sbase + (n & 1) * TILE32K, &p.tk, 0, t * 128, head * 2, s_bar + B_AFULL + 8 * (n & 1), HINT(t == qt ? 29 : 25));
                if (n) LOAD_V();
                n++;
                pv_row = t * 128;
                pv_col = head * 2;
                pv_hint = HINT(t == qt ? 29 : 26);
              }
            }
            ACQ_SLOT(n & 1, n);
            mbar_arrive(s_bar + B_AFULL + 8 * (n & 1));
            LOAD_V();
            tail = tail_item(code);
            aswz = (it & 1) * TILE32K;
            mbar_wait(s_bar + B_QEMPTY + 8 * (it & 1), ((it >> 1) & 1) ^ 1);
            rsel = (code >> 3) & 1;
            lastq = ((it - 1) >> 1) & 1;
          }
        }
        if (cnt_done(NCTA * 2)) cnt_rearm();
#pragma unroll 1
        for (int s = 0; s < 4; s++) mbar_wait(s_bar + B_GEMPTY + 8 * s, gphase);
        TL(1, 0xFFFF);
      }
    } else if (warp0 == 9) {
      if (elect_one()) {
        TL_DECL;
        uint32_t tail = 0;
        int gi = 0;
        uint32_t rsel = rank, aswz = 0;
        bool rearm = false;
        for (int seg = 0; seg < 2; seg++) {
          for (;;) {
            uint32_t item = p.g[cluster_id][gi++];
            if (item == 0x500u) item = tail;
            if (item >= 0x600u) break;
            const int prob = item >> 8;
            const int rt = ((item >> 4) & 15) * 2 + rsel;
            const int cg = (item & 15) * 4 + (prob == 5 ? 16 : 0);
            const CUtensorMap* tc = &p.tc[prob];
            const int nl = (p.g[cluster_id][gi] >> 8) == 4 && DO_LOCAL ? 8 : 1;
            const int grp = ((blockIdx.x >> 4) & 1) * 48 + (blockIdx.x & 15), r0 = (blockIdx.x >> 5) * 512;
            if (nl > 1) {
              cnt_wait(CNT_QKVB, 192);
              fence_proxy_async_global();
              sts32(s_bar + S_CODE, 2);
            }
            if (prob >= 4) rearm = cnt_done(NCTA * 2);
            const bool lastt = p.g[cluster_id][gi] >= 0x600u;
#pragma unroll 1
            for (int c = 0; c < 8; c++) {
              const int q = lastt ? c & 3 : c >> 1, w = lastt ? c >> 2 : c & 1;
              const int idx = w * 2 + (q & 1);
              const bool alt = lastt && q >= 2;
              mbar_wait(s_bar + (alt ? B_SFULL2 : B_SFULL) + 8 * idx, lastt ? seg : q >> 1);
              tma_store_3d(tc, sbase + (alt ? OFF_A + ((q * 16384) ^ aswz) + w * 8192 : OFF_STG + idx * 8192), 0,
                           rt * 128 + w * 64, cg + q, HINT(16 + prob));
              bulk_commit();
              if (c > 0 && !lastt) {
                bulk_wait_read<1>();
                mbar_arrive(s_bar + B_SEMPTY + 8 * ((w ^ 1) * 2 + (((c - 1) >> 1) & 1)));
              }
            }
            bulk_wait_read<0>();
            mbar_arrive(s_bar + (lastt ? B_STGFREE : B_SEMPTY + 8 * 3));
#pragma unroll 1
            for (int c = 0; c < nl; c++) {
              if (nl > 1) {
                mbar_wait(s_bar + B_AEMPTY, (c & 1) ^ 1);
                mbar_expect_tx(s_bar + B_AFULL, L_V);
                tma_load_3d(sbase + OFF_STG, &p.tl, 0, r0 + c * 64, grp, s_bar + B_AFULL, HINT(28));
                tma_load_3d(sbase + OFF_STG + L_K, &p.th, 0, r0 + c * 64 - 8, 16 + grp, s_bar + B_AFULL, HINT(28));
                mbar_wait(s_bar + B_AEMPTY + 8, (c & 1) ^ 1);
                mbar_expect_tx(s_bar + B_AFULL + 8, 9216);
                tma_load_3d(sbase + OFF_STG + L_V, &p.th, 0, r0 + c * 64 - 8, 32 + grp, s_bar + B_AFULL + 8, HINT(28));
                sts32(s_bar + S_CODE, c + 3);
              }
              if (c) {
                mbar_wait(s_bar + B_OFULL, ~c & 1);
                cnt_signal(CNT_OB + (blockIdx.x >> 5) * 2 + ((c - 1) >> 2), 1u << ((c - 1) & 3) * 8);
              } else if (prob < 4) {
                bulk_wait<0>();
                cnt_signal_done(prob == 3 ? CNT_QKVB : CNT_QKV + (item & 15));
                TL(2, item);
              }
            }
            if (nl > 1) {
              mbar_wait(s_bar + B_OFULL, 1);
              cnt_signal(CNT_OB + (blockIdx.x >> 5) * 2 + 1, 1u << 24);
              TL(2, 0x600);
            }
          }
          if (seg == 0 && isB && DO_ATT) {
            uint32_t code = p.order[blockIdx.x - 2 * NA_CL];
            for (int it = 0; !(code & 0x8000u); it++) {
              aswz = (~it & 1) * TILE32K;
              mbar_wait(s_bar + B_OFULL, it & 1);
              tma_store_3d(&p.to, sbase + OFF_STG, 0, (code & 15) * 128, (code >> 4) * 2, HINT(27));
              bulk_commit();
              const uint32_t nxt = lds32(s_bar + S_CODE + 4 * ((it + 1) & 7));
              bulk_wait_read<0>();
              mbar_arrive(s_bar + B_STGFREE);
              bulk_wait<0>();
              cnt_signal_done(CNT_CTX + (code >> 5), 1u << (code & 16));
              TL(2, 0x1000 | code);
              code = nxt;
            }
            tail = tail_item(code);
            rsel = (code >> 3) & 1;
            if (tail == 0xFFFFu) rearm = cnt_done(NCTA * 2);
          }
        }
        if (rearm) cnt_rearm();
        TL(2, 0xFFFF);
      }
    } else if (warp0 == 10 && !isB && DO_LOCAL) {
      const char* src = reinterpret_cast<const char*>(p.qkvb) + (((blockIdx.x >> 4) & 1) * 48 + (blockIdx.x & 15)) * 128;
      int spin = 0;
#pragma unroll 1
      for (int c = 0; c < 8; c++) {
        while (lds32(s_bar + S_CODE) <= c && ++spin < 100000) __nanosleep(256);
#pragma unroll 1
        for (int r = c ? 8 + lane : lane; r < 72; r += 32) {
          const int row = max((int)(blockIdx.x >> 5) * 512 + c * 64 - 8 + r, 0);
#pragma unroll
          for (int j = 0; j < 3; j++) asm volatile("prefetch.global.L2 [%0];" ::"l"(src + (size_t)row * 12288 + j * 2048));
        }
      }
    }
  } else {
    CLUSTER_ARRIVE();
    reg_alloc<REG_C>();
    named_bar_sync(7, 288);
    const int warp = __shfl_sync(0xffffffffu, opaque_tid() >> 5, 0);
    const int wg = warp >> 2;
    const int lane = threadIdx.x & 31;
    TL_DECL;
    TR_DECL;
    uint32_t gphase = 0;
    uint32_t tail = 0, aswz = 0, rot = 0, etgt = warp & 1, stgpar = 1;
    int gi = 0;
    for (int seg = 0; seg < 2; seg++) {
      uint32_t item = p.g[cluster_id][gi++];
      if (item == 0x500u) item = tail;
      if (item < 0x600u) {
        float acc[128];
        uint32_t pk[64];
        int have = 0;
#define G_STORE_CHUNK(q)                                                                               \
  {                                                                                                    \
    const uint32_t st_base = sbase + OFF_STG + wg * 8192 + stg_off(opaque_tid());                      \
    if (have == 2) { _Pragma("unroll") for (int j = 0; j < 16; j++) pk[(q) * 16 + j] = scale_q(pk[(q) * 16 + j]); } \
    mbar_wait(s_bar + B_SEMPTY + 8 * (wg * 2 + ((q) & 1)), (((q) >> 1) & 1) ^ 1);                      \
    _Pragma("unroll") for (int j = 0; j < 4; j++)                                                      \
        stmatrix_x4((st_base ^ (j << 5)) + ((q) & 1) * 8192, pk[(q) * 16 + j * 4],                     \
                    pk[(q) * 16 + j * 4 + 1], pk[(q) * 16 + j * 4 + 2], pk[(q) * 16 + j * 4 + 3]);     \
    fence_proxy_async_smem();                                                                          \
    __syncwarp();                                                                                      \
    mbar_arrive_elect(s_bar + B_SFULL + 8 * (wg * 2 + ((q) & 1)), true);                              \
  }
#define G_STAGE(s) G_STAGE_Y(s, false, false, )
#define G_STAGE_X(s, ...) G_STAGE_Y(s, false, false, __VA_ARGS__)
#define G_STAGE_Y(s, first, last, ...)                                                                    \
  {                                                                                                       \
    mbar_wait_rest(s_bar + B_GFULL + 8 * (s), gphase, gok && (first));                                    \
    TR(9);                                                                                                \
    const uint32_t da = make_desc(DBASE + OFF_A + (((s) * 16384) ^ aswz) + wg * 8192, 16);                \
    const uint32_t db = make_desc(DBASE + ((s) ^ rot) * TILE32K, 8192);                                   \
    named_bar_sync_if(5 + wg, 256, !(first));                                                             \
    wgmma_fence();                                                                                        \
    _Pragma("unroll") for (int k = 0; k < 5; k++) {                                                       \
      __VA_ARGS__;                                                                                        \
      if (k == 0) wgmma_ss_n256_tbo<0, 0>(acc, da, db, !(first));                                         \
      if (k == 1) wgmma_ss_n256_tbo<2, 128>(acc, da, db, 1);                                              \
      if (k == 2) wgmma_ss_n256_tbo<4, 256>(acc, da, db, 1);                                              \
      if (k == 3) wgmma_ss_n256_tbo<6, 384>(acc, da, db, 1);                                              \
    }                                                                                                     \
    wgmma_commit();                                                                                       \
    named_bar_arrive_if(6 - wg, 256, !(wg ? (last) : (first)));                                           \
    if (!(first)) {                                                                                       \
      wgmma_wait<1>();                                                                                    \
      mbar_arrive_cluster_if(s_bar + B_GEMPTY + 8 * (((s) + 3) & 3), etgt, lane == 0 && (warp & 3) < 2);  \
    }                                                                                                     \
  }
        TL0(item);
        undef_regs(acc);
        {
          constexpr bool gok = false;
          G_STAGE_Y(0, true, false, )
        }
        if (seg == 0) CLUSTER_WAIT();
        undef_regs(pk);
        for (;;) {
          constexpr bool gok = false;
          const int nkb4 = prob_nkb4(item >> 8);
          const uint32_t next = p.g[cluster_id][gi++];
          if (have) G_STORE_CHUNK(0)
          G_STAGE(1)
          G_STAGE(2)
          if (have) G_STORE_CHUNK(1)
          G_STAGE(3)
          gphase ^= 1;
          G_STAGE(0)
          if (have) G_STORE_CHUNK(2)
          G_STAGE(1)
          G_STAGE(2)
          if (have) G_STORE_CHUNK(3)
          G_STAGE_Y(3, false, nkb4 == 2, )
          gphase ^= 1;
          int kb4 = 2;
          if (nkb4 == 16 && DO_LOCAL) {
            constexpr uint32_t aswz = 0, rot = 0;
            G_STAGE(0)
            G_STAGE(1)
            for (; kb4 < 10; kb4++) {
              float ls[36];
              TR(10);
              mbar_wait(s_bar + B_AFULL, kb4 & 1);
              TR(11);
              {
                const uint32_t dq = make_desc(DBASE + OFF_STG + wg * 64, 16);
                G_STAGE_X(2, if (k == 1) wgmma_ss_n72_init(ls, dq, dq + L_K / 16); if (k == 3) wgmma_ss_n72(ls, dq + 2, dq + L_K / 16 + 2, 1))
              }
              mbar_wait(s_bar + B_AFULL + 8, kb4 & 1);
              const int tid = opaque_tid();
              uint32_t vw[16];
              uint4 pw[8];
              {
                const uint32_t va = sbase + OFF_STG + L_V + ((tid >> 4) & 7) * 1024 + wg * 64 + (tid & 15) * 4;
#pragma unroll
                for (int j = 1; j < 16; j++) vw[j] = lds32((va ^ ((j & 7) << 4)) + j * 128);
              }
              G_STAGE(3)
              gphase ^= 1;
              fence_regs(ls);
              mbar_arrive_if(s_bar + B_AEMPTY, (threadIdx.x & 127) == 0);
              {
                const int d = (tid & 3) * 2 - ((tid >> 2) & 7);
                const bool p0 = d > 0, p1 = d >= 0;
                const int w = warp & 3;
                float x0, x1, y0, y1;
#define L_PICK(w_)                                   \
  {                                                  \
    x0 = p0 ? ls[8 * (w_)] : ls[8 * (w_) + 4];       \
    x1 = p1 ? ls[8 * (w_) + 1] : ls[8 * (w_) + 5];   \
    y0 = p0 ? ls[8 * (w_) + 6] : ls[8 * (w_) + 10];  \
    y1 = p1 ? ls[8 * (w_) + 7] : ls[8 * (w_) + 11];  \
  }
                if (w == 0) {
                  if (kb4 == 2 && blockIdx.x < 32) ls[0] = ls[1] = -INFINITY;
                  L_PICK(0)
                } else if (w == 1) L_PICK(1)
                else if (w == 2) L_PICK(2)
                else L_PICK(3)
                constexpr float C = 0.17677669529663687f * 1.4426950408889634f;
                float mx = fmaxf(x0, x1), my = fmaxf(y0, y1);
                mx = fmaxf(mx, __shfl_xor_sync(0xffffffffu, mx, 1));
                my = fmaxf(my, __shfl_xor_sync(0xffffffffu, my, 1));
                mx = -C * fmaxf(mx, __shfl_xor_sync(0xffffffffu, mx, 2));
                my = -C * fmaxf(my, __shfl_xor_sync(0xffffffffu, my, 2));
                x0 = ex2(fmaf(x0, C, mx));
                x1 = ex2(fmaf(x1, C, mx));
                y0 = ex2(fmaf(y0, C, my));
                y1 = ex2(fmaf(y1, C, my));
                float sx = x0 + x1, sy = y0 + y1;
                sx += __shfl_xor_sync(0xffffffffu, sx, 1);
                sy += __shfl_xor_sync(0xffffffffu, sy, 1);
                sx += __shfl_xor_sync(0xffffffffu, sx, 2);
                sy += __shfl_xor_sync(0xffffffffu, sy, 2);
                sx = rcp(sx);
                sy = rcp(sy);
                const uint32_t pa = sbase + OFF_STG + L_P + (tid >> 5) * 512 + (tid & 31) * 8;
                sts64(pa, x0 * sx, x1 * sx);
                sts64(pa + 256, y0 * sy, y1 * sy);
                __syncwarp();
              }
              const uint32_t pr = sbase + OFF_STG + L_P + (tid >> 4) * 256;
              uint32_t* dst = reinterpret_cast<uint32_t*>(p.ob) + (blockIdx.x & 15) * 32 + wg * 16 + (tid & 15) +
                              (((blockIdx.x >> 5) * 512 + (kb4 - 2) * 64 + ((tid >> 4) & 7) * 8) * 2 + ((blockIdx.x >> 4) & 1)) * 512;
#define L_PV(g0)                                                                                       \
  _Pragma("unroll") for (int g = (g0); g < (g0) + 4; g++) {                                            \
    const uint4 a = pw[2 * (g & 3)], b = pw[2 * (g & 3) + 1];                                          \
    const uint32_t w[8] = {a.x, a.y, a.z, a.w, b.x, b.y, b.z, b.w};                                    \
    float o0 = 0.f, o1 = 0.f;                                                                          \
    _Pragma("unroll") for (int c = 0; c < 8; c++) {                                                    \
      const uint32_t u = vw[c > g ? c : c + 8];                                                        \
      o0 = fmaf(__uint_as_float(w[c]), __uint_as_float(u << 16), o0);                                  \
      o1 = fmaf(__uint_as_float(w[c]), __uint_as_float(u & 0xFFFF0000u), o1);                          \
    }                                                                                                  \
    dst[g * 1024] = pack_bf16(o0, o1);                                                                 \
  }
#pragma unroll
              for (int j = 0; j < 8; j++) pw[j] = lds128(pr + j * 16);
              mbar_arrive_elect(s_bar + B_AEMPTY + 8, true);
              G_STAGE(0)
              L_PV(0)
#pragma unroll
              for (int j = 0; j < 8; j++) pw[j] = lds128(pr + 128 + j * 16);
              G_STAGE(1)
              L_PV(4)
              __syncwarp();
              mbar_arrive_elect(s_bar + B_OFULL, true);
            }
            G_STAGE(2)
            G_STAGE(3)
            gphase ^= 1;
            kb4++;
          }
          const bool fin = next >= 0x600u;
          for (; kb4 < nkb4 - fin; kb4++) {
            G_STAGE(0)
            G_STAGE(1)
            G_STAGE(2)
            G_STAGE_Y(3, false, kb4 + 1 == nkb4, )
            gphase ^= 1;
          }
          if (fin) break;
          wgmma_wait<0>();
          mbar_arrive_cluster_if(s_bar + B_GEMPTY + 8 * 3, etgt, lane == 0 && (warp & 3) < 2);
          {
            const bool gok = mbar_test(s_bar + B_GFULL, gphase);
            fence_regs(acc);
#pragma unroll
            for (int j = 0; j < 64; j++) pk[j] = pack_bf16(acc[2 * j], acc[2 * j + 1]);
            have = item < 0x100u ? 2 : 1;
            item = next;
            TL0(item);
            G_STAGE_Y(0, true, false, )
          }
        }
        {
          constexpr bool gok = false;
          G_STAGE(0)
          G_STAGE(1)
          wgmma_wait<0>();
          mbar_arrive_cluster_if(s_bar + B_GEMPTY + 8 * (FS - 1), etgt, lane == 0 && (warp & 3) < 2);
          fence_regs(acc);
          float lo[64], hi[64];
#pragma unroll
          for (int j = 0; j < 64; j++) {
            asm volatile("mov.b32 %0, %1;" : "=f"(lo[j]) : "f"(acc[j]));
            asm volatile("mov.b32 %0, %1;" : "=f"(hi[j]) : "f"(acc[64 + j]));
          }
#pragma unroll
          for (int s = FS; s < 4; s++) {
            mbar_wait(s_bar + B_GFULL + 8 * s, gphase);
            const uint32_t da = make_desc(DBASE + OFF_A + ((s * 16384) ^ aswz) + wg * 8192, 16);
            const uint32_t db = make_desc(DBASE + (s ^ rot) * TILE32K, 8192);
            if (s == FS) named_bar_sync(5 + wg, 256);
            wgmma_fence();
            wgmma_ss_n128_tb<0, 0>(lo, da, db, 1);
            wgmma_ss_n128_tb<2, 128>(lo, da, db, 1);
            wgmma_ss_n128_tb<4, 256>(lo, da, db, 1);
            wgmma_ss_n128_tb<6, 384>(lo, da, db, 1);
            wgmma_commit();
          }
          wgmma_fence();
#pragma unroll
          for (int s = FS; s < 4; s++) {
            const uint32_t da = make_desc(DBASE + OFF_A + ((s * 16384) ^ aswz) + wg * 8192, 16);
            const uint32_t db = make_desc(DBASE + (s ^ rot) * TILE32K, 8192);
            wgmma_ss_n128_tb<0, 1024>(hi, da, db, 1);
            wgmma_ss_n128_tb<2, 1152>(hi, da, db, 1);
            wgmma_ss_n128_tb<4, 1280>(hi, da, db, 1);
            wgmma_ss_n128_tb<6, 1408>(hi, da, db, 1);
          }
          wgmma_commit();
          named_bar_arrive_if(6, 256, wg == 0);
          gphase ^= 1;
          const uint32_t so = sbase + stg_off(opaque_tid());
          mbar_wait(s_bar + B_STGFREE, stgpar);
          mbar_wait(s_bar + B_SEMPTY + 16 * wg, 1);
          mbar_wait(s_bar + B_SEMPTY + 16 * wg + 8, 1);
#define FIN_HALF(x, base, stride, bar)                                                                                \
  fence_regs(x);                                                                                                      \
  _Pragma("unroll") for (int j = 0; j < 8; j++)                                                                       \
      stmatrix_x4(((base) ^ ((j & 3) << 5)) + (j >> 2) * (stride), pack_bf16(x[8 * j], x[8 * j + 1]),                 \
                  pack_bf16(x[8 * j + 2], x[8 * j + 3]), pack_bf16(x[8 * j + 4], x[8 * j + 5]), pack_bf16(x[8 * j + 6], x[8 * j + 7])); \
  fence_proxy_async_smem();                                                                                           \
  __syncwarp();                                                                                                       \
  mbar_arrive_elect(s_bar + (bar) + 16 * wg, true);                                                                   \
  mbar_arrive_elect(s_bar + (bar) + 16 * wg + 8, true);
          wgmma_wait<1>();
          FIN_HALF(lo, so + OFF_STG + wg * 8192, 8192, B_SFULL)
          wgmma_wait<0>();
          TRI(12, 8);
#pragma unroll
          for (int s = FS; s < 4; s++) mbar_arrive_cluster_if(s_bar + B_GEMPTY + 8 * s, etgt, lane == 0 && (warp & 3) < 2);
          FIN_HALF(hi, so + OFF_A + (32768 ^ aswz), 16384, B_SFULL2)
          TRI(12, 10);
        }
      }
      if (seg == 0 && isB && DO_ATT) {
        float o[64], s[64];
        uint32_t pa[32], pb[32];
        undef_regs(o);
        undef_regs(s);
        undef_regs(pa);
        undef_regs(pb);
        uint32_t phase = 0;
        const bool sig = (threadIdx.x & 127) == 0;
        if (wg == 1) named_bar_arrive(1, 256);

#define ISSUE_PV(pr, slot_)                                                             \
  {                                                                                     \
    const uint32_t dv = make_desc(DBASE + (slot_) * TILE32K, 16384);                    \
    if (!(pfirst && wg == HW)) {                                                        \
      wgmma_fence();                                                                    \
      _Pragma("unroll") for (int k = 0; k < 8; k++)                                     \
          wgmma_rs_n128_tb(o, pr[4 * k], pr[4 * k + 1], pr[4 * k + 2], pr[4 * k + 3], dv + k * 128, (k != 0) || !pfirst); \
      wgmma_commit();                                                                   \
    } else {                                                                            \
      wgmma_fence();                                                                    \
      _Pragma("unroll") for (int k = 0; k < 4; k++)                                     \
          wgmma_rs_n128_tb(o, pr[16 + 4 * k], pr[17 + 4 * k], pr[18 + 4 * k], pr[19 + 4 * k], dv + k * 128, k != 0); \
      wgmma_commit();                                                                   \
    }                                                                                   \
  }
#define EPILOGUE(on_)                                                                             \
  _Pragma("unroll") for (int j = 0; j < 8; j++) {                                                 \
    const int b = j * 8;                                                                          \
    stmatrix_x4_p((st_o ^ ((j & 3) << 5)) + (j >> 2) * 16384,                                     \
                  pack_bf16(o[b] * sc0, o[b + 1] * sc0), pack_bf16(o[b + 2] * sc1, o[b + 3] * sc1),   \
                  pack_bf16(o[b + 4] * sc0, o[b + 5] * sc0), pack_bf16(o[b + 6] * sc1, o[b + 7] * sc1), on_); \
  }
#define PUBLISH_O()                                  \
  {                                                  \
    fence_proxy_async_smem();                        \
    __syncwarp();                                    \
    mbar_arrive_elect(s_bar + B_OFULL, true);        \
  }
#define FINAL_SCALE()     \
  {                                                    \
    sc0 += __shfl_xor_sync(0xffffffffu, sc0, 1);       \
    sc1 += __shfl_xor_sync(0xffffffffu, sc1, 1);       \
    sc0 += __shfl_xor_sync(0xffffffffu, sc0, 2);       \
    sc1 += __shfl_xor_sync(0xffffffffu, sc1, 2);       \
    sc0 = rcp(sc0);            \
    sc1 = rcp(sc1);                                    \
  }
        float l0 = 1.f, l1 = 1.f, t0 = 1.f, t1 = 1.f;
        float b0 = 0.f, b1 = 0.f, sc0 = 0.f, sc1 = 0.f;
        int gen = 0;
        int pfirst = 1;
        int fresh = 1;
        int opub = 0;
        int last = 0;
        float rdy = -0.f;
        float x0 = 0.f, x1 = 0.f, x2 = 0.f, x3 = 0.f;
        bool rs = false;
        uint32_t code = p.order[blockIdx.x - 2 * NA_CL];
        int it = -1, nit = 0, rem = -1;
        const float mrow = float((warp & 3) * 16 + (lane >> 2) - (lane & 3) * 2);
        const float lo0 = mrow < 0.f && wg == HW ? 0.f : SM_LO;
        const uint32_t st_o = sbase + OFF_STG + stg_off(opaque_tid() ^ (HW * 128));
#define MMA_PART(N_, acc_, PIN, PAR)                                                                       \
  {                                                                                                        \
    const uint32_t dq = make_desc(DBASE + OFF_A + (it & 1) * TILE32K + (wg ^ HW) * 8192, 16);              \
    const uint32_t dk = make_desc(DBASE + (PAR) * TILE32K, 16);                                            \
    TRI(0, fresh ? 7 : 0);                                                                                 \
    named_bar_sync(1 + wg, 256);                                                                           \
    TRI(1, fresh ? 6 : 1);                                                                                 \
    wgmma_fence();                                                                                         \
    uint32_t cv;                                                                                           \
    bool rv;                                                                                               \
    _Pragma("unroll") for (int k = 0; k < 8; k++) {                                                        \
      wgmma_ss_n##N_(acc_, dq + (k >> 2) * 1024 + (k & 3) * 2, dk + (k >> 2) * 1024 + (k & 3) * 2, k != 0 || gen); \
      if (k == 1) cv = lds32(s_bar + S_CODE + 4 * ((it + 1) & 7));        \
      if (k == 3) rv = mbar_test(s_bar + B_AFULL + 8 * (3 - (PAR)), phase ^ (1 - (PAR)));                  \
    }                                                                                                      \
    wgmma_commit();                                                                                        \
    code = __reduce_or_sync(0xffffffffu, cv);                                                              \
    if (N_ == 128 && opub) PUBLISH_O();                                                                    \
    if (N_ == 128 && fresh) FINAL_SCALE();                                                                 \
    last = rem == 0 && (code & 0x8000u);                                                                   \
    nit = it + (rem == 0 && !last);                                                                        \
    mbar_wait_rest(s_bar + B_AFULL + 8 * (3 - (PAR)), phase ^ (1 - (PAR)), rv);                            \
    ISSUE_PV(PIN, 3 - (PAR));                                                                              \
    named_bar_arrive(2 - wg, 256);                                                                         \
    TR(2);                                                                                                 \
    wgmma_wait<1>();                                                                                       \
    fence_regs(acc_);                                                                                      \
    TR(3);                                                                                                 \
    mbar_arrive_if(s_bar + B_AEMPTY + 8 * (PAR), sig);                                                     \
    mbar_arrive_if(s_bar + B_QEMPTY + 8 * (it & 1), sig && rem == 0);                                      \
    rs = mbar_test(s_bar + B_STGFREE, ~it & 1) | (it == 0);                                                \
    l0 = t0;                                                                                               \
    l1 = t1;                                                                                               \
  }
#define LOW_SUM() ((t0 < lo0) | (t1 < SM_LO))
#define SECOND_HALF(POUT, PAR, FRESH, ...)                                                                 \
  wgmma_wait<0>();                                                                                         \
  fence_regs(o);                                                                                           \
  mbar_arrive_if(s_bar + B_AEMPTY + 8 * (3 - (PAR)), sig && ((PAR) || !(FRESH) || it > 0));                \
  rdy = mbar_test2(s_bar + B_AFULL + 8 * (1 - (PAR)), phase ^ (PAR), s_bar + B_QFULL + 8 * (nit & 1), (nit >> 1) & 1); \
  TR(8);                                                                                                   \
  __VA_ARGS__;                                                                                             \
  t0 += x0 + x1;                                                                                           \
  t1 += x2 + x3;                                                                                           \
  POUT[16] = pack_bf16(x0, x1);                                                                            \
  POUT[17] = pack_bf16(x2, x3);                                                                            \
  softmax_exp<9, TPOS, false>(s, 0.f, 0.f, POUT, t0, t1);                                                  \
  t0 = addv(t0, rdy);                                                                                      \
  softmax_exp<TPOS, 16, false>(s, 0.f, 0.f, POUT, t0, t1);                                                 \
  opub = (FRESH) && it > 0 && wg != HW;                                                                    \
  pfirst = FRESH;                                                                                          \
  fresh = 0;                                                                                               \
  rem--;                                                                                                   \
  if (PAR) phase ^= 1;                                                                                     \
                                              \
  const float lim = __uint_as_float(__float_as_uint(rem < 0 || gen ? -1.f : SM_HI) | __float_as_uint(rdy)); \
  TR(4);
#define TPOS 14
#define STEP_END(POUT, PAR, NEXT, ...)                                                                     \
  if (fresh) {                                                                                             \
    __VA_ARGS__;                                                                                           \
    mbar_wait_rest(s_bar + B_STGFREE, ~it & 1, rs);                                                        \
    SECOND_HALF(POUT, PAR, 1, EPILOGUE(it > 0))                                                            \
    const bool nx = __any_sync(0xffffffffu, !(t0 + t1 <= lim) | LOW_SUM());                               \
    if (wg == HW && it > 0) PUBLISH_O();                                     \
    if (!nx) goto plain##NEXT;                                                                             \
  } else {                                                                                                 \
    SECOND_HALF(POUT, PAR, 0, )                                                                            \
    if (!__any_sync(0xffffffffu, !(t0 + t1 <= lim))) goto plain##NEXT;                                     \
  }
#define STEP_BEGIN(PIN, POUT, PAR, ...)                                                                    \
  {                                                                                                        \
    if (__any_sync(0xffffffffu, !(t0 + t1 <= SM_HI) | (LOW_SUM() & (pfirst != 0)))) {                           \
              \
      if (pfirst && wg == HW) { _Pragma("unroll") for (int j = 0; j < 32; j++) asm volatile("mov.b32 %0, 0xff800000;" : "=f"(s[j])); } \
      float d0, d1;                                                                                        \
      softmax_max(s, d0, d1);                                                                              \
      if (!pfirst) {                                                                                       \
        d0 = fmaxf(d0, 0.f);                                                                               \
        d1 = fmaxf(d1, 0.f);                                                                               \
      }                                                                                                    \
      const float r0 = pfirst ? 1.f : ex2(-d0), r1 = pfirst ? 1.f : ex2(-d1);                              \
      t0 = l0 * r0;                                                                                        \
      t1 = l1 * r1;                                                                                        \
      softmax_exp<0, 16, true>(s, -d0, -d1, PIN, t0, t1);                                                  \
      b0 -= d0;                                                                                            \
      b1 -= d1;                                                                                            \
      gen = 1;                                                                                             \
      _Pragma("unroll") for (int j = 0; j < 16; j++) {                                                     \
        o[4 * j] *= r0;                                                                                    \
        o[4 * j + 1] *= r0;                                                                                \
        o[4 * j + 2] *= r1;                                                                                \
        o[4 * j + 3] *= r1;                                                                                \
      }                                                                                                    \
    }                                                                                                      \
    if (last) {                                                                                            \
      __VA_ARGS__;                                                                                         \
      break;                                                                                               \
    }                                                                                                      \
    fresh = rem < 0;                                                                                       \
    it = nit;                                                                                              \
    if (fresh) {                                                                                           \
      TL0(0x1000 | code);                                                                                  \
      rem = code & 15;                                                                                     \
      sc0 = t0;                                                                                            \
      sc1 = t1;                                                                                            \
      t0 = t1 = 0.f;                                                                                       \
    }                                                                                                      \
    if (gen) {                                                      \
      _Pragma("unroll") for (int j = 0; j < 64; j++) asm volatile("mov.b32 %0, %1;" : "=f"(s[j]) : "f"((j & 2) ? b1 : b0)); \
    }                                                                                                      \
    mbar_wait_rest(s_bar + B_AFULL + 8 * (PAR), phase, __float_as_uint(rdy) == 0);                         \
    mbar_wait_rest(s_bar + B_QFULL + 8 * (it & 1), (it >> 1) & 1, __float_as_uint(rdy) == 0);              \
  }                                                                                                        \
  if (fresh && wg == HW) {                                                                                 \
                                                     \
    float sl[32];                                                                                          \
    _Pragma("unroll") for (int j = 0; j < 32; j++) asm volatile("mov.b32 %0, %1;" : "=f"(sl[j]) : "f"(s[32 + j])); \
    MMA_PART(64, sl, PIN, PAR)                                                                             \
    _Pragma("unroll") for (int j = 0; j < 32; j++) asm volatile("mov.b32 %0, %1;" : "=f"(s[32 + j]) : "f"(sl[j])); \
    FINAL_SCALE();                                                                                         \
    _Pragma("unroll") for (int j = 0; j < 8; j++) {                                                        \
      if (float(8 * j) > mrow) s[32 + 4 * j] = -3e38f;                                                     \
      if (float(8 * j + 1) > mrow) s[33 + 4 * j] = -3e38f;                                                 \
      if (float(8 * j - 8) > mrow) s[34 + 4 * j] = -3e38f;                                                 \
      if (float(8 * j - 7) > mrow) s[35 + 4 * j] = -3e38f;                                                 \
    }                                                                                                      \
    x0 = ex2v(s[32]), x1 = ex2v(s[33]), x2 = ex2v(s[34]), x3 = ex2v(s[35]);                                \
  } else {                                                                                                 \
  plain##PAR:                                                                                              \
    MMA_PART(128, s, PIN, PAR)                                                                             \
    if (fresh) {                                                                                           \
                                     \
      _Pragma("unroll") for (int j = 0; j < 8; j++) {                                                      \
        s[32 + 4 * j] = fmaf(__saturatef(float(8 * j) - mrow), -3e38f, s[32 + 4 * j]);                     \
        s[33 + 4 * j] = fmaf(__saturatef(float(8 * j + 1) - mrow), -3e38f, s[33 + 4 * j]);                 \
        s[34 + 4 * j] = fmaf(__saturatef(float(8 * j - 8) - mrow), -3e38f, s[34 + 4 * j]);                 \
        s[35 + 4 * j] = fmaf(__saturatef(float(8 * j - 7) - mrow), -3e38f, s[35 + 4 * j]);                 \
      }                                                                                                    \
      softmax_exp<0, 8, false>(s, 0.f, 0.f, POUT, t0, t1);                                                 \
      x0 = ex2v(s[32]), x1 = ex2v(s[33]), x2 = ex2v(s[34]), x3 = ex2v(s[35]);                              \
    } else {                                                                                               \
      softmax_exp<0, 8, false>(s, 0.f, 0.f, POUT, t0, t1);                                                 \
      x0 = ex2v(s[32]), x1 = ex2v(s[33]), x2 = ex2v(s[34]), x3 = ex2v(s[35]);                              \
    }                                                                                                      \
  }
        for (;;) {
          STEP_END(pa, 1, 0, if (it < 0) { wgmma_wait<0>(); goto begin0; })
        begin0:
          STEP_BEGIN(pa, pb, 0, rot = 0; phase ^= 1)
          STEP_END(pb, 0, 1, )
          STEP_BEGIN(pb, pa, 1, rot = 1; _Pragma("unroll") for (int j = 0; j < 32; j++) asm volatile("mov.b32 %0, %1;" : "=r"(pa[j]) : "r"(pb[j])))
        }
        {
          mbar_wait(s_bar + B_AFULL + 8 * (3 - rot), phase);
          TRI(12, 2);
          ISSUE_PV(pa, 3 - rot);
          if (opub) PUBLISH_O();
          sc0 = t0;
          sc1 = t1;
          FINAL_SCALE();
          mbar_wait(s_bar + B_STGFREE, it & 1);
          wgmma_wait<0>();
          fence_regs(o);
          TRI(12, 4);
          mbar_arrive_if(s_bar + B_AEMPTY + 8 * (3 - rot), sig);
          EPILOGUE(true);
          PUBLISH_O();
          TRI(12, 5);
          stgpar = ~it & 1;
          tail = tail_item(code);
          aswz = (~it & 1) * TILE32K;
          etgt = blockIdx.x & 1;
        }
      }
    }
    TL0(0xFFFF);
    TRI(15, 15);
  }
}

typedef CUresult (*EncodeFn)(CUtensorMap*, CUtensorMapDataType, cuuint32_t, void*, const cuuint64_t*,
                             const cuuint64_t*, const cuuint32_t*, const cuuint32_t*, CUtensorMapInterleave,
                             CUtensorMapSwizzle, CUtensorMapL2promotion, CUtensorMapFloatOOBfill);

EncodeFn get_encode() {
  static EncodeFn fn = nullptr;
  if (!fn) {
    void* p = nullptr;
    cudaDriverEntryPointQueryResult st;
    cudaGetDriverEntryPoint("cuTensorMapEncodeTiled", &p, cudaEnableDefault, &st);
    fn = (EncodeFn)p;
  }
  return fn;
}

void make_map(CUtensorMap* m, const void* ptr, int rows, int cols, int box_rows, int box_groups,
              CUtensorMapSwizzle swz = CU_TENSOR_MAP_SWIZZLE_128B) {
  cuuint64_t dims[3] = {64, (cuuint64_t)rows, (cuuint64_t)(cols / 64)};
  cuuint64_t strides[2] = {(cuuint64_t)cols * 2, 128};
  cuuint32_t box[3] = {64, (cuuint32_t)box_rows, (cuuint32_t)box_groups};
  cuuint32_t es[3] = {1, 1, 1};
  CUtensorMapL2promotion prom = box_groups == 1 ? CU_TENSOR_MAP_L2_PROMOTION_NONE : CU_TENSOR_MAP_L2_PROMOTION_L2_256B;
  get_encode()(m, CU_TENSOR_MAP_DATA_TYPE_BFLOAT16, 3, const_cast<void*>(ptr), dims, strides, box, es,
               CU_TENSOR_MAP_INTERLEAVE_NONE, swz, prom,
               CU_TENSOR_MAP_FLOAT_OOB_FILL_NONE);
}

#define PARAM(name, val) const int name = val
void build_schedule(Params& p) {
  PARAM(C_KB, 1028);
  PARAM(C_TILE, 10);
  PARAM(C_QX, 0);
  PARAM(C_START, 4500);
  PARAM(C_STEP, 2052);
  PARAM(C_ITEM, 300);
  PARAM(C_LAG, 8000);
  PARAM(C_SP, 5200);
  PARAM(C_TAIL, 22000);
  PARAM(C_SHORT, 0);
  PARAM(C_AT, 72);
  PARAM(C_LATE, 0);
  PARAM(C_LMASK, 0xAA0);
  PARAM(C_AM, 100);
  PARAM(C_ODD, 1300);
  PARAM(C_READY, 10000);
  auto gemm_cost = [&](int prob) {
    static const int nkb[NPROB] = {16, 8, 8, 16, 64, 16};
    return nkb[prob] * C_KB + C_TILE + (prob == 0 ? C_QX : 0);
  };
  PARAM(OPT, 0);
  p.opt = OPT;
  memset(p.g, 0xFF, sizeof(p.g));
  int n1[NCLUSTER];
  long t1[NCLUSTER];
  long ready[16];
  for (int c = 0; c < NCLUSTER; c++) { n1[c] = 0; t1[c] = C_START; }
  for (int i = 0; i < 16; i++) ready[i] = 0;
  auto add = [&](int c, int prob, int mp, int nt) {
    p.g[c][n1[c]++] = (uint16_t)((prob << 8) | (mp << 4) | nt);
    t1[c] += gemm_cost(prob);
    if (prob < 3) {
      const long r = t1[c] + C_READY;
      if (r > ready[nt]) ready[nt] = r;
    }
  };
  for (int r = 0; r < 8; r++)
    for (int c = 0; c < NA_CL; c++) {
      const int mp = c & 7, nt = 2 * r + ((c >> 3) & 1);
      for (int j = 0; j < (c < 16 ? 1 : 2); j++) {
        add(c, c < 16 ? 0 : 1 + j, mp, nt);
      }
    }
  long tA = 0;
  for (int c = 0; c < NA_CL; c++) {
    if (t1[c] > tA) tA = t1[c];
    add(c, 4, c & 7, c >> 3);
  }
  for (int i = 0; i < 96; i++) add(NA_CL + i % (NCLUSTER - NA_CL), 3, i % 8, i / 8);
  for (int c = NA_CL; c < NCLUSTER; c++) {
    p.g[c][n1[c]++] = 0x600;
    p.g[c][n1[c]++] = 0x500;
  }
  long tf[NB_CTA];
  bool done[512], started[NB_CTA];
  long fin[16];
  for (int c = 0; c < NB_CTA; c++) { tf[c] = t1[NA_CL + (c >> 1)] + 2000; started[c] = false; }
  for (int i = 0; i < 512; i++) done[i] = false;
  for (int i = 0; i < 16; i++) fin[i] = 0;
  auto alen = [&](int qt) { return (long)(qt + 1) * C_STEP + C_ITEM + (qt < 2 ? C_SHORT : 0); };
  int nq = NB_CTA;
  for (int n = 0; n < 512; n++) {
    int cb = 0;
    for (int c = 1; c < NB_CTA; c++)
      if (tf[c] < tf[cb]) cb = c;
    int best = -1;
    long bkey = 0;
    for (int i = 0; i < 512; i++) {
      if (done[i]) continue;
      const int hp = i >> 5;
      long dl = -(long)(16 - hp) * C_SP - C_LAG + ((i >> 4) & 1) * C_ODD;
      if (dl > -C_TAIL) dl = -C_TAIL;
      long key = dl - alen(i & 15) * (dl == -C_TAIL ? C_AT : C_AM) / 100;
      if ((i >> 4) == 31 && (C_LMASK >> (i & 15) & 1)) key += C_LATE;
      if (ready[hp] > tf[cb]) key += (1L << 40) + (ready[hp] - tf[cb]) * 1024;
      if (best < 0 || key < bkey) { best = i; bkey = key; }
    }
    done[best] = true;
    if (!started[cb]) { p.order[cb] = (uint16_t)best; started[cb] = true; }
    else p.order[nq++] = (uint16_t)best;
    if (ready[best >> 5] > tf[cb]) tf[cb] = ready[best >> 5];
    tf[cb] += alen(best & 15);
    if (tf[cb] + C_LAG > fin[best >> 5]) fin[best >> 5] = tf[cb] + C_LAG;
  }
}

}

extern "C" void kernel_launch(void* const* d_in, const int* in_sizes, int n_in, void* d_out, int out_size) {
  const bf16* A_x = (const bf16*)d_in[0];
  const bf16* A_c = (const bf16*)d_in[1];
  const bf16* A_wq = (const bf16*)d_in[2];
  const bf16* A_wuk = (const bf16*)d_in[3];
  const bf16* A_wuv = (const bf16*)d_in[4];
  const bf16* A_wo = (const bf16*)d_in[5];
  const bf16* B_x = (const bf16*)d_in[6];
  const bf16* B_wqkv = (const bf16*)d_in[7];
  const bf16* B_wo = (const bf16*)d_in[8];
  bf16* out = (bf16*)d_out;

  static Params p;
  static bf16 *q, *k, *v, *ctx, *qkvb, *ob;
  static bool init = false;
  if (!init) {
    cudaGetSymbolAddress((void**)&q, g_q);
    cudaGetSymbolAddress((void**)&k, g_k);
    cudaGetSymbolAddress((void**)&v, g_v);
    cudaGetSymbolAddress((void**)&ctx, g_ctx);
    cudaGetSymbolAddress((void**)&qkvb, g_qkvb);
    cudaGetSymbolAddress((void**)&ob, g_ob);
    cudaFuncSetAttribute(mega_kernel, cudaFuncAttributeMaxDynamicSharedMemorySize, SMEM_BYTES);
    build_schedule(p);
    if (p.opt & 2) ctx = q;
    init = true;
  }
  make_map(&p.ta[0], A_x, SEQ, DM, 128, 1);
  make_map(&p.tb[0], A_wq, DM, HHD, 64, 2);
  make_map(&p.tc[0], q, SEQ, HHD, 64, 1);
  make_map(&p.ta[1], A_c, SEQ, DC, 128, 1);
  make_map(&p.tb[1], A_wuk, DC, HHD, 64, 2);
  make_map(&p.tc[1], k, SEQ, HHD, 64, 1);
  make_map(&p.ta[2], A_c, SEQ, DC, 128, 1);
  make_map(&p.tb[2], A_wuv, DC, HHD, 64, 2);
  make_map(&p.tc[2], v, SEQ, HHD, 64, 1);
  make_map(&p.ta[3], B_x, SEQ, DM, 128, 1);
  make_map(&p.tb[3], B_wqkv, DM, 3 * DM, 64, 2);
  make_map(&p.tc[3], qkvb, SEQ, 3 * DM, 64, 1);
  make_map(&p.ta[4], ctx, SEQ, HHD, 128, 1);
  make_map(&p.tb[4], A_wo, HHD, DM, 64, 2);
  make_map(&p.tc[4], out, SEQ, 2 * DM, 64, 1);
  make_map(&p.ta[5], ob, SEQ, DM, 128, 1);
  make_map(&p.tb[5], B_wo, DM, DM, 64, 2);
  make_map(&p.tc[5], out, SEQ, 2 * DM, 64, 1);
  make_map(&p.tq, q, SEQ, HHD, 128, 2);
  make_map(&p.tk, k, SEQ, HHD, 128, 2);
  make_map(&p.tv, v, SEQ, HHD, 128, 2);
  make_map(&p.tl, qkvb, SEQ / 2, 6 * DM, 64, 1);
  make_map(&p.th, qkvb, SEQ / 2, 6 * DM, 72, 1);
  make_map(&p.to, ctx, SEQ, HHD, 128, 2);
  p.ob = ob;
  p.qkvb = qkvb;
  mega_kernel<<<NCTA, 384, SMEM_BYTES, cudaStreamPerThread>>>(p);
}
```

```cpp
#include <cuda_runtime.h>
#include <cuda_bf16.h>
#include <cuda.h>
#include <stdint.h>
#include <string.h>

namespace {

typedef __nv_bfloat16 bf16;

constexpr int SEQ = 2048;
constexpr int NHEAD = 32;
constexpr int HD = 128;
constexpr int DM = 1024;
constexpr int DC = 512;
constexpr int HHD = NHEAD * HD;

__device__ __align__(1024) bf16 g_q[SEQ * HHD];
__device__ __align__(1024) bf16 g_k[SEQ * HHD];
__device__ __align__(1024) bf16 g_v[SEQ * HHD];
__device__ __align__(1024) bf16 g_qkvb[SEQ * 3 * DM];
__device__ __align__(1024) bf16 g_ob[SEQ * DM];
constexpr int CNT_QKV = 0, CNT_CTX = 16, CNT_QKVB = 32, CNT_DONE = 33, CNT_QUEUE = 34, CNT_OB = 35, CNT_N = 39;
__device__ uint32_t g_cnt[CNT_N * 8];

__device__ __forceinline__ uint32_t smem_u32(const void* p) {
  return static_cast<uint32_t>(__cvta_generic_to_shared(p));
}
__device__ __forceinline__ void mbar_init(uint32_t bar, uint32_t count) {
  asm volatile("mbarrier.init.shared::cta.b64 [%0], %1;" ::"r"(bar), "r"(count) : "memory");
}
__device__ __forceinline__ void mbar_expect_tx(uint32_t bar, uint32_t bytes) {
  asm volatile("mbarrier.arrive.expect_tx.shared::cta.b64 _, [%0], %1;" ::"r"(bar), "r"(bytes) : "memory");
}
__device__ __forceinline__ void mbar_arrive(uint32_t bar) {
  asm volatile("mbarrier.arrive.shared::cta.b64 _, [%0];" ::"r"(bar) : "memory");
}
__device__ __forceinline__ void mbar_arrive_if(uint32_t bar, bool on) {
  asm volatile("{\n.reg .pred p;\nsetp.ne.b32 p, %1, 0;\n@p mbarrier.arrive.shared::cta.b64 _, [%0];\n}" ::"r"(bar),
               "r"((int)on)
               : "memory");
}
__device__ __forceinline__ void mbar_arrive_cluster_if(uint32_t bar, uint32_t cta, bool on) {
  asm volatile(
      "{\n.reg .b32 ra;\n.reg .pred p;\nsetp.ne.b32 p, %2, 0;\nmapa.shared::cluster.u32 ra, %0, %1;\n"
      "@p mbarrier.arrive.shared::cluster.b64 _, [ra];\n}" ::"r"(bar),
      "r"(cta), "r"((int)on)
      : "memory");
}
__device__ __forceinline__ bool mbar_try_wait(uint32_t bar, uint32_t parity) {
  uint32_t ok;
  asm volatile(
      "{\n.reg .pred p;\nmbarrier.try_wait.parity.shared::cta.b64 p, [%1], %2;\nselp.u32 %0, 1, 0, p;\n}"
      : "=r"(ok)
      : "r"(bar), "r"(parity)
      : "memory");
  return ok != 0;
}
__device__ __forceinline__ bool mbar_test(uint32_t bar, uint32_t parity) {
  uint32_t ok;
  asm volatile(
      "{\n.reg .pred p;\nmbarrier.test_wait.parity.shared::cta.b64 p, [%1], %2;\nselp.u32 %0, 1, 0, p;\n}"
      : "=r"(ok)
      : "r"(bar), "r"(parity)
      : "memory");
  return ok != 0;
}
#define DBG(i, v)
__device__ __forceinline__ void mbar_wait(uint32_t bar, uint32_t parity) {
  asm volatile(
      "{\n.reg .pred p;\n.reg .u32 t;\n"
      "mbarrier.try_wait.parity.shared::cta.b64 p, [%0], %1;\n"
      "@p bra DONE;\n"
      "mov.u32 t, 0x100000;\n"
      "LAB_WAIT:\n"
      "mbarrier.try_wait.parity.shared::cta.b64 p, [%0], %1;\n"
      "@p bra DONE;\n"
      "sub.u32 t, t, 1;\n"
      "setp.ne.u32 p, t, 0;\n"
      "@p bra LAB_WAIT;\n"
      "trap;\n"
      "DONE:\n}" ::"r"(bar),
      "r"(parity)
      : "memory");
}
constexpr uint64_t EV_NORMAL = 0x1000000000000000ull;
__device__ __forceinline__ uint64_t policy_first() {
  uint64_t p;
  asm("createpolicy.fractional.L2::evict_first.b64 %0, 1.0;" : "=l"(p));
  return p;
}
#define EV_FIRST policy_first()
__device__ __forceinline__ void tma_load_3d(uint32_t dst, const CUtensorMap* map, int c0, int c1, int c2,
                                            uint32_t bar, uint64_t hint) {
  asm volatile(
      "cp.async.bulk.tensor.3d.shared::cluster.global.mbarrier::complete_tx::bytes.L2::cache_hint [%0], [%1, {%3, %4, %5}], [%2], %6;" ::"r"(dst),
      "l"(map), "r"(bar), "r"(c0), "r"(c1), "r"(c2), "l"(hint)
      : "memory");
}
__device__ __forceinline__ void tma_load_3d_mc(uint32_t dst, const CUtensorMap* map, int c0, int c1, int c2,
                                               uint32_t bar, uint16_t mask, uint64_t hint) {
  asm volatile(
      "cp.async.bulk.tensor.3d.shared::cluster.global.mbarrier::complete_tx::bytes.multicast::cluster.L2::cache_hint [%0], [%1, {%3, %4, %5}], [%2], %6, %7;" ::"r"(dst),
      "l"(map), "r"(bar), "r"(c0), "r"(c1), "r"(c2), "h"(mask), "l"(hint)
      : "memory");
}
__device__ __forceinline__ void tma_store_3d(const CUtensorMap* map, uint32_t src, int c0, int c1, int c2, uint64_t hint) {
  asm volatile("cp.async.bulk.tensor.3d.global.shared::cta.bulk_group.L2::cache_hint [%0, {%2, %3, %4}], [%1], %5;" ::"l"(map),
               "r"(src), "r"(c0), "r"(c1), "r"(c2), "l"(hint)
               : "memory");
}
__device__ __forceinline__ void bulk_commit() { asm volatile("cp.async.bulk.commit_group;" ::: "memory"); }
template <int N>
__device__ __forceinline__ void bulk_wait_read() {
  asm volatile("cp.async.bulk.wait_group.read %0;" ::"n"(N) : "memory");
}
template <int N>
__device__ __forceinline__ void bulk_wait() {
  asm volatile("cp.async.bulk.wait_group %0;" ::"n"(N) : "memory");
}
__device__ __forceinline__ void fence_proxy_async_smem() {
  asm volatile("fence.proxy.async.shared::cta;" ::: "memory");
}
__device__ __forceinline__ bool elect_one() {
  uint32_t pred;
  asm volatile("{\n.reg .pred P;\nelect.sync _|P, 0xffffffff;\nselp.b32 %0, 1, 0, P;\n}" : "=r"(pred));
  return pred != 0;
}
__device__ __forceinline__ void named_bar_sync(int id, int n) {
  asm volatile("bar.sync %0, %1;" ::"r"(id), "r"(n) : "memory");
}
__device__ __forceinline__ void named_bar_arrive(int id, int n) {
  asm volatile("bar.arrive %0, %1;" ::"r"(id), "r"(n) : "memory");
}
__device__ __forceinline__ void named_bar_sync_if(int id, int n, bool on) {
  asm volatile("{\n.reg .pred p;\nsetp.ne.b32 p, %2, 0;\n@p bar.sync %0, %1;\n}" ::"r"(id), "r"(n), "r"((int)on) : "memory");
}
__device__ __forceinline__ void named_bar_arrive_if(int id, int n, bool on) {
  asm volatile("{\n.reg .pred p;\nsetp.ne.b32 p, %2, 0;\n@p bar.arrive %0, %1;\n}" ::"r"(id), "r"(n), "r"((int)on) : "memory");
}
template <int N>
__device__ __forceinline__ void reg_alloc() {
  asm volatile("setmaxnreg.inc.sync.aligned.u32 %0;" ::"n"(N));
}
template <int N>
__device__ __forceinline__ void reg_dealloc() {
  asm volatile("setmaxnreg.dec.sync.aligned.u32 %0;" ::"n"(N));
}
__device__ __forceinline__ void wgmma_fence() { asm volatile("wgmma.fence.sync.aligned;" ::: "memory"); }
__device__ __forceinline__ void wgmma_commit() { asm volatile("wgmma.commit_group.sync.aligned;" ::: "memory"); }
template <int N>
__device__ __forceinline__ void wgmma_wait() {
  asm volatile("wgmma.wait_group.sync.aligned %0;" ::"n"(N) : "memory");
}
template <int N>
__device__ __forceinline__ void fence_regs(float (&d)[N]) {
#pragma unroll
  for (int i = 0; i < N; i++) asm volatile("" : "+f"(d[i])::"memory");
}
__device__ __forceinline__ void fence_regs(uint32_t (&d)[32]) {
#pragma unroll
  for (int i = 0; i < 16; i++) asm volatile("" : "+r"(d[i])::"memory");
}
template <int N>
__device__ __forceinline__ void undef_regs(float (&d)[N]) {
#pragma unroll
  for (int i = 0; i < N; i++) d[i] = 0.f;
}
template <int N>
__device__ __forceinline__ void undef_regs(uint32_t (&d)[N]) {
#pragma unroll
  for (int i = 0; i < N; i++) d[i] = 0u;
}
__device__ __forceinline__ uint32_t pack_bf16(float lo, float hi) {
  uint32_t r;
  asm("cvt.rn.bf16x2.f32 %0, %1, %2;" : "=r"(r) : "f"(hi), "f"(lo));
  return r;
}
__device__ __forceinline__ void stmatrix_x4(uint32_t addr, uint32_t r0, uint32_t r1, uint32_t r2, uint32_t r3) {
  asm volatile("stmatrix.sync.aligned.m8n8.x4.shared.b16 [%0], {%1, %2, %3, %4};" ::"r"(addr), "r"(r0), "r"(r1),
               "r"(r2), "r"(r3)
               : "memory");
}
__device__ __forceinline__ void stmatrix_x4_p(uint32_t addr, uint32_t r0, uint32_t r1, uint32_t r2, uint32_t r3,
                                              bool on) {
  asm volatile("{\n.reg .pred p;\nsetp.ne.b32 p, %5, 0;\n@p stmatrix.sync.aligned.m8n8.x4.shared.b16 [%0], {%1, %2, %3, %4};\n}" ::"r"(addr),
               "r"(r0), "r"(r1), "r"(r2), "r"(r3), "r"((int)on)
               : "memory");
}
__device__ __forceinline__ float ex2(float x) {
  float y;
  asm("ex2.approx.ftz.f32 %0, %1;" : "=f"(y) : "f"(x));
  return y;
}
__device__ __forceinline__ float rcp(float x) {
  float y;
  asm("rcp.approx.ftz.f32 %0, %1;" : "=f"(y) : "f"(x));
  return y;
}
__device__ __forceinline__ float ex2v(float x) {
  float y;
  asm volatile("ex2.approx.ftz.f32 %0, %1;" : "=f"(y) : "f"(x));
  return y;
}
__device__ __forceinline__ float addv(float a, float b) {
  float y;
  asm volatile("add.f32 %0, %1, %2;" : "=f"(y) : "f"(a), "f"(b));
  return y;
}
__device__ __forceinline__ void mbar_arrive_elect(uint32_t bar, bool on) {
  asm volatile("{\n.reg .pred p, q;\nelect.sync _|q, 0xffffffff;\nsetp.ne.and.b32 p, %1, 0, q;\n@p mbarrier.arrive.shared::cta.b64 _, [%0];\n}" ::"r"(bar),
               "r"((int)on)
               : "memory");
}
__device__ __forceinline__ float mbar_test2(uint32_t bar0, uint32_t par0, uint32_t bar1, uint32_t par1) {
  float f;
  asm volatile(
      "{\n.reg .pred p, q;\nmbarrier.test_wait.parity.shared::cta.b64 p, [%1], %2;\n"
      "mbarrier.test_wait.parity.shared::cta.b64 q, [%3], %4;\nand.pred p, p, q;\nselp.f32 %0, 0f00000000, 0f80000000, p;\n}"
      : "=f"(f)
      : "r"(bar0), "r"(par0), "r"(bar1), "r"(par1)
      : "memory");
  return f;
}
__device__ __forceinline__ void mbar_wait_rest(uint32_t bar, uint32_t parity, bool ok) {
  asm volatile(
      "{\n.reg .pred p;\n.reg .u32 t;\n"
      "setp.ne.b32 p, %2, 0;\n"
      "@p bra DONE;\n"
      "mov.u32 t, 0x100000;\n"
      "LAB_WAIT:\n"
      "mbarrier.try_wait.parity.shared::cta.b64 p, [%0], %1;\n"
      "@p bra DONE;\n"
      "sub.u32 t, t, 1;\n"
      "setp.ne.u32 p, t, 0;\n"
      "@p bra LAB_WAIT;\n"
      "trap;\n"
      "DONE:\n}" ::"r"(bar),
      "r"(parity), "r"((int)ok)
      : "memory");
}
__device__ __forceinline__ void cnt_signal(int idx, uint32_t inc = 1) {
  asm volatile("red.release.gpu.global.add.u32 [%0], %1;" ::"l"(g_cnt + idx * 8), "r"(inc) : "memory");
}
__device__ __forceinline__ void cnt_signal_done(int idx, uint32_t inc = 1) {
  asm volatile("red.relaxed.gpu.global.add.u32 [%0], %1;" ::"l"(g_cnt + idx * 8), "r"(inc) : "memory");
}
__device__ __forceinline__ uint32_t cnt_next(int idx) {
  uint32_t v;
  asm volatile("atom.relaxed.gpu.global.add.u32 %0, [%1], 1;" : "=r"(v) : "l"(g_cnt + idx * 8) : "memory");
  return v;
}
__device__ __forceinline__ uint32_t cnt_peek(int idx) {
  uint32_t v;
  asm volatile("ld.acquire.gpu.global.u32 %0, [%1];" : "=r"(v) : "l"(g_cnt + idx * 8) : "memory");
  return v;
}
__device__ __forceinline__ void cnt_wait(int idx, uint32_t target) {
  asm volatile(
      "{\n.reg .pred p;\n.reg .u32 v, t0, t1;\n"
      "ld.acquire.gpu.global.u32 v, [%0];\n"
      "setp.ge.u32 p, v, %1;\n"
      "@p bra DONE;\n"
      "mov.u32 t0, %%clock;\n"
      "LAB_WAIT:\n"
      "nanosleep.u32 100;\n"
      "ld.acquire.gpu.global.u32 v, [%0];\n"
      "setp.ge.u32 p, v, %1;\n"
      "@p bra DONE;\n"
      "mov.u32 t1, %%clock;\n"
      "sub.u32 t1, t1, t0;\n"
      "setp.lt.u32 p, t1, 0x80000000;\n"
      "@p bra LAB_WAIT;\n"
      "trap;\n"
      "DONE:\n}" ::"l"(g_cnt + idx * 8),
      "r"(target)
      : "memory");
}
__device__ __forceinline__ void cnt_wait_bit(int idx, uint32_t bit, uint32_t& v) {
  asm volatile(
      "{\n.reg .pred p;\n.reg .u32 x, t0, t1;\n"
      "and.b32 x, %0, %2;\n"
      "setp.ne.u32 p, x, 0;\n"
      "@p bra DONE;\n"
      "mov.u32 t0, %%clock;\n"
      "LAB_WAIT:\n"
      "ld.acquire.gpu.global.u32 %0, [%1];\n"
      "and.b32 x, %0, %2;\n"
      "setp.ne.u32 p, x, 0;\n"
      "@p bra DONE;\n"
      "nanosleep.u32 64;\n"
      "mov.u32 t1, %%clock;\n"
      "sub.u32 t1, t1, t0;\n"
      "setp.lt.u32 p, t1, 0x80000000;\n"
      "@p bra LAB_WAIT;\n"
      "trap;\n"
      "DONE:\n}" : "+r"(v) : "l"(g_cnt + idx * 8),
      "r"(bit)
      : "memory");
}
__device__ __forceinline__ bool cnt_done(uint32_t total) {
  uint32_t old;
  asm volatile("atom.acq_rel.gpu.global.add.u32 %0, [%1], 1;" : "=r"(old) : "l"(g_cnt + CNT_DONE * 8) : "memory");
  return old == total - 1;
}
__device__ __forceinline__ void cnt_rearm() {
#pragma unroll
  for (int i = 0; i < CNT_N; i++) g_cnt[i * 8] = 0;
}
__device__ __forceinline__ void fence_proxy_async_global() { asm volatile("fence.proxy.async.global;" ::: "memory"); }
#define TL(role, code)
#define TL0(code)
#define TL_DECL
#define TR_DECL
#define TR(code)
#define TRI(id, code)
#define TW_DECL
#define TW(w, stmt) stmt
#define TW_FLUSH()
#define TW_END()

__device__ __forceinline__ uint32_t make_desc(uint32_t addr, uint32_t lbo_bytes) {
  return (addr >> 4) + ((lbo_bytes >> 4) << 16);
}

__device__ __forceinline__ void wgmma_ss_n128(float (&d)[64], uint32_t da, uint32_t db, int scale_d) {
  asm volatile("{\n.reg .pred p;\n.reg .b64 a, b;\nsetp.ne.b32 p, %66, 0;\nmov.b64 a, {%64, 0x40000040};\nmov.b64 b, {%65, 0x40000040};\n"
    "wgmma.mma_async.sync.aligned.m64n128k16.f32.bf16.bf16 {%0, %1, %2, %3, %4, %5, %6, %7, %8, %9, %10, %11, %12, %13, %14, %15, %16, %17, %18, %19, %20, %21, %22, %23, %24, %25, %26, %27, %28, %29, %30, %31, %32, %33, %34, %35, %36, %37, %38, %39, %40, %41, %42, %43, %44, %45, %46, %47, %48, %49, %50, %51, %52, %53, %54, %55, %56, %57, %58, %59, %60, %61, %62, %63}, a, b, p, 1, 1, 0, 0;\n}\n"
    : "+f"(d[0]), "+f"(d[1]), "+f"(d[2]), "+f"(d[3]), "+f"(d[4]), "+f"(d[5]), "+f"(d[6]), "+f"(d[7]), "+f"(d[8]), "+f"(d[9]), "+f"(d[10]), "+f"(d[11]), "+f"(d[12]), "+f"(d[13]), "+f"(d[14]), "+f"(d[15]), "+f"(d[16]), "+f"(d[17]), "+f"(d[18]), "+f"(d[19]), "+f"(d[20]), "+f"(d[21]), "+f"(d[22]), "+f"(d[23]), "+f"(d[24]), "+f"(d[25]), "+f"(d[26]), "+f"(d[27]), "+f"(d[28]), "+f"(d[29]), "+f"(d[30]), "+f"(d[31]), "+f"(d[32]), "+f"(d[33]), "+f"(d[34]), "+f"(d[35]), "+f"(d[36]), "+f"(d[37]), "+f"(d[38]), "+f"(d[39]), "+f"(d[40]), "+f"(d[41]), "+f"(d[42]), "+f"(d[43]), "+f"(d[44]), "+f"(d[45]), "+f"(d[46]), "+f"(d[47]), "+f"(d[48]), "+f"(d[49]), "+f"(d[50]), "+f"(d[51]), "+f"(d[52]), "+f"(d[53]), "+f"(d[54]), "+f"(d[55]), "+f"(d[56]), "+f"(d[57]), "+f"(d[58]), "+f"(d[59]), "+f"(d[60]), "+f"(d[61]), "+f"(d[62]), "+f"(d[63])
    : "r"(da), "r"(db), "r"(scale_d));
}
__device__ __forceinline__ void wgmma_ss_n64(float (&d)[32], uint32_t da, uint32_t db, int scale_d) {
  asm volatile("{\n.reg .pred p;\n.reg .b64 a, b;\nsetp.ne.b32 p, %34, 0;\nmov.b64 a, {%32, 0x40000040};\nmov.b64 b, {%33, 0x40000040};\n"
    "wgmma.mma_async.sync.aligned.m64n64k16.f32.bf16.bf16 {%0, %1, %2, %3, %4, %5, %6, %7, %8, %9, %10, %11, %12, %13, %14, %15, %16, %17, %18, %19, %20, %21, %22, %23, %24, %25, %26, %27, %28, %29, %30, %31}, a, b, p, 1, 1, 0, 0;\n}\n"
    : "+f"(d[0]), "+f"(d[1]), "+f"(d[2]), "+f"(d[3]), "+f"(d[4]), "+f"(d[5]), "+f"(d[6]), "+f"(d[7]), "+f"(d[8]), "+f"(d[9]), "+f"(d[10]), "+f"(d[11]), "+f"(d[12]), "+f"(d[13]), "+f"(d[14]), "+f"(d[15]), "+f"(d[16]), "+f"(d[17]), "+f"(d[18]), "+f"(d[19]), "+f"(d[20]), "+f"(d[21]), "+f"(d[22]), "+f"(d[23]), "+f"(d[24]), "+f"(d[25]), "+f"(d[26]), "+f"(d[27]), "+f"(d[28]), "+f"(d[29]), "+f"(d[30]), "+f"(d[31])
    : "r"(da), "r"(db), "r"(scale_d));
}
__device__ __forceinline__ void wgmma_rs_n128_tb(float (&d)[64], uint32_t a0, uint32_t a1, uint32_t a2, uint32_t a3, uint32_t db, int scale_d) {
  asm volatile("{\n.reg .pred p;\n.reg .b64 b;\nsetp.ne.b32 p, %69, 0;\nmov.b64 b, {%68, 0x40000040};\n"
    "wgmma.mma_async.sync.aligned.m64n128k16.f32.bf16.bf16 {%0, %1, %2, %3, %4, %5, %6, %7, %8, %9, %10, %11, %12, %13, %14, %15, %16, %17, %18, %19, %20, %21, %22, %23, %24, %25, %26, %27, %28, %29, %30, %31, %32, %33, %34, %35, %36, %37, %38, %39, %40, %41, %42, %43, %44, %45, %46, %47, %48, %49, %50, %51, %52, %53, %54, %55, %56, %57, %58, %59, %60, %61, %62, %63}, {%64, %65, %66, %67}, b, p, 1, 1, 1;\n}\n"
    : "+f"(d[0]), "+f"(d[1]), "+f"(d[2]), "+f"(d[3]), "+f"(d[4]), "+f"(d[5]), "+f"(d[6]), "+f"(d[7]), "+f"(d[8]), "+f"(d[9]), "+f"(d[10]), "+f"(d[11]), "+f"(d[12]), "+f"(d[13]), "+f"(d[14]), "+f"(d[15]), "+f"(d[16]), "+f"(d[17]), "+f"(d[18]), "+f"(d[19]), "+f"(d[20]), "+f"(d[21]), "+f"(d[22]), "+f"(d[23]), "+f"(d[24]), "+f"(d[25]), "+f"(d[26]), "+f"(d[27]), "+f"(d[28]), "+f"(d[29]), "+f"(d[30]), "+f"(d[31]), "+f"(d[32]), "+f"(d[33]), "+f"(d[34]), "+f"(d[35]), "+f"(d[36]), "+f"(d[37]), "+f"(d[38]), "+f"(d[39]), "+f"(d[40]), "+f"(d[41]), "+f"(d[42]), "+f"(d[43]), "+f"(d[44]), "+f"(d[45]), "+f"(d[46]), "+f"(d[47]), "+f"(d[48]), "+f"(d[49]), "+f"(d[50]), "+f"(d[51]), "+f"(d[52]), "+f"(d[53]), "+f"(d[54]), "+f"(d[55]), "+f"(d[56]), "+f"(d[57]), "+f"(d[58]), "+f"(d[59]), "+f"(d[60]), "+f"(d[61]), "+f"(d[62]), "+f"(d[63])
    : "r"(a0), "r"(a1), "r"(a2), "r"(a3), "r"(db), "r"(scale_d));
}
__device__ __forceinline__ void wgmma_ss_n72_init(float (&d)[36], uint32_t da, uint32_t db) {
  asm volatile("{\n.reg .pred p;\n.reg .b64 a, b;\nsetp.ne.b32 p, 0, 0;\nmov.b64 a, {%36, 0x40000040};\nmov.b64 b, {%37, 0x40000040};\n"
    "wgmma.mma_async.sync.aligned.m64n72k16.f32.bf16.bf16 {%0, %1, %2, %3, %4, %5, %6, %7, %8, %9, %10, %11, %12, %13, %14, %15, %16, %17, %18, %19, %20, %21, %22, %23, %24, %25, %26, %27, %28, %29, %30, %31, %32, %33, %34, %35}, a, b, p, 1, 1, 0, 0;\n}\n"
    : "=f"(d[0]), "=f"(d[1]), "=f"(d[2]), "=f"(d[3]), "=f"(d[4]), "=f"(d[5]), "=f"(d[6]), "=f"(d[7]), "=f"(d[8]), "=f"(d[9]), "=f"(d[10]), "=f"(d[11]), "=f"(d[12]), "=f"(d[13]), "=f"(d[14]), "=f"(d[15]), "=f"(d[16]), "=f"(d[17]), "=f"(d[18]), "=f"(d[19]), "=f"(d[20]), "=f"(d[21]), "=f"(d[22]), "=f"(d[23]), "=f"(d[24]), "=f"(d[25]), "=f"(d[26]), "=f"(d[27]), "=f"(d[28]), "=f"(d[29]), "=f"(d[30]), "=f"(d[31]), "=f"(d[32]), "=f"(d[33]), "=f"(d[34]), "=f"(d[35])
    : "r"(da), "r"(db));
}
__device__ __forceinline__ void wgmma_ss_n72(float (&d)[36], uint32_t da, uint32_t db, int scale_d) {
  asm volatile("{\n.reg .pred p;\n.reg .b64 a, b;\nsetp.ne.b32 p, %38, 0;\nmov.b64 a, {%36, 0x40000040};\nmov.b64 b, {%37, 0x40000040};\n"
    "wgmma.mma_async.sync.aligned.m64n72k16.f32.bf16.bf16 {%0, %1, %2, %3, %4, %5, %6, %7, %8, %9, %10, %11, %12, %13, %14, %15, %16, %17, %18, %19, %20, %21, %22, %23, %24, %25, %26, %27, %28, %29, %30, %31, %32, %33, %34, %35}, a, b, p, 1, 1, 0, 0;\n}\n"
    : "+f"(d[0]), "+f"(d[1]), "+f"(d[2]), "+f"(d[3]), "+f"(d[4]), "+f"(d[5]), "+f"(d[6]), "+f"(d[7]), "+f"(d[8]), "+f"(d[9]), "+f"(d[10]), "+f"(d[11]), "+f"(d[12]), "+f"(d[13]), "+f"(d[14]), "+f"(d[15]), "+f"(d[16]), "+f"(d[17]), "+f"(d[18]), "+f"(d[19]), "+f"(d[20]), "+f"(d[21]), "+f"(d[22]), "+f"(d[23]), "+f"(d[24]), "+f"(d[25]), "+f"(d[26]), "+f"(d[27]), "+f"(d[28]), "+f"(d[29]), "+f"(d[30]), "+f"(d[31]), "+f"(d[32]), "+f"(d[33]), "+f"(d[34]), "+f"(d[35])
    : "r"(da), "r"(db), "r"(scale_d));
}
template <int OA, int OB>
__device__ __forceinline__ void wgmma_ss_n128_tb(float (&d)[64], uint32_t da, uint32_t db, int scale_d) {
  asm volatile("{\n.reg .pred p;\n.reg .b64 a, b;\n.reg .b32 x, y;\nsetp.ne.b32 p, %66, 0;\nadd.u32 x, %64, %67;\nadd.u32 y, %65, %68;\nmov.b64 a, {x, 0x40000040};\nmov.b64 b, {y, 0x40000040};\n"
    "wgmma.mma_async.sync.aligned.m64n128k16.f32.bf16.bf16 {%0, %1, %2, %3, %4, %5, %6, %7, %8, %9, %10, %11, %12, %13, %14, %15, %16, %17, %18, %19, %20, %21, %22, %23, %24, %25, %26, %27, %28, %29, %30, %31, %32, %33, %34, %35, %36, %37, %38, %39, %40, %41, %42, %43, %44, %45, %46, %47, %48, %49, %50, %51, %52, %53, %54, %55, %56, %57, %58, %59, %60, %61, %62, %63}, a, b, p, 1, 1, 0, 1;\n}\n"
    : "+f"(d[0]), "+f"(d[1]), "+f"(d[2]), "+f"(d[3]), "+f"(d[4]), "+f"(d[5]), "+f"(d[6]), "+f"(d[7]), "+f"(d[8]), "+f"(d[9]), "+f"(d[10]), "+f"(d[11]), "+f"(d[12]), "+f"(d[13]), "+f"(d[14]), "+f"(d[15]), "+f"(d[16]), "+f"(d[17]), "+f"(d[18]), "+f"(d[19]), "+f"(d[20]), "+f"(d[21]), "+f"(d[22]), "+f"(d[23]), "+f"(d[24]), "+f"(d[25]), "+f"(d[26]), "+f"(d[27]), "+f"(d[28]), "+f"(d[29]), "+f"(d[30]), "+f"(d[31]), "+f"(d[32]), "+f"(d[33]), "+f"(d[34]), "+f"(d[35]), "+f"(d[36]), "+f"(d[37]), "+f"(d[38]), "+f"(d[39]), "+f"(d[40]), "+f"(d[41]), "+f"(d[42]), "+f"(d[43]), "+f"(d[44]), "+f"(d[45]), "+f"(d[46]), "+f"(d[47]), "+f"(d[48]), "+f"(d[49]), "+f"(d[50]), "+f"(d[51]), "+f"(d[52]), "+f"(d[53]), "+f"(d[54]), "+f"(d[55]), "+f"(d[56]), "+f"(d[57]), "+f"(d[58]), "+f"(d[59]), "+f"(d[60]), "+f"(d[61]), "+f"(d[62]), "+f"(d[63])
    : "r"(da), "r"(db), "r"(scale_d), "n"(OA), "n"(OB));
}
template <int OA, int OB>
__device__ __forceinline__ void wgmma_ss_n256_tbo(float (&d)[128], uint32_t da, uint32_t db, int scale_d) {
  asm volatile("{\n.reg .pred p;\n.reg .b64 a, b;\n.reg .b32 x, y;\nsetp.ne.b32 p, %130, 0;\nadd.u32 x, %128, %131;\nadd.u32 y, %129, %132;\nmov.b64 a, {x, 0x40000040};\nmov.b64 b, {y, 0x40000040};\n"
    "wgmma.mma_async.sync.aligned.m64n256k16.f32.bf16.bf16 {%0, %1, %2, %3, %4, %5, %6, %7, %8, %9, %10, %11, %12, %13, %14, %15, %16, %17, %18, %19, %20, %21, %22, %23, %24, %25, %26, %27, %28, %29, %30, %31, %32, %33, %34, %35, %36, %37, %38, %39, %40, %41, %42, %43, %44, %45, %46, %47, %48, %49, %50, %51, %52, %53, %54, %55, %56, %57, %58, %59, %60, %61, %62, %63, %64, %65, %66, %67, %68, %69, %70, %71, %72, %73, %74, %75, %76, %77, %78, %79, %80, %81, %82, %83, %84, %85, %86, %87, %88, %89, %90, %91, %92, %93, %94, %95, %96, %97, %98, %99, %100, %101, %102, %103, %104, %105, %106, %107, %108, %109, %110, %111, %112, %113, %114, %115, %116, %117, %118, %119, %120, %121, %122, %123, %124, %125, %126, %127}, a, b, p, 1, 1, 0, 1;\n}\n"
    : "+f"(d[0]), "+f"(d[1]), "+f"(d[2]), "+f"(d[3]), "+f"(d[4]), "+f"(d[5]), "+f"(d[6]), "+f"(d[7]), "+f"(d[8]), "+f"(d[9]), "+f"(d[10]), "+f"(d[11]), "+f"(d[12]), "+f"(d[13]), "+f"(d[14]), "+f"(d[15]), "+f"(d[16]), "+f"(d[17]), "+f"(d[18]), "+f"(d[19]), "+f"(d[20]), "+f"(d[21]), "+f"(d[22]), "+f"(d[23]), "+f"(d[24]), "+f"(d[25]), "+f"(d[26]), "+f"(d[27]), "+f"(d[28]), "+f"(d[29]), "+f"(d[30]), "+f"(d[31]), "+f"(d[32]), "+f"(d[33]), "+f"(d[34]), "+f"(d[35]), "+f"(d[36]), "+f"(d[37]), "+f"(d[38]), "+f"(d[39]), "+f"(d[40]), "+f"(d[41]), "+f"(d[42]), "+f"(d[43]), "+f"(d[44]), "+f"(d[45]), "+f"(d[46]), "+f"(d[47]), "+f"(d[48]), "+f"(d[49]), "+f"(d[50]), "+f"(d[51]), "+f"(d[52]), "+f"(d[53]), "+f"(d[54]), "+f"(d[55]), "+f"(d[56]), "+f"(d[57]), "+f"(d[58]), "+f"(d[59]), "+f"(d[60]), "+f"(d[61]), "+f"(d[62]), "+f"(d[63]), "+f"(d[64]), "+f"(d[65]), "+f"(d[66]), "+f"(d[67]), "+f"(d[68]), "+f"(d[69]), "+f"(d[70]), "+f"(d[71]), "+f"(d[72]), "+f"(d[73]), "+f"(d[74]), "+f"(d[75]), "+f"(d[76]), "+f"(d[77]), "+f"(d[78]), "+f"(d[79]), "+f"(d[80]), "+f"(d[81]), "+f"(d[82]), "+f"(d[83]), "+f"(d[84]), "+f"(d[85]), "+f"(d[86]), "+f"(d[87]), "+f"(d[88]), "+f"(d[89]), "+f"(d[90]), "+f"(d[91]), "+f"(d[92]), "+f"(d[93]), "+f"(d[94]), "+f"(d[95]), "+f"(d[96]), "+f"(d[97]), "+f"(d[98]), "+f"(d[99]), "+f"(d[100]), "+f"(d[101]), "+f"(d[102]), "+f"(d[103]), "+f"(d[104]), "+f"(d[105]), "+f"(d[106]), "+f"(d[107]), "+f"(d[108]), "+f"(d[109]), "+f"(d[110]), "+f"(d[111]), "+f"(d[112]), "+f"(d[113]), "+f"(d[114]), "+f"(d[115]), "+f"(d[116]), "+f"(d[117]), "+f"(d[118]), "+f"(d[119]), "+f"(d[120]), "+f"(d[121]), "+f"(d[122]), "+f"(d[123]), "+f"(d[124]), "+f"(d[125]), "+f"(d[126]), "+f"(d[127])
    : "r"(da), "r"(db), "r"(scale_d), "n"(OA), "n"(OB));
}

constexpr int NCTA = 132;
constexpr int NCLUSTER = 66;
constexpr int NPROB = 6;
#define DO_LOCAL true
#define DO_ATT true
#define NA_CL_ 32
#define NITEMS 512
constexpr int G1_MAX = 24, NA_CL = NA_CL_, NB_CTA = NCTA - 2 * NA_CL;
constexpr int TILE32K = 32768;
constexpr uint32_t DBASE = 1024;
constexpr int OFF_STG = 4 * TILE32K;
constexpr int OFF_A = 5 * TILE32K;
constexpr int OFF_BAR = 7 * TILE32K;
constexpr int L_K = 8192, L_V = L_K + 9216, L_P = L_V + 9216;
constexpr int SMEM_BYTES = OFF_BAR + 1024;
constexpr int B_GFULL = 0, B_GEMPTY = 32, B_AFULL = 64, B_AEMPTY = 104, B_QFULL = 144, B_QEMPTY = 160,
              B_SFULL = 176, B_SEMPTY = 208, B_OFULL = 240, B_STGFREE = 256, S_CODE = 272, B_SFULL2 = 304;
#define FS 2
#define HW 1
#define PACE 900u
#define REG_C 232
#define REG_P 40

struct Params {
  CUtensorMap ta[NPROB];
  CUtensorMap tb[NPROB];
  CUtensorMap tc[NPROB];
  CUtensorMap tq, tk, tv, to, tl, th;
  bf16* ob;
  uint16_t g[NCLUSTER][G1_MAX];
  uint16_t order[512];
};
__device__ __forceinline__ uint32_t tail_item(uint32_t code) {
  return (code & 0x7FFF) < 64 ? (5u << 8) | ((code & 4) << 4) | (code & 0x33) : 0xFFFFu;
}
#define HM 0x39383F30
#define HINT(b) ((HM >> (b) & 1) ? EV_FIRST : EV_NORMAL)
__device__ __forceinline__ uint32_t lds32(uint32_t a) {
  uint32_t v;
  asm volatile("ld.shared.u32 %0, [%1];" : "=r"(v) : "r"(a) : "memory");
  return v;
}
__device__ __forceinline__ uint4 lds128(uint32_t a) {
  uint4 v;
  asm volatile("ld.shared.v4.u32 {%0, %1, %2, %3}, [%4];" : "=r"(v.x), "=r"(v.y), "=r"(v.z), "=r"(v.w) : "r"(a) : "memory");
  return v;
}
__device__ __forceinline__ void sts64(uint32_t a, float x, float y) {
  asm volatile("st.shared.v2.f32 [%0], {%1, %2};" ::"r"(a), "f"(x), "f"(y) : "memory");
}
__device__ __forceinline__ void sts32(uint32_t a, uint32_t v) {
  asm volatile("st.shared.u32 [%0], %1;" ::"r"(a), "r"(v) : "memory");
}
__device__ __forceinline__ uint32_t opaque_tid() {
  uint32_t t;
  asm volatile("mov.u32 %0, %%tid.x;" : "=r"(t));
  return t;
}
__device__ __forceinline__ uint32_t stg_off(uint32_t tid) {
  return (tid >> 5) * 2048 + (tid & 15) * 128 + ((((tid >> 4) & 1) ^ (tid & 7)) << 4);
}
__device__ __forceinline__ int prob_nkb4(int prob) { return (0x4F4224 >> (prob * 4) & 15) + (prob == 4); }

constexpr float SM_C = 0.08838834764831845f * 1.4426950408889634f;
constexpr float SM_HI = 1099511627776.0f;
constexpr float SM_LO = 8.673617379884035e-19f;
__device__ __forceinline__ void softmax_max(const float (&s)[64], float& a0, float& a1) {
  a0 = fmaxf(s[0], s[1]);
  a1 = fmaxf(s[2], s[3]);
#pragma unroll
  for (int j = 1; j < 16; j++) {
    a0 = fmaxf(a0, fmaxf(s[4 * j], s[4 * j + 1]));
    a1 = fmaxf(a1, fmaxf(s[4 * j + 2], s[4 * j + 3]));
  }
  a0 = fmaxf(a0, __shfl_xor_sync(0xffffffffu, a0, 1));
  a1 = fmaxf(a1, __shfl_xor_sync(0xffffffffu, a1, 1));
  a0 = fmaxf(a0, __shfl_xor_sync(0xffffffffu, a0, 2));
  a1 = fmaxf(a1, __shfl_xor_sync(0xffffffffu, a1, 2));
}
template <int J0, int J1, bool OFS, int N>
__device__ __forceinline__ void softmax_exp(const float (&s)[64], float b0, float b1, uint32_t (&out)[N], float& t0,
                                            float& t1) {
#pragma unroll
  for (int j = J0; j < J1; j++) {
    const float e0 = ex2(OFS ? s[4 * j] + b0 : s[4 * j]);
    const float e1 = ex2(OFS ? s[4 * j + 1] + b0 : s[4 * j + 1]);
    const float e2 = ex2(OFS ? s[4 * j + 2] + b1 : s[4 * j + 2]);
    const float e3 = ex2(OFS ? s[4 * j + 3] + b1 : s[4 * j + 3]);
    t0 += e0 + e1;
    t1 += e2 + e3;
    out[2 * j] = pack_bf16(e0, e1);
    out[2 * j + 1] = pack_bf16(e2, e3);
  }
}

__device__ __forceinline__ uint32_t scale_q(uint32_t x) {
  uint32_t t, y;
  asm("mul.rn.bf16x2 %0, %1, %2;" : "=r"(t) : "r"(x), "r"(0xb9d8b9d8u));
  asm("fma.rn.bf16x2 %0, %1, %2, %3;" : "=r"(y) : "r"(x), "r"(0x3e033e03u), "r"(t));
  return y;
}

__global__ void __cluster_dims__(2, 1, 1) __launch_bounds__(384, 1) mega_kernel(const __grid_constant__ Params p) {
  extern __shared__ __align__(1024) uint8_t smem_raw[];
  const uint32_t sbase = smem_u32(smem_raw);
  const uint32_t s_bar = sbase + OFF_BAR;
  const int cluster_id = blockIdx.x >> 1;
  const bool isB = cluster_id >= NA_CL;
#define EARLY 1
  const int prob0 = isB ? 3 : cluster_id >> 4;
  const int ng0 = (isB ? (cluster_id - NA_CL) >> 3 : (cluster_id >> 3) & 1) * 4;
  const uint32_t t0 = clock();
  auto early = [&](int s) {
    const uint32_t full = s_bar + B_GFULL + 8 * s;
    mbar_expect_tx(full, 49152);
    tma_load_3d(sbase + OFF_A + s * 16384, &p.ta[prob0], 0, (blockIdx.x & 15) * 128, s, full, EV_NORMAL);
    tma_load_3d(sbase + s * TILE32K, &p.tb[prob0], 0, s * 64, ng0, full, EV_NORMAL);
    tma_load_3d(sbase + s * TILE32K + 16384, &p.tb[prob0], 0, s * 64, ng0 + 2, full, EV_NORMAL);
  };
  if ((threadIdx.x >> 5) == 8) {
    if (elect_one()) {
      mbar_init(s_bar + B_GFULL, 1);
      if (EARLY) early(0);
      for (int s = 1; s < 4; s++) mbar_init(s_bar + B_GFULL + 8 * s, 1);
      asm volatile("fence.mbarrier_init.release.cluster;" ::: "memory");
    }
    __syncwarp();
    named_bar_arrive(7, 288);
  }
  const int warp0 = __shfl_sync(0xffffffffu, threadIdx.x >> 5, 0);
  if (warp0 >= 8) reg_dealloc<REG_P>();
#define CLUSTER_ARRIVE() asm volatile("barrier.cluster.arrive.relaxed.aligned;" ::: "memory")
#define CLUSTER_WAIT() asm volatile("barrier.cluster.wait.acquire.aligned;" ::: "memory")

  if (warp0 >= 8) {
    if (warp0 == 10 && elect_one()) {
      if ((sbase & 0x3FFFFu) != DBASE) __trap();
      for (int s = 0; s < 4; s++) {
        mbar_init(s_bar + B_GEMPTY + 8 * s, 4);
        mbar_init(s_bar + B_SFULL + 8 * s, 4);
        mbar_init(s_bar + B_SFULL2 + 8 * s, 4);
        mbar_init(s_bar + B_SEMPTY + 8 * s, 1);
        mbar_init(s_bar + B_AFULL + 8 * s, 1);
        mbar_init(s_bar + B_AEMPTY + 8 * s, s == 1 && !isB ? 8 : 2);
      }
      for (int s = 0; s < 2; s++) {
        mbar_init(s_bar + B_QFULL + 8 * s, 1);
        mbar_init(s_bar + B_QEMPTY + 8 * s, 2);
      }
      mbar_init(s_bar + B_OFULL, 8);
      mbar_init(s_bar + B_STGFREE, 1);
      asm volatile("fence.mbarrier_init.release.cluster;" ::: "memory");
    }
    __syncwarp();
    CLUSTER_ARRIVE();
    if (EARLY && warp0 == 8 && elect_one()) {
#pragma unroll 1
      for (int s = 1; s < 4; s++) {
        while ((uint32_t)clock() - t0 < s * PACE) {}
        early(s);
      }
    }
    __syncwarp();
    CLUSTER_WAIT();
    const uint32_t rank = blockIdx.x & 1;
    if (warp0 == 8) {
      if (elect_one()) {
        TL_DECL;
        uint32_t gphase = 1 - EARLY;
        uint32_t tail = 0;
        int gi = 0;
        uint32_t rsel = rank, aswz = 0, lastq = 0, n = 0;
        for (int seg = 0; seg < 2; seg++) {
          for (;;) {
            uint32_t item = p.g[cluster_id][gi++];
            if (item == 0x500u) item = tail;
            if (item >= 0x600u) break;
            const int prob = item >> 8;
            const int rt = ((item >> 4) & 15) * 2 + rsel;
            const int ngrp0 = (item & 15) * 4;
            const int nkb4 = prob_nkb4(prob);
            const CUtensorMap* ta = &p.ta[prob];
            const CUtensorMap* tb = &p.tb[prob];
            TL(1, item);
            if (prob == 5) {
              uint32_t seen = 0;
              cnt_wait_bit(CNT_OB + (rt >> 2), 32u << (rt & 3) * 8, seen);
              fence_proxy_async_global();
            }
            for (int kb4 = EARLY && gi == 1; kb4 < nkb4; kb4++) {
              uint32_t seen = 0;
#pragma unroll 1
              for (int s = 0; s < 4; s++) {
                const int bs = s ^ (n & 1);
                if (prob == 4 && !(s & 1)) {
                  cnt_wait_bit(CNT_CTX + kb4, 16u << (s * 8), seen);
                  fence_proxy_async_global();
                }
                if (prob == 5 && kb4 == 0) {
                  mbar_wait(s_bar + B_AEMPTY + 8 * bs, (~(n + (s & 1)) >> 1) & 1);
                  if (s == 2) mbar_wait(s_bar + B_QEMPTY + (aswz ? 0 : 8), lastq);
                }
                mbar_wait(s_bar + B_GEMPTY + 8 * s, gphase);
                const uint32_t full = s_bar + B_GFULL + 8 * s;
                mbar_expect_tx(full, 49152);
                tma_load_3d(sbase + OFF_A + ((s * 16384) ^ aswz), ta, 0, rt * 128, kb4 * 4 + s, full, HINT(prob));
                if (prob == 5) {
                  tma_load_3d(sbase + bs * TILE32K, tb, 0, (kb4 * 4 + s) * 64, ngrp0, full, HINT(8 + prob));
                  tma_load_3d(sbase + bs * TILE32K + 16384, tb, 0, (kb4 * 4 + s) * 64, ngrp0 + 2, full, HINT(8 + prob));
                } else {
                  tma_load_3d_mc(sbase + s * TILE32K + rank * 16384, tb, 0, (kb4 * 4 + s) * 64, ngrp0 + rank * 2, full,
                                 (uint16_t)3, HINT(8 + prob));
                }
              }
              gphase ^= 1;
            }
          }
          if (seg == 0 && isB && DO_ATT) {
            int pv_row = 0, pv_col = 0;
            uint64_t pv_hint = 0;
#define ACQ_SLOT(slot, n)                                                              \
  {                                                                                    \
    if ((n) < 2) mbar_wait(s_bar + B_GEMPTY + 8 * (slot), gphase);                     \
    mbar_wait(s_bar + B_AEMPTY + 8 * (slot), (~(n) >> 1) & 1);                         \
  }
#define LOAD_V()                                                                       \
  {                                                                                    \
    const uint32_t vs = 3 - (n & 1);                                                   \
    ACQ_SLOT(vs, n - 1);                                                               \
    mbar_expect_tx(s_bar + B_AFULL + 8 * vs, TILE32K);                                 \
    tma_load_3d(sbase + vs * TILE32K, &p.tv, 0, pv_row, pv_col, s_bar + B_AFULL + 8 * vs, pv_hint); \
  }
#define NEXT_CODE() (nxt < 512 ? p.order[nxt] : nxt + (0x8000u - 512))
            uint32_t code = p.order[blockIdx.x - 2 * NA_CL];
            int it = 0;
            uint32_t seen = 0;
            for (;; it++) {
              if (it == 1) mbar_wait(s_bar + B_STGFREE, 0);
              if (code & 0x8000u) break;
              const int head = code >> 4;
              const int qt = code & 15;
              uint32_t nxt = 0;
              TL(1, 0x1000 | code);
              if (seen < 48) cnt_wait(CNT_QKV + (head >> 1), 48);
              fence_proxy_async_global();
              {
                const int b = it & 1;
                if (it < 2) {
                  mbar_wait(s_bar + B_GEMPTY + 16 * b, gphase);
                  mbar_wait(s_bar + B_GEMPTY + 16 * b + 8, gphase);
                }
                mbar_wait(s_bar + B_QEMPTY + 8 * b, ((it >> 1) & 1) ^ 1);
                mbar_expect_tx(s_bar + B_QFULL + 8 * b, TILE32K);
                tma_load_3d(sbase + OFF_A + b * TILE32K, &p.tq, 0, qt * 128, head * 2, s_bar + B_QFULL + 8 * b, HINT(24));
              }
#pragma unroll 1
              for (int t = qt; t >= 0; t--) {
                if (t == min(qt, 1)) nxt = cnt_next(CNT_QUEUE) + NB_CTA;
                if (t == 0) {
                  code = NEXT_CODE();
                  sts32(s_bar + S_CODE + 4 * ((it + 1) & 7), code);
                  seen = cnt_peek(CNT_QKV + ((code >> 5) & 15));
                }
                ACQ_SLOT(n & 1, n);
                mbar_expect_tx(s_bar + B_AFULL + 8 * (n & 1), TILE32K);
                tma_load_3d(sbase + (n & 1) * TILE32K, &p.tk, 0, t * 128, head * 2, s_bar + B_AFULL + 8 * (n & 1), HINT(t == qt ? 29 : 25));
                if (n) LOAD_V();
                n++;
                pv_row = t * 128;
                pv_col = head * 2;
                pv_hint = HINT(t == qt ? 29 : 26);
              }
            }
            ACQ_SLOT(n & 1, n);
            mbar_arrive(s_bar + B_AFULL + 8 * (n & 1));
            LOAD_V();
            tail = tail_item(code);
            aswz = (it & 1) * TILE32K;
            mbar_wait(s_bar + B_QEMPTY + 8 * (it & 1), ((it >> 1) & 1) ^ 1);
            rsel = (code >> 3) & 1;
            lastq = ((it - 1) >> 1) & 1;
          }
        }
        if (cnt_done(NCTA * 2)) cnt_rearm();
#pragma unroll 1
        for (int s = 0; s < 4; s++) mbar_wait(s_bar + B_GEMPTY + 8 * s, gphase);
        TL(1, 0xFFFF);
      }
    } else if (warp0 == 9) {
      if (elect_one()) {
        TL_DECL;
        uint32_t tail = 0;
        int gi = 0;
        uint32_t rsel = rank, aswz = 0;
        bool rearm = false;
        for (int seg = 0; seg < 2; seg++) {
          for (;;) {
            uint32_t item = p.g[cluster_id][gi++];
            if (item == 0x500u) item = tail;
            if (item >= 0x600u) break;
            const int prob = item >> 8;
            const int rt = ((item >> 4) & 15) * 2 + rsel;
            const int cg = (item & 15) * 4 + (prob == 5 ? 16 : 0);
            const CUtensorMap* tc = &p.tc[prob];
            const int nl = (p.g[cluster_id][gi] >> 8) == 4 && DO_LOCAL ? 8 : 1;
            const int grp = ((blockIdx.x >> 4) & 1) * 48 + (blockIdx.x & 15), r0 = (blockIdx.x >> 5) * 512;
            if (nl > 1) {
              cnt_wait(CNT_QKVB, 192);
              fence_proxy_async_global();
            }
            if (prob >= 4) rearm = cnt_done(NCTA * 2);
            const bool lastt = p.g[cluster_id][gi] >= 0x600u;
#pragma unroll 1
            for (int c = 0; c < 8; c++) {
              const int q = lastt ? c & 3 : c >> 1, w = lastt ? c >> 2 : c & 1;
              const int idx = w * 2 + (q & 1);
              const bool alt = lastt && q >= 2;
              mbar_wait(s_bar + (alt ? B_SFULL2 : B_SFULL) + 8 * idx, lastt ? seg : q >> 1);
              tma_store_3d(tc, sbase + (alt ? OFF_A + ((q * 16384) ^ aswz) + w * 8192 : OFF_STG + idx * 8192), 0,
                           rt * 128 + w * 64, cg + q, HINT(16 + prob));
              bulk_commit();
              if (c > 0 && !lastt) {
                bulk_wait_read<1>();
                mbar_arrive(s_bar + B_SEMPTY + 8 * ((w ^ 1) * 2 + (((c - 1) >> 1) & 1)));
              }
            }
            bulk_wait_read<0>();
            mbar_arrive(s_bar + (lastt ? B_STGFREE : B_SEMPTY + 8 * 3));
#pragma unroll 1
            for (int c = 0; c < nl; c++) {
              if (nl > 1) {
                mbar_wait(s_bar + B_AEMPTY, (c & 1) ^ 1);
                mbar_expect_tx(s_bar + B_AFULL, L_V);
                tma_load_3d(sbase + OFF_STG, &p.tl, 0, r0 + c * 64, grp, s_bar + B_AFULL, HINT(28));
                tma_load_3d(sbase + OFF_STG + L_K, &p.th, 0, r0 + c * 64 - 8, 16 + grp, s_bar + B_AFULL, HINT(28));
                mbar_wait(s_bar + B_AEMPTY + 8, (c & 1) ^ 1);
                mbar_expect_tx(s_bar + B_AFULL + 8, 9216);
                tma_load_3d(sbase + OFF_STG + L_V, &p.th, 0, r0 + c * 64 - 8, 32 + grp, s_bar + B_AFULL + 8, HINT(28));
              }
              if (c) {
                mbar_wait(s_bar + B_OFULL, ~c & 1);
                cnt_signal(CNT_OB + (blockIdx.x >> 5) * 2 + ((c - 1) >> 2), 1u << ((c - 1) & 3) * 8);
              } else if (prob < 4) {
                bulk_wait<0>();
                cnt_signal_done(prob == 3 ? CNT_QKVB : CNT_QKV + (item & 15));
                TL(2, item);
              }
            }
            if (nl > 1) {
              mbar_wait(s_bar + B_OFULL, 1);
              cnt_signal(CNT_OB + (blockIdx.x >> 5) * 2 + 1, 1u << 24);
              TL(2, 0x600);
            }
          }
          if (seg == 0 && isB && DO_ATT) {
            uint32_t code = p.order[blockIdx.x - 2 * NA_CL];
            for (int it = 0; !(code & 0x8000u); it++) {
              aswz = (~it & 1) * TILE32K;
              mbar_wait(s_bar + B_OFULL, it & 1);
              tma_store_3d(&p.to, sbase + OFF_STG, 0, (code & 15) * 128, (code >> 4) * 2, HINT(27));
              bulk_commit();
              const uint32_t nxt = lds32(s_bar + S_CODE + 4 * ((it + 1) & 7));
              bulk_wait_read<0>();
              mbar_arrive(s_bar + B_STGFREE);
              bulk_wait<0>();
              cnt_signal_done(CNT_CTX + (code >> 5), 1u << (code & 16));
              TL(2, 0x1000 | code);
              code = nxt;
            }
            tail = tail_item(code);
            rsel = (code >> 3) & 1;
            if (tail == 0xFFFFu) rearm = cnt_done(NCTA * 2);
          }
        }
        if (rearm) cnt_rearm();
        TL(2, 0xFFFF);
      }
    }
  } else {
    CLUSTER_ARRIVE();
    reg_alloc<REG_C>();
    named_bar_sync(7, 288);
    const int warp = __shfl_sync(0xffffffffu, opaque_tid() >> 5, 0);
    const int wg = warp >> 2;
    const int lane = threadIdx.x & 31;
    TL_DECL;
    TR_DECL;
    uint32_t gphase = 0;
    uint32_t tail = 0, aswz = 0, rot = 0, etgt = warp & 1, stgpar = 1;
    int gi = 0;
    for (int seg = 0; seg < 2; seg++) {
      uint32_t item = p.g[cluster_id][gi++];
      if (item == 0x500u) item = tail;
      if (item < 0x600u) {
        float acc[128];
        uint32_t pk[64];
        int have = 0;
#define G_STORE_CHUNK(q)                                                                               \
  {                                                                                                    \
    const uint32_t st_base = sbase + OFF_STG + wg * 8192 + stg_off(opaque_tid());                      \
    if (have == 2) { _Pragma("unroll") for (int j = 0; j < 16; j++) pk[(q) * 16 + j] = scale_q(pk[(q) * 16 + j]); } \
    mbar_wait(s_bar + B_SEMPTY + 8 * (wg * 2 + ((q) & 1)), (((q) >> 1) & 1) ^ 1);                      \
    _Pragma("unroll") for (int j = 0; j < 4; j++)                                                      \
        stmatrix_x4((st_base ^ (j << 5)) + ((q) & 1) * 8192, pk[(q) * 16 + j * 4],                     \
                    pk[(q) * 16 + j * 4 + 1], pk[(q) * 16 + j * 4 + 2], pk[(q) * 16 + j * 4 + 3]);     \
    fence_proxy_async_smem();                                                                          \
    __syncwarp();                                                                                      \
    mbar_arrive_elect(s_bar + B_SFULL + 8 * (wg * 2 + ((q) & 1)), true);                              \
  }
#define G_STAGE(s) G_STAGE_Y(s, false, false, )
#define G_STAGE_X(s, ...) G_STAGE_Y(s, false, false, __VA_ARGS__)
#define G_STAGE_Y(s, first, last, ...)                                                                    \
  {                                                                                                       \
    mbar_wait_rest(s_bar + B_GFULL + 8 * (s), gphase, gok && (first));                                    \
    TR(9);                                                                                                \
    const uint32_t da = make_desc(DBASE + OFF_A + (((s) * 16384) ^ aswz) + wg * 8192, 16);                \
    const uint32_t db = make_desc(DBASE + ((s) ^ rot) * TILE32K, 8192);                                   \
    named_bar_sync_if(5 + wg, 256, !(first));                                                             \
    wgmma_fence();                                                                                        \
    _Pragma("unroll") for (int k = 0; k < 5; k++) {                                                       \
      __VA_ARGS__;                                                                                        \
      if (k == 0) wgmma_ss_n256_tbo<0, 0>(acc, da, db, !(first));                                         \
      if (k == 1) wgmma_ss_n256_tbo<2, 128>(acc, da, db, 1);                                              \
      if (k == 2) wgmma_ss_n256_tbo<4, 256>(acc, da, db, 1);                                              \
      if (k == 3) wgmma_ss_n256_tbo<6, 384>(acc, da, db, 1);                                              \
    }                                                                                                     \
    wgmma_commit();                                                                                       \
    named_bar_arrive_if(6 - wg, 256, !(wg ? (last) : (first)));                                           \
    if (!(first)) {                                                                                       \
      wgmma_wait<1>();                                                                                    \
      mbar_arrive_cluster_if(s_bar + B_GEMPTY + 8 * (((s) + 3) & 3), etgt, lane == 0 && (warp & 3) < 2);  \
    }                                                                                                     \
  }
        TL0(item);
        undef_regs(acc);
        {
          constexpr bool gok = false;
          G_STAGE_Y(0, true, false, )
        }
        if (seg == 0) CLUSTER_WAIT();
        undef_regs(pk);
        for (;;) {
          constexpr bool gok = false;
          const int nkb4 = prob_nkb4(item >> 8);
          const uint32_t next = p.g[cluster_id][gi++];
          G_STAGE(1)
          if (have) G_STORE_CHUNK(0)
          G_STAGE(2)
          G_STAGE(3)
          if (have) G_STORE_CHUNK(1)
          gphase ^= 1;
          G_STAGE(0)
          G_STAGE(1)
          if (have) G_STORE_CHUNK(2)
          G_STAGE(2)
          if (have) G_STORE_CHUNK(3)
          G_STAGE_Y(3, false, nkb4 == 2, )
          gphase ^= 1;
          int kb4 = 2;
          if (nkb4 == 16 && DO_LOCAL) {
            constexpr uint32_t aswz = 0, rot = 0;
            G_STAGE(0)
            G_STAGE(1)
            for (; kb4 < 10; kb4++) {
              float ls[36];
              TR(10);
              mbar_wait(s_bar + B_AFULL, kb4 & 1);
              TR(11);
              {
                const uint32_t dq = make_desc(DBASE + OFF_STG + wg * 64, 16);
                G_STAGE_X(2, if (k == 1) wgmma_ss_n72_init(ls, dq, dq + L_K / 16); if (k == 3) wgmma_ss_n72(ls, dq + 2, dq + L_K / 16 + 2, 1))
              }
              mbar_wait(s_bar + B_AFULL + 8, kb4 & 1);
              const int tid = opaque_tid();
              uint32_t vw[16];
              uint4 pw[8];
              {
                const uint32_t va = sbase + OFF_STG + L_V + ((tid >> 4) & 7) * 1024 + wg * 64 + (tid & 15) * 4;
#pragma unroll
                for (int j = 1; j < 16; j++) vw[j] = lds32((va ^ ((j & 7) << 4)) + j * 128);
              }
              G_STAGE(3)
              gphase ^= 1;
              fence_regs(ls);
              mbar_arrive_if(s_bar + B_AEMPTY, (threadIdx.x & 127) == 0);
              {
                const int d = (tid & 3) * 2 - ((tid >> 2) & 7);
                const bool p0 = d > 0, p1 = d >= 0;
                const int w = warp & 3;
                float x0, x1, y0, y1;
#define L_PICK(w_)                                   \
  {                                                  \
    x0 = p0 ? ls[8 * (w_)] : ls[8 * (w_) + 4];       \
    x1 = p1 ? ls[8 * (w_) + 1] : ls[8 * (w_) + 5];   \
    y0 = p0 ? ls[8 * (w_) + 6] : ls[8 * (w_) + 10];  \
    y1 = p1 ? ls[8 * (w_) + 7] : ls[8 * (w_) + 11];  \
  }
                if (w == 0) {
                  if (kb4 == 2 && blockIdx.x < 32) ls[0] = ls[1] = -INFINITY;
                  L_PICK(0)
                } else if (w == 1) L_PICK(1)
                else if (w == 2) L_PICK(2)
                else L_PICK(3)
                constexpr float C = 0.17677669529663687f * 1.4426950408889634f;
                float mx = fmaxf(x0, x1), my = fmaxf(y0, y1);
                mx = fmaxf(mx, __shfl_xor_sync(0xffffffffu, mx, 1));
                my = fmaxf(my, __shfl_xor_sync(0xffffffffu, my, 1));
                mx = -C * fmaxf(mx, __shfl_xor_sync(0xffffffffu, mx, 2));
                my = -C * fmaxf(my, __shfl_xor_sync(0xffffffffu, my, 2));
                x0 = ex2(fmaf(x0, C, mx));
                x1 = ex2(fmaf(x1, C, mx));
                y0 = ex2(fmaf(y0, C, my));
                y1 = ex2(fmaf(y1, C, my));
                float sx = x0 + x1, sy = y0 + y1;
                sx += __shfl_xor_sync(0xffffffffu, sx, 1);
                sy += __shfl_xor_sync(0xffffffffu, sy, 1);
                sx += __shfl_xor_sync(0xffffffffu, sx, 2);
                sy += __shfl_xor_sync(0xffffffffu, sy, 2);
                sx = rcp(sx);
                sy = rcp(sy);
                const uint32_t pa = sbase + OFF_STG + L_P + (tid >> 5) * 512 + (tid & 31) * 8;
                sts64(pa, x0 * sx, x1 * sx);
                sts64(pa + 256, y0 * sy, y1 * sy);
                __syncwarp();
              }
              const uint32_t pr = sbase + OFF_STG + L_P + (tid >> 4) * 256;
              uint32_t* dst = reinterpret_cast<uint32_t*>(p.ob) + (blockIdx.x & 15) * 32 + wg * 16 + (tid & 15) +
                              (((blockIdx.x >> 5) * 512 + (kb4 - 2) * 64 + ((tid >> 4) & 7) * 8) * 2 + ((blockIdx.x >> 4) & 1)) * 512;
#define L_PV(g0)                                                                                       \
  _Pragma("unroll") for (int g = (g0); g < (g0) + 4; g++) {                                            \
    const uint4 a = pw[2 * (g & 3)], b = pw[2 * (g & 3) + 1];                                          \
    const uint32_t w[8] = {a.x, a.y, a.z, a.w, b.x, b.y, b.z, b.w};                                    \
    float o0 = 0.f, o1 = 0.f;                                                                          \
    _Pragma("unroll") for (int c = 0; c < 8; c++) {                                                    \
      const uint32_t u = vw[c > g ? c : c + 8];                                                        \
      o0 = fmaf(__uint_as_float(w[c]), __uint_as_float(u << 16), o0);                                  \
      o1 = fmaf(__uint_as_float(w[c]), __uint_as_float(u & 0xFFFF0000u), o1);                          \
    }                                                                                                  \
    dst[g * 1024] = pack_bf16(o0, o1);                                                                 \
  }
#pragma unroll
              for (int j = 0; j < 8; j++) pw[j] = lds128(pr + j * 16);
              mbar_arrive_elect(s_bar + B_AEMPTY + 8, true);
              G_STAGE(0)
              L_PV(0)
#pragma unroll
              for (int j = 0; j < 8; j++) pw[j] = lds128(pr + 128 + j * 16);
              G_STAGE(1)
              L_PV(4)
              __syncwarp();
              mbar_arrive_elect(s_bar + B_OFULL, true);
            }
            G_STAGE(2)
            G_STAGE(3)
            gphase ^= 1;
            kb4++;
          }
          const bool fin = next >= 0x600u;
          for (; kb4 < nkb4 - fin; kb4++) {
            G_STAGE(0)
            G_STAGE(1)
            G_STAGE(2)
            G_STAGE_Y(3, false, kb4 + 1 == nkb4, )
            gphase ^= 1;
          }
          if (fin) break;
          wgmma_wait<0>();
          mbar_arrive_cluster_if(s_bar + B_GEMPTY + 8 * 3, etgt, lane == 0 && (warp & 3) < 2);
          {
            const bool gok = mbar_test(s_bar + B_GFULL, gphase);
            fence_regs(acc);
#pragma unroll
            for (int j = 0; j < 64; j++) pk[j] = pack_bf16(acc[2 * j], acc[2 * j + 1]);
            have = item < 0x100u ? 2 : 1;
            item = next;
            TL0(item);
            G_STAGE_Y(0, true, false, )
          }
        }
        {
          constexpr bool gok = false;
          G_STAGE(0)
          G_STAGE(1)
          wgmma_wait<0>();
          mbar_arrive_cluster_if(s_bar + B_GEMPTY + 8 * (FS - 1), etgt, lane == 0 && (warp & 3) < 2);
          fence_regs(acc);
          float lo[64], hi[64];
#pragma unroll
          for (int j = 0; j < 64; j++) {
            asm volatile("mov.b32 %0, %1;" : "=f"(lo[j]) : "f"(acc[j]));
            asm volatile("mov.b32 %0, %1;" : "=f"(hi[j]) : "f"(acc[64 + j]));
          }
#pragma unroll
          for (int s = FS; s < 4; s++) {
            mbar_wait(s_bar + B_GFULL + 8 * s, gphase);
            const uint32_t da = make_desc(DBASE + OFF_A + ((s * 16384) ^ aswz) + wg * 8192, 16);
            const uint32_t db = make_desc(DBASE + (s ^ rot) * TILE32K, 8192);
            if (s == FS) named_bar_sync(5 + wg, 256);
            wgmma_fence();
            wgmma_ss_n128_tb<0, 0>(lo, da, db, 1);
            wgmma_ss_n128_tb<2, 128>(lo, da, db, 1);
            wgmma_ss_n128_tb<4, 256>(lo, da, db, 1);
            wgmma_ss_n128_tb<6, 384>(lo, da, db, 1);
            wgmma_commit();
          }
          wgmma_fence();
#pragma unroll
          for (int s = FS; s < 4; s++) {
            const uint32_t da = make_desc(DBASE + OFF_A + ((s * 16384) ^ aswz) + wg * 8192, 16);
            const uint32_t db = make_desc(DBASE + (s ^ rot) * TILE32K, 8192);
            wgmma_ss_n128_tb<0, 1024>(hi, da, db, 1);
            wgmma_ss_n128_tb<2, 1152>(hi, da, db, 1);
            wgmma_ss_n128_tb<4, 1280>(hi, da, db, 1);
            wgmma_ss_n128_tb<6, 1408>(hi, da, db, 1);
          }
          wgmma_commit();
          named_bar_arrive_if(6, 256, wg == 0);
          gphase ^= 1;
          const uint32_t so = sbase + stg_off(opaque_tid());
          mbar_wait(s_bar + B_STGFREE, stgpar);
          mbar_wait(s_bar + B_SEMPTY + 16 * wg, 1);
          mbar_wait(s_bar + B_SEMPTY + 16 * wg + 8, 1);
#define FIN_HALF(x, base, stride, bar)                                                                                \
  fence_regs(x);                                                                                                      \
  _Pragma("unroll") for (int j = 0; j < 8; j++)                                                                       \
      stmatrix_x4(((base) ^ ((j & 3) << 5)) + (j >> 2) * (stride), pack_bf16(x[8 * j], x[8 * j + 1]),                 \
                  pack_bf16(x[8 * j + 2], x[8 * j + 3]), pack_bf16(x[8 * j + 4], x[8 * j + 5]), pack_bf16(x[8 * j + 6], x[8 * j + 7])); \
  fence_proxy_async_smem();                                                                                           \
  __syncwarp();                                                                                                       \
  mbar_arrive_elect(s_bar + (bar) + 16 * wg, true);                                                                   \
  mbar_arrive_elect(s_bar + (bar) + 16 * wg + 8, true);
          wgmma_wait<1>();
          FIN_HALF(lo, so + OFF_STG + wg * 8192, 8192, B_SFULL)
          wgmma_wait<0>();
          TRI(12, 8);
#pragma unroll
          for (int s = FS; s < 4; s++) mbar_arrive_cluster_if(s_bar + B_GEMPTY + 8 * s, etgt, lane == 0 && (warp & 3) < 2);
          FIN_HALF(hi, so + OFF_A + (32768 ^ aswz), 16384, B_SFULL2)
          TRI(12, 10);
        }
      }
      if (seg == 0 && isB && DO_ATT) {
        float o[64], s[64];
        uint32_t pa[32], pb[32];
        undef_regs(o);
        undef_regs(s);
        undef_regs(pa);
        undef_regs(pb);
        uint32_t phase = 0;
        const bool sig = (threadIdx.x & 127) == 0;
        if (wg == 1) named_bar_arrive(1, 256);

#define ISSUE_PV(pr, slot_)                                                             \
  {                                                                                     \
    const uint32_t dv = make_desc(DBASE + (slot_) * TILE32K, 16384);                    \
    if (!(pfirst && wg == HW)) {                                                        \
      wgmma_fence();                                                                    \
      _Pragma("unroll") for (int k = 0; k < 8; k++)                                     \
          wgmma_rs_n128_tb(o, pr[4 * k], pr[4 * k + 1], pr[4 * k + 2], pr[4 * k + 3], dv + k * 128, (k != 0) || !pfirst); \
      wgmma_commit();                                                                   \
    } else {                                                                            \
      wgmma_fence();                                                                    \
      _Pragma("unroll") for (int k = 0; k < 4; k++)                                     \
          wgmma_rs_n128_tb(o, pr[16 + 4 * k], pr[17 + 4 * k], pr[18 + 4 * k], pr[19 + 4 * k], dv + k * 128, k != 0); \
      wgmma_commit();                                                                   \
    }                                                                                   \
  }
#define EPILOGUE(on_)                                                                             \
  _Pragma("unroll") for (int j = 0; j < 8; j++) {                                                 \
    const int b = j * 8;                                                                          \
    stmatrix_x4_p((st_o ^ ((j & 3) << 5)) + (j >> 2) * 16384,                                     \
                  pack_bf16(o[b] * sc0, o[b + 1] * sc0), pack_bf16(o[b + 2] * sc1, o[b + 3] * sc1),   \
                  pack_bf16(o[b + 4] * sc0, o[b + 5] * sc0), pack_bf16(o[b + 6] * sc1, o[b + 7] * sc1), on_); \
  }
#define PUBLISH_O()                                  \
  {                                                  \
    fence_proxy_async_smem();                        \
    __syncwarp();                                    \
    mbar_arrive_elect(s_bar + B_OFULL, true);        \
  }
#define FINAL_SCALE()     \
  {                                                    \
    sc0 += __shfl_xor_sync(0xffffffffu, sc0, 1);       \
    sc1 += __shfl_xor_sync(0xffffffffu, sc1, 1);       \
    sc0 += __shfl_xor_sync(0xffffffffu, sc0, 2);       \
    sc1 += __shfl_xor_sync(0xffffffffu, sc1, 2);       \
    sc0 = rcp(sc0);            \
    sc1 = rcp(sc1);                                    \
  }
        float l0 = 1.f, l1 = 1.f, t0 = 1.f, t1 = 1.f;
        float b0 = 0.f, b1 = 0.f, sc0 = 0.f, sc1 = 0.f;
        int gen = 0;
        int pfirst = 1;
        int fresh = 1;
        int opub = 0;
        int last = 0;
        float rdy = -0.f;
        float x0 = 0.f, x1 = 0.f, x2 = 0.f, x3 = 0.f;
        bool rs = false;
        uint32_t code = p.order[blockIdx.x - 2 * NA_CL];
        int it = -1, nit = 0, rem = -1;
        const float mrow = float((warp & 3) * 16 + (lane >> 2) - (lane & 3) * 2);
        const float lo0 = mrow < 0.f && wg == HW ? 0.f : SM_LO;
        const uint32_t st_o = sbase + OFF_STG + stg_off(opaque_tid() ^ (HW * 128));
#define MMA_PART(N_, acc_, PIN, PAR)                                                                       \
  {                                                                                                        \
    const uint32_t dq = make_desc(DBASE + OFF_A + (it & 1) * TILE32K + (wg ^ HW) * 8192, 16);              \
    const uint32_t dk = make_desc(DBASE + (PAR) * TILE32K, 16);                                            \
    TRI(0, fresh ? 7 : 0);                                                                                 \
    named_bar_sync(1 + wg, 256);                                                                           \
    TRI(1, fresh ? 6 : 1);                                                                                 \
    wgmma_fence();                                                                                         \
    uint32_t cv;                                                                                           \
    bool rv;                                                                                               \
    _Pragma("unroll") for (int k = 0; k < 8; k++) {                                                        \
      wgmma_ss_n##N_(acc_, dq + (k >> 2) * 1024 + (k & 3) * 2, dk + (k >> 2) * 1024 + (k & 3) * 2, k != 0 || gen); \
      if (k == 1) cv = lds32(s_bar + S_CODE + 4 * ((it + 1) & 7));        \
      if (k == 3) rv = mbar_test(s_bar + B_AFULL + 8 * (3 - (PAR)), phase ^ (1 - (PAR)));                  \
    }                                                                                                      \
    wgmma_commit();                                                                                        \
    code = __reduce_or_sync(0xffffffffu, cv);                                                              \
    if (N_ == 128 && opub) PUBLISH_O();                                                                    \
    if (N_ == 128 && fresh) FINAL_SCALE();                                                                 \
    last = rem == 0 && (code & 0x8000u);                                                                   \
    nit = it + (rem == 0 && !last);                                                                        \
    mbar_wait_rest(s_bar + B_AFULL + 8 * (3 - (PAR)), phase ^ (1 - (PAR)), rv);                            \
    ISSUE_PV(PIN, 3 - (PAR));                                                                              \
    named_bar_arrive(2 - wg, 256);                                                                         \
    TR(2);                                                                                                 \
    wgmma_wait<1>();                                                                                       \
    fence_regs(acc_);                                                                                      \
    TR(3);                                                                                                 \
    mbar_arrive_if(s_bar + B_AEMPTY + 8 * (PAR), sig);                                                     \
    mbar_arrive_if(s_bar + B_QEMPTY + 8 * (it & 1), sig && rem == 0);                                      \
    rs = mbar_test(s_bar + B_STGFREE, ~it & 1) | (it == 0);                                                \
    l0 = t0;                                                                                               \
    l1 = t1;                                                                                               \
  }
#define LOW_SUM() ((t0 < lo0) | (t1 < SM_LO))
#define SECOND_HALF(POUT, PAR, FRESH, ...)                                                                 \
  wgmma_wait<0>();                                                                                         \
  fence_regs(o);                                                                                           \
  mbar_arrive_if(s_bar + B_AEMPTY + 8 * (3 - (PAR)), sig && ((PAR) || !(FRESH) || it > 0));                \
  rdy = mbar_test2(s_bar + B_AFULL + 8 * (1 - (PAR)), phase ^ (PAR), s_bar + B_QFULL + 8 * (nit & 1), (nit >> 1) & 1); \
  TR(8);                                                                                                   \
  __VA_ARGS__;                                                                                             \
  t0 += x0 + x1;                                                                                           \
  t1 += x2 + x3;                                                                                           \
  POUT[16] = pack_bf16(x0, x1);                                                                            \
  POUT[17] = pack_bf16(x2, x3);                                                                            \
  softmax_exp<9, TPOS, false>(s, 0.f, 0.f, POUT, t0, t1);                                                  \
  t0 = addv(t0, rdy);                                                                                      \
  softmax_exp<TPOS, 16, false>(s, 0.f, 0.f, POUT, t0, t1);                                                 \
  opub = (FRESH) && it > 0 && wg != HW;                                                                    \
  pfirst = FRESH;                                                                                          \
  fresh = 0;                                                                                               \
  rem--;                                                                                                   \
  if (PAR) phase ^= 1;                                                                                     \
                                              \
  const float lim = __uint_as_float(__float_as_uint(rem < 0 || gen ? -1.f : SM_HI) | __float_as_uint(rdy)); \
  TR(4);
#define TPOS 14
#define STEP_END(POUT, PAR, NEXT, ...)                                                                     \
  if (fresh) {                                                                                             \
    __VA_ARGS__;                                                                                           \
    mbar_wait_rest(s_bar + B_STGFREE, ~it & 1, rs);                                                        \
    SECOND_HALF(POUT, PAR, 1, EPILOGUE(it > 0))                                                            \
    const bool nx = __any_sync(0xffffffffu, !(t0 + t1 <= lim) | LOW_SUM());                               \
    if (wg == HW && it > 0) PUBLISH_O();                                     \
    if (!nx) goto plain##NEXT;                                                                             \
  } else {                                                                                                 \
    SECOND_HALF(POUT, PAR, 0, )                                                                            \
    if (!__any_sync(0xffffffffu, !(t0 + t1 <= lim))) goto plain##NEXT;                                     \
  }
#define STEP_BEGIN(PIN, POUT, PAR, ...)                                                                    \
  {                                                                                                        \
    if (__any_sync(0xffffffffu, !(t0 + t1 <= SM_HI) | (LOW_SUM() & (pfirst != 0)))) {                           \
              \
      if (pfirst && wg == HW) { _Pragma("unroll") for (int j = 0; j < 32; j++) asm volatile("mov.b32 %0, 0xff800000;" : "=f"(s[j])); } \
      float d0, d1;                                                                                        \
      softmax_max(s, d0, d1);                                                                              \
      if (!pfirst) {                                                                                       \
        d0 = fmaxf(d0, 0.f);                                                                               \
        d1 = fmaxf(d1, 0.f);                                                                               \
      }                                                                                                    \
      const float r0 = pfirst ? 1.f : ex2(-d0), r1 = pfirst ? 1.f : ex2(-d1);                              \
      t0 = l0 * r0;                                                                                        \
      t1 = l1 * r1;                                                                                        \
      softmax_exp<0, 16, true>(s, -d0, -d1, PIN, t0, t1);                                                  \
      b0 -= d0;                                                                                            \
      b1 -= d1;                                                                                            \
      gen = 1;                                                                                             \
      _Pragma("unroll") for (int j = 0; j < 16; j++) {                                                     \
        o[4 * j] *= r0;                                                                                    \
        o[4 * j + 1] *= r0;                                                                                \
        o[4 * j + 2] *= r1;                                                                                \
        o[4 * j + 3] *= r1;                                                                                \
      }                                                                                                    \
    }                                                                                                      \
    if (last) {                                                                                            \
      __VA_ARGS__;                                                                                         \
      break;                                                                                               \
    }                                                                                                      \
    fresh = rem < 0;                                                                                       \
    it = nit;                                                                                              \
    if (fresh) {                                                                                           \
      TL0(0x1000 | code);                                                                                  \
      rem = code & 15;                                                                                     \
      sc0 = t0;                                                                                            \
      sc1 = t1;                                                                                            \
      t0 = t1 = 0.f;                                                                                       \
    }                                                                                                      \
    if (gen) {                                                      \
      _Pragma("unroll") for (int j = 0; j < 64; j++) asm volatile("mov.b32 %0, %1;" : "=f"(s[j]) : "f"((j & 2) ? b1 : b0)); \
    }                                                                                                      \
    mbar_wait_rest(s_bar + B_AFULL + 8 * (PAR), phase, __float_as_uint(rdy) == 0);                         \
    mbar_wait_rest(s_bar + B_QFULL + 8 * (it & 1), (it >> 1) & 1, __float_as_uint(rdy) == 0);              \
  }                                                                                                        \
  if (fresh && wg == HW) {                                                                                 \
                                                     \
    float sl[32];                                                                                          \
    _Pragma("unroll") for (int j = 0; j < 32; j++) asm volatile("mov.b32 %0, %1;" : "=f"(sl[j]) : "f"(s[32 + j])); \
    MMA_PART(64, sl, PIN, PAR)                                                                             \
    _Pragma("unroll") for (int j = 0; j < 32; j++) asm volatile("mov.b32 %0, %1;" : "=f"(s[32 + j]) : "f"(sl[j])); \
    FINAL_SCALE();                                                                                         \
    _Pragma("unroll") for (int j = 0; j < 8; j++) {                                                        \
      if (float(8 * j) > mrow) s[32 + 4 * j] = -3e38f;                                                     \
      if (float(8 * j + 1) > mrow) s[33 + 4 * j] = -3e38f;                                                 \
      if (float(8 * j - 8) > mrow) s[34 + 4 * j] = -3e38f;                                                 \
      if (float(8 * j - 7) > mrow) s[35 + 4 * j] = -3e38f;                                                 \
    }                                                                                                      \
    x0 = ex2v(s[32]), x1 = ex2v(s[33]), x2 = ex2v(s[34]), x3 = ex2v(s[35]);                                \
  } else {                                                                                                 \
  plain##PAR:                                                                                              \
    MMA_PART(128, s, PIN, PAR)                                                                             \
    if (fresh) {                                                                                           \
                                     \
      _Pragma("unroll") for (int j = 0; j < 8; j++) {                                                      \
        s[32 + 4 * j] = fmaf(__saturatef(float(8 * j) - mrow), -3e38f, s[32 + 4 * j]);                     \
        s[33 + 4 * j] = fmaf(__saturatef(float(8 * j + 1) - mrow), -3e38f, s[33 + 4 * j]);                 \
        s[34 + 4 * j] = fmaf(__saturatef(float(8 * j - 8) - mrow), -3e38f, s[34 + 4 * j]);                 \
        s[35 + 4 * j] = fmaf(__saturatef(float(8 * j - 7) - mrow), -3e38f, s[35 + 4 * j]);                 \
      }                                                                                                    \
      softmax_exp<0, 8, false>(s, 0.f, 0.f, POUT, t0, t1);                                                 \
      x0 = ex2v(s[32]), x1 = ex2v(s[33]), x2 = ex2v(s[34]), x3 = ex2v(s[35]);                              \
    } else {                                                                                               \
      softmax_exp<0, 8, false>(s, 0.f, 0.f, POUT, t0, t1);                                                 \
      x0 = ex2v(s[32]), x1 = ex2v(s[33]), x2 = ex2v(s[34]), x3 = ex2v(s[35]);                              \
    }                                                                                                      \
  }
        for (;;) {
          STEP_END(pa, 1, 0, if (it < 0) { wgmma_wait<0>(); goto begin0; })
        begin0:
          STEP_BEGIN(pa, pb, 0, rot = 0; phase ^= 1)
          STEP_END(pb, 0, 1, )
          STEP_BEGIN(pb, pa, 1, rot = 1; _Pragma("unroll") for (int j = 0; j < 32; j++) asm volatile("mov.b32 %0, %1;" : "=r"(pa[j]) : "r"(pb[j])))
        }
        {
          mbar_wait(s_bar + B_AFULL + 8 * (3 - rot), phase);
          TRI(12, 2);
          ISSUE_PV(pa, 3 - rot);
          if (opub) PUBLISH_O();
          sc0 = t0;
          sc1 = t1;
          FINAL_SCALE();
          mbar_wait(s_bar + B_STGFREE, it & 1);
          wgmma_wait<0>();
          fence_regs(o);
          TRI(12, 4);
          mbar_arrive_if(s_bar + B_AEMPTY + 8 * (3 - rot), sig);
          EPILOGUE(true);
          PUBLISH_O();
          TRI(12, 5);
          stgpar = ~it & 1;
          tail = tail_item(code);
          aswz = (~it & 1) * TILE32K;
          etgt = blockIdx.x & 1;
        }
      }
    }
    TL0(0xFFFF);
    TRI(15, 15);
  }
}

typedef CUresult (*EncodeFn)(CUtensorMap*, CUtensorMapDataType, cuuint32_t, void*, const cuuint64_t*,
                             const cuuint64_t*, const cuuint32_t*, const cuuint32_t*, CUtensorMapInterleave,
                             CUtensorMapSwizzle, CUtensorMapL2promotion, CUtensorMapFloatOOBfill);

EncodeFn get_encode() {
  static EncodeFn fn = nullptr;
  if (!fn) {
    void* p = nullptr;
    cudaDriverEntryPointQueryResult st;
    cudaGetDriverEntryPoint("cuTensorMapEncodeTiled", &p, cudaEnableDefault, &st);
    fn = (EncodeFn)p;
  }
  return fn;
}

void make_map(CUtensorMap* m, const void* ptr, int rows, int cols, int box_rows, int box_groups,
              CUtensorMapSwizzle swz = CU_TENSOR_MAP_SWIZZLE_128B) {
  cuuint64_t dims[3] = {64, (cuuint64_t)rows, (cuuint64_t)(cols / 64)};
  cuuint64_t strides[2] = {(cuuint64_t)cols * 2, 128};
  cuuint32_t box[3] = {64, (cuuint32_t)box_rows, (cuuint32_t)box_groups};
  cuuint32_t es[3] = {1, 1, 1};
  CUtensorMapL2promotion prom = box_groups == 1 ? CU_TENSOR_MAP_L2_PROMOTION_NONE : CU_TENSOR_MAP_L2_PROMOTION_L2_256B;
  get_encode()(m, CU_TENSOR_MAP_DATA_TYPE_BFLOAT16, 3, const_cast<void*>(ptr), dims, strides, box, es,
               CU_TENSOR_MAP_INTERLEAVE_NONE, swz, prom,
               CU_TENSOR_MAP_FLOAT_OOB_FILL_NONE);
}

#define PARAM(name, val) const int name = val
void build_schedule(Params& p) {
  PARAM(C_KB, 1028);
  PARAM(C_TILE, 10);
  PARAM(C_QX, 0);
  PARAM(C_START, 4500);
  PARAM(C_STEP, 2052);
  PARAM(C_ITEM, 300);
  PARAM(C_LAG, 8000);
  PARAM(C_SP, 5200);
  PARAM(C_TAIL, 22000);
  PARAM(C_SHORT, 0);
  PARAM(C_AT, 72);
  PARAM(C_LATE, 0);
  PARAM(C_LMASK, 0xAA0);
  PARAM(C_AM, 100);
  PARAM(C_ODD, 1300);
  PARAM(C_READY, 10000);
  auto gemm_cost = [&](int prob) {
    static const int nkb[NPROB] = {16, 8, 8, 16, 64, 16};
    return nkb[prob] * C_KB + C_TILE + (prob == 0 ? C_QX : 0);
  };
  memset(p.g, 0xFF, sizeof(p.g));
  int n1[NCLUSTER];
  long t1[NCLUSTER];
  long ready[16];
  for (int c = 0; c < NCLUSTER; c++) { n1[c] = 0; t1[c] = C_START; }
  for (int i = 0; i < 16; i++) ready[i] = 0;
  auto add = [&](int c, int prob, int mp, int nt) {
    p.g[c][n1[c]++] = (uint16_t)((prob << 8) | (mp << 4) | nt);
    t1[c] += gemm_cost(prob);
    if (prob < 3) {
      const long r = t1[c] + C_READY;
      if (r > ready[nt]) ready[nt] = r;
    }
  };
  for (int r = 0; r < 8; r++)
    for (int c = 0; c < NA_CL; c++) {
      const int mp = c & 7, nt = 2 * r + ((c >> 3) & 1);
      for (int j = 0; j < (c < 16 ? 1 : 2); j++) {
        add(c, c < 16 ? 0 : 1 + j, mp, nt);
      }
    }
  long tA = 0;
  for (int c = 0; c < NA_CL; c++) {
    if (t1[c] > tA) tA = t1[c];
    add(c, 4, c & 7, c >> 3);
  }
  for (int i = 0; i < 96; i++) add(NA_CL + i % (NCLUSTER - NA_CL), 3, i % 8, i / 8);
  for (int c = NA_CL; c < NCLUSTER; c++) {
    p.g[c][n1[c]++] = 0x600;
    p.g[c][n1[c]++] = 0x500;
  }
  long tf[NB_CTA];
  bool done[512], started[NB_CTA];
  long fin[16];
  for (int c = 0; c < NB_CTA; c++) { tf[c] = t1[NA_CL + (c >> 1)] + 2000; started[c] = false; }
  for (int i = 0; i < 512; i++) done[i] = false;
  for (int i = 0; i < 16; i++) fin[i] = 0;
  auto alen = [&](int qt) { return (long)(qt + 1) * C_STEP + C_ITEM + (qt < 2 ? C_SHORT : 0); };
  int nq = NB_CTA;
  for (int n = 0; n < 512; n++) {
    int cb = 0;
    for (int c = 1; c < NB_CTA; c++)
      if (tf[c] < tf[cb]) cb = c;
    int best = -1;
    long bkey = 0;
    for (int i = 0; i < 512; i++) {
      if (done[i]) continue;
      const int hp = i >> 5;
      long dl = -(long)(16 - hp) * C_SP - C_LAG + ((i >> 4) & 1) * C_ODD;
      if (dl > -C_TAIL) dl = -C_TAIL;
      long key = dl - alen(i & 15) * (dl == -C_TAIL ? C_AT : C_AM) / 100;
      if ((i >> 4) == 31 && (C_LMASK >> (i & 15) & 1)) key += C_LATE;
      if (ready[hp] > tf[cb]) key += (1L << 40) + (ready[hp] - tf[cb]) * 1024;
      if (best < 0 || key < bkey) { best = i; bkey = key; }
    }
    done[best] = true;
    if (!started[cb]) { p.order[cb] = (uint16_t)best; started[cb] = true; }
    else p.order[nq++] = (uint16_t)best;
    if (ready[best >> 5] > tf[cb]) tf[cb] = ready[best >> 5];
    tf[cb] += alen(best & 15);
    if (tf[cb] + C_LAG > fin[best >> 5]) fin[best >> 5] = tf[cb] + C_LAG;
  }
}

}

extern "C" void kernel_launch(void* const* d_in, const int* in_sizes, int n_in, void* d_out, int out_size) {
  const bf16* A_x = (const bf16*)d_in[0];
  const bf16* A_c = (const bf16*)d_in[1];
  const bf16* A_wq = (const bf16*)d_in[2];
  const bf16* A_wuk = (const bf16*)d_in[3];
  const bf16* A_wuv = (const bf16*)d_in[4];
  const bf16* A_wo = (const bf16*)d_in[5];
  const bf16* B_x = (const bf16*)d_in[6];
  const bf16* B_wqkv = (const bf16*)d_in[7];
  const bf16* B_wo = (const bf16*)d_in[8];
  bf16* out = (bf16*)d_out;

  static Params p;
  static bf16 *q, *k, *v, *ctx, *qkvb, *ob;
  static bool init = false;
  if (!init) {
    cudaGetSymbolAddress((void**)&q, g_q);
    cudaGetSymbolAddress((void**)&k, g_k);
    cudaGetSymbolAddress((void**)&v, g_v);
    cudaGetSymbolAddress((void**)&qkvb, g_qkvb);
    cudaGetSymbolAddress((void**)&ob, g_ob);
    cudaFuncSetAttribute(mega_kernel, cudaFuncAttributeMaxDynamicSharedMemorySize, SMEM_BYTES);
    build_schedule(p);
    ctx = q;
    init = true;
  }
  make_map(&p.ta[0], A_x, SEQ, DM, 128, 1);
  make_map(&p.tb[0], A_wq, DM, HHD, 64, 2);
  make_map(&p.tc[0], q, SEQ, HHD, 64, 1);
  make_map(&p.ta[1], A_c, SEQ, DC, 128, 1);
  make_map(&p.tb[1], A_wuk, DC, HHD, 64, 2);
  make_map(&p.tc[1], k, SEQ, HHD, 64, 1);
  make_map(&p.ta[2], A_c, SEQ, DC, 128, 1);
  make_map(&p.tb[2], A_wuv, DC, HHD, 64, 2);
  make_map(&p.tc[2], v, SEQ, HHD, 64, 1);
  make_map(&p.ta[3], B_x, SEQ, DM, 128, 1);
  make_map(&p.tb[3], B_wqkv, DM, 3 * DM, 64, 2);
  make_map(&p.tc[3], qkvb, SEQ, 3 * DM, 64, 1);
  make_map(&p.ta[4], ctx, SEQ, HHD, 128, 1);
  make_map(&p.tb[4], A_wo, HHD, DM, 64, 2);
  make_map(&p.tc[4], out, SEQ, 2 * DM, 64, 1);
  make_map(&p.ta[5], ob, SEQ, DM, 128, 1);
  make_map(&p.tb[5], B_wo, DM, DM, 64, 2);
  make_map(&p.tc[5], out, SEQ, 2 * DM, 64, 1);
  make_map(&p.tq, q, SEQ, HHD, 128, 2);
  make_map(&p.tk, k, SEQ, HHD, 128, 2);
  make_map(&p.tv, v, SEQ, HHD, 128, 2);
  make_map(&p.tl, qkvb, SEQ / 2, 6 * DM, 64, 1);
  make_map(&p.th, qkvb, SEQ / 2, 6 * DM, 72, 1);
  make_map(&p.to, ctx, SEQ, HHD, 128, 2);
  p.ob = ob;
  mega_kernel<<<NCTA, 384, SMEM_BYTES, cudaStreamPerThread>>>(p);
}
```

```cpp
#include <cuda_runtime.h>
#include <cuda_bf16.h>
#include <cuda.h>
#include <stdint.h>
#include <string.h>

namespace {

typedef __nv_bfloat16 bf16;

constexpr int SEQ = 2048;
constexpr int NHEAD = 32;
constexpr int HD = 128;
constexpr int DM = 1024;
constexpr int DC = 512;
constexpr int HHD = NHEAD * HD;

__device__ __align__(1024) bf16 g_q[SEQ * HHD];
__device__ __align__(1024) bf16 g_k[SEQ * HHD];
__device__ __align__(1024) bf16 g_v[SEQ * HHD];
__device__ __align__(1024) bf16 g_qkvb[SEQ * 3 * DM];
__device__ __align__(1024) bf16 g_ob[SEQ * DM];
constexpr int CNT_QKV = 0, CNT_CTX = 16, CNT_QKVB = 32, CNT_DONE = 33, CNT_QUEUE = 34, CNT_OB = 35, CNT_N = 39;
__device__ uint32_t g_cnt[CNT_N * 8];

__device__ __forceinline__ uint32_t smem_u32(const void* p) {
  return static_cast<uint32_t>(__cvta_generic_to_shared(p));
}
__device__ __forceinline__ void mbar_init(uint32_t bar, uint32_t count) {
  asm volatile("mbarrier.init.shared::cta.b64 [%0], %1;" ::"r"(bar), "r"(count) : "memory");
}
__device__ __forceinline__ void mbar_expect_tx(uint32_t bar, uint32_t bytes) {
  asm volatile("mbarrier.arrive.expect_tx.shared::cta.b64 _, [%0], %1;" ::"r"(bar), "r"(bytes) : "memory");
}
__device__ __forceinline__ void mbar_arrive(uint32_t bar) {
  asm volatile("mbarrier.arrive.shared::cta.b64 _, [%0];" ::"r"(bar) : "memory");
}
__device__ __forceinline__ void mbar_arrive_if(uint32_t bar, bool on) {
  asm volatile("{\n.reg .pred p;\nsetp.ne.b32 p, %1, 0;\n@p mbarrier.arrive.shared::cta.b64 _, [%0];\n}" ::"r"(bar),
               "r"((int)on)
               : "memory");
}
__device__ __forceinline__ void mbar_arrive_cluster_if(uint32_t bar, uint32_t cta, bool on) {
  asm volatile(
      "{\n.reg .b32 ra;\n.reg .pred p;\nsetp.ne.b32 p, %2, 0;\nmapa.shared::cluster.u32 ra, %0, %1;\n"
      "@p mbarrier.arrive.shared::cluster.b64 _, [ra];\n}" ::"r"(bar),
      "r"(cta), "r"((int)on)
      : "memory");
}
__device__ __forceinline__ bool mbar_try_wait(uint32_t bar, uint32_t parity) {
  uint32_t ok;
  asm volatile(
      "{\n.reg .pred p;\nmbarrier.try_wait.parity.shared::cta.b64 p, [%1], %2;\nselp.u32 %0, 1, 0, p;\n}"
      : "=r"(ok)
      : "r"(bar), "r"(parity)
      : "memory");
  return ok != 0;
}
__device__ __forceinline__ bool mbar_test(uint32_t bar, uint32_t parity) {
  uint32_t ok;
  asm volatile(
      "{\n.reg .pred p;\nmbarrier.test_wait.parity.shared::cta.b64 p, [%1], %2;\nselp.u32 %0, 1, 0, p;\n}"
      : "=r"(ok)
      : "r"(bar), "r"(parity)
      : "memory");
  return ok != 0;
}
#define DBG(i, v)
__device__ __forceinline__ void mbar_wait(uint32_t bar, uint32_t parity) {
  asm volatile(
      "{\n.reg .pred p;\n.reg .u32 t;\n"
      "mbarrier.try_wait.parity.shared::cta.b64 p, [%0], %1;\n"
      "@p bra DONE;\n"
      "mov.u32 t, 0x100000;\n"
      "LAB_WAIT:\n"
      "mbarrier.try_wait.parity.shared::cta.b64 p, [%0], %1;\n"
      "@p bra DONE;\n"
      "sub.u32 t, t, 1;\n"
      "setp.ne.u32 p, t, 0;\n"
      "@p bra LAB_WAIT;\n"
      "trap;\n"
      "DONE:\n}" ::"r"(bar),
      "r"(parity)
      : "memory");
}
constexpr uint64_t EV_NORMAL = 0x1000000000000000ull;
__device__ __forceinline__ uint64_t policy_first() {
  uint64_t p;
  asm("createpolicy.fractional.L2::evict_first.b64 %0, 1.0;" : "=l"(p));
  return p;
}
#define EV_FIRST policy_first()
__device__ __forceinline__ void tma_load_3d(uint32_t dst, const CUtensorMap* map, int c0, int c1, int c2,
                                            uint32_t bar, uint64_t hint) {
  asm volatile(
      "cp.async.bulk.tensor.3d.shared::cluster.global.mbarrier::complete_tx::bytes.L2::cache_hint [%0], [%1, {%3, %4, %5}], [%2], %6;" ::"r"(dst),
      "l"(map), "r"(bar), "r"(c0), "r"(c1), "r"(c2), "l"(hint)
      : "memory");
}
__device__ __forceinline__ void tma_load_3d_mc(uint32_t dst, const CUtensorMap* map, int c0, int c1, int c2,
                                               uint32_t bar, uint16_t mask, uint64_t hint) {
  asm volatile(
      "cp.async.bulk.tensor.3d.shared::cluster.global.mbarrier::complete_tx::bytes.multicast::cluster.L2::cache_hint [%0], [%1, {%3, %4, %5}], [%2], %6, %7;" ::"r"(dst),
      "l"(map), "r"(bar), "r"(c0), "r"(c1), "r"(c2), "h"(mask), "l"(hint)
      : "memory");
}
__device__ __forceinline__ void tma_store_3d(const CUtensorMap* map, uint32_t src, int c0, int c1, int c2, uint64_t hint) {
  asm volatile("cp.async.bulk.tensor.3d.global.shared::cta.bulk_group.L2::cache_hint [%0, {%2, %3, %4}], [%1], %5;" ::"l"(map),
               "r"(src), "r"(c0), "r"(c1), "r"(c2), "l"(hint)
               : "memory");
}
__device__ __forceinline__ void tma_store_4d(const CUtensorMap* map, uint32_t src, int c2, int c3, uint64_t hint) {
  asm volatile("cp.async.bulk.tensor.4d.global.shared::cta.bulk_group.L2::cache_hint [%0, {%2, %2, %3, %4}], [%1], %5;" ::"l"(map),
               "r"(src), "r"(0), "r"(c2), "r"(c3), "l"(hint)
               : "memory");
}
__device__ __forceinline__ void bulk_commit() { asm volatile("cp.async.bulk.commit_group;" ::: "memory"); }
template <int N>
__device__ __forceinline__ void bulk_wait_read() {
  asm volatile("cp.async.bulk.wait_group.read %0;" ::"n"(N) : "memory");
}
template <int N>
__device__ __forceinline__ void bulk_wait() {
  asm volatile("cp.async.bulk.wait_group %0;" ::"n"(N) : "memory");
}
__device__ __forceinline__ void fence_proxy_async_smem() {
  asm volatile("fence.proxy.async.shared::cta;" ::: "memory");
}
__device__ __forceinline__ bool elect_one() {
  uint32_t pred;
  asm volatile("{\n.reg .pred P;\nelect.sync _|P, 0xffffffff;\nselp.b32 %0, 1, 0, P;\n}" : "=r"(pred));
  return pred != 0;
}
__device__ __forceinline__ void named_bar_sync(int id, int n) {
  asm volatile("bar.sync %0, %1;" ::"r"(id), "r"(n) : "memory");
}
__device__ __forceinline__ void named_bar_arrive(int id, int n) {
  asm volatile("bar.arrive %0, %1;" ::"r"(id), "r"(n) : "memory");
}
__device__ __forceinline__ void named_bar_sync_if(int id, int n, bool on) {
  asm volatile("{\n.reg .pred p;\nsetp.ne.b32 p, %2, 0;\n@p bar.sync %0, %1;\n}" ::"r"(id), "r"(n), "r"((int)on) : "memory");
}
__device__ __forceinline__ void named_bar_arrive_if(int id, int n, bool on) {
  asm volatile("{\n.reg .pred p;\nsetp.ne.b32 p, %2, 0;\n@p bar.arrive %0, %1;\n}" ::"r"(id), "r"(n), "r"((int)on) : "memory");
}
template <int N>
__device__ __forceinline__ void reg_alloc() {
  asm volatile("setmaxnreg.inc.sync.aligned.u32 %0;" ::"n"(N));
}
template <int N>
__device__ __forceinline__ void reg_dealloc() {
  asm volatile("setmaxnreg.dec.sync.aligned.u32 %0;" ::"n"(N));
}
__device__ __forceinline__ void wgmma_fence() { asm volatile("wgmma.fence.sync.aligned;" ::: "memory"); }
__device__ __forceinline__ void wgmma_commit() { asm volatile("wgmma.commit_group.sync.aligned;" ::: "memory"); }
template <int N>
__device__ __forceinline__ void wgmma_wait() {
  asm volatile("wgmma.wait_group.sync.aligned %0;" ::"n"(N) : "memory");
}
template <int N>
__device__ __forceinline__ void fence_regs(float (&d)[N]) {
#pragma unroll
  for (int i = 0; i < N; i++) asm volatile("" : "+f"(d[i])::"memory");
}
__device__ __forceinline__ void fence_regs(uint32_t (&d)[32]) {
#pragma unroll
  for (int i = 0; i < 16; i++) asm volatile("" : "+r"(d[i])::"memory");
}
template <int N>
__device__ __forceinline__ void undef_regs(float (&d)[N]) {
#pragma unroll
  for (int i = 0; i < N; i++) d[i] = 0.f;
}
template <int N>
__device__ __forceinline__ void undef_regs(uint32_t (&d)[N]) {
#pragma unroll
  for (int i = 0; i < N; i++) d[i] = 0u;
}
__device__ __forceinline__ uint32_t pack_bf16(float lo, float hi) {
  uint32_t r;
  asm("cvt.rn.bf16x2.f32 %0, %1, %2;" : "=r"(r) : "f"(hi), "f"(lo));
  return r;
}
__device__ __forceinline__ void stmatrix_x4(uint32_t addr, uint32_t r0, uint32_t r1, uint32_t r2, uint32_t r3) {
  asm volatile("stmatrix.sync.aligned.m8n8.x4.shared.b16 [%0], {%1, %2, %3, %4};" ::"r"(addr), "r"(r0), "r"(r1),
               "r"(r2), "r"(r3)
               : "memory");
}
__device__ __forceinline__ void stmatrix_x4_p(uint32_t addr, uint32_t r0, uint32_t r1, uint32_t r2, uint32_t r3,
                                              bool on) {
  asm volatile("{\n.reg .pred p;\nsetp.ne.b32 p, %5, 0;\n@p stmatrix.sync.aligned.m8n8.x4.shared.b16 [%0], {%1, %2, %3, %4};\n}" ::"r"(addr),
               "r"(r0), "r"(r1), "r"(r2), "r"(r3), "r"((int)on)
               : "memory");
}
__device__ __forceinline__ float ex2(float x) {
  float y;
  asm("ex2.approx.ftz.f32 %0, %1;" : "=f"(y) : "f"(x));
  return y;
}
__device__ __forceinline__ float rcp(float x) {
  float y;
  asm("rcp.approx.ftz.f32 %0, %1;" : "=f"(y) : "f"(x));
  return y;
}
__device__ __forceinline__ float ex2v(float x) {
  float y;
  asm volatile("ex2.approx.ftz.f32 %0, %1;" : "=f"(y) : "f"(x));
  return y;
}
__device__ __forceinline__ float addv(float a, float b) {
  float y;
  asm volatile("add.f32 %0, %1, %2;" : "=f"(y) : "f"(a), "f"(b));
  return y;
}
__device__ __forceinline__ void mbar_arrive_elect(uint32_t bar, bool on) {
  asm volatile("{\n.reg .pred p, q;\nelect.sync _|q, 0xffffffff;\nsetp.ne.and.b32 p, %1, 0, q;\n@p mbarrier.arrive.shared::cta.b64 _, [%0];\n}" ::"r"(bar),
               "r"((int)on)
               : "memory");
}
__device__ __forceinline__ float mbar_test2(uint32_t bar0, uint32_t par0, uint32_t bar1, uint32_t par1) {
  float f;
  asm volatile(
      "{\n.reg .pred p, q;\nmbarrier.test_wait.parity.shared::cta.b64 p, [%1], %2;\n"
      "mbarrier.test_wait.parity.shared::cta.b64 q, [%3], %4;\nand.pred p, p, q;\nselp.f32 %0, 0f00000000, 0f80000000, p;\n}"
      : "=f"(f)
      : "r"(bar0), "r"(par0), "r"(bar1), "r"(par1)
      : "memory");
  return f;
}
__device__ __forceinline__ void mbar_wait_rest(uint32_t bar, uint32_t parity, bool ok) {
  asm volatile(
      "{\n.reg .pred p;\n.reg .u32 t;\n"
      "setp.ne.b32 p, %2, 0;\n"
      "@p bra DONE;\n"
      "mov.u32 t, 0x100000;\n"
      "LAB_WAIT:\n"
      "mbarrier.try_wait.parity.shared::cta.b64 p, [%0], %1;\n"
      "@p bra DONE;\n"
      "sub.u32 t, t, 1;\n"
      "setp.ne.u32 p, t, 0;\n"
      "@p bra LAB_WAIT;\n"
      "trap;\n"
      "DONE:\n}" ::"r"(bar),
      "r"(parity), "r"((int)ok)
      : "memory");
}
__device__ __forceinline__ void cnt_signal(int idx, uint32_t inc = 1) {
  asm volatile("red.release.gpu.global.add.u32 [%0], %1;" ::"l"(g_cnt + idx * 8), "r"(inc) : "memory");
}
__device__ __forceinline__ void cnt_signal_done(int idx, uint32_t inc = 1) {
  asm volatile("red.relaxed.gpu.global.add.u32 [%0], %1;" ::"l"(g_cnt + idx * 8), "r"(inc) : "memory");
}
__device__ __forceinline__ uint32_t cnt_next(int idx) {
  uint32_t v;
  asm volatile("atom.relaxed.gpu.global.add.u32 %0, [%1], 1;" : "=r"(v) : "l"(g_cnt + idx * 8) : "memory");
  return v;
}
__device__ __forceinline__ uint32_t cnt_peek(int idx) {
  uint32_t v;
  asm volatile("ld.acquire.gpu.global.u32 %0, [%1];" : "=r"(v) : "l"(g_cnt + idx * 8) : "memory");
  return v;
}
__device__ __forceinline__ void cnt_wait(int idx, uint32_t target) {
  asm volatile(
      "{\n.reg .pred p;\n.reg .u32 v, t0, t1;\n"
      "ld.acquire.gpu.global.u32 v, [%0];\n"
      "setp.ge.u32 p, v, %1;\n"
      "@p bra DONE;\n"
      "mov.u32 t0, %%clock;\n"
      "LAB_WAIT:\n"
      "nanosleep.u32 100;\n"
      "ld.acquire.gpu.global.u32 v, [%0];\n"
      "setp.ge.u32 p, v, %1;\n"
      "@p bra DONE;\n"
      "mov.u32 t1, %%clock;\n"
      "sub.u32 t1, t1, t0;\n"
      "setp.lt.u32 p, t1, 0x80000000;\n"
      "@p bra LAB_WAIT;\n"
      "trap;\n"
      "DONE:\n}" ::"l"(g_cnt + idx * 8),
      "r"(target)
      : "memory");
}
__device__ __forceinline__ void cnt_wait_bit(int idx, uint32_t bit, uint32_t& v) {
  asm volatile(
      "{\n.reg .pred p;\n.reg .u32 x, t0, t1;\n"
      "and.b32 x, %0, %2;\n"
      "setp.ne.u32 p, x, 0;\n"
      "@p bra DONE;\n"
      "mov.u32 t0, %%clock;\n"
      "LAB_WAIT:\n"
      "ld.acquire.gpu.global.u32 %0, [%1];\n"
      "and.b32 x, %0, %2;\n"
      "setp.ne.u32 p, x, 0;\n"
      "@p bra DONE;\n"
      "nanosleep.u32 64;\n"
      "mov.u32 t1, %%clock;\n"
      "sub.u32 t1, t1, t0;\n"
      "setp.lt.u32 p, t1, 0x80000000;\n"
      "@p bra LAB_WAIT;\n"
      "trap;\n"
      "DONE:\n}" : "+r"(v) : "l"(g_cnt + idx * 8),
      "r"(bit)
      : "memory");
}
__device__ __forceinline__ bool cnt_done(uint32_t total) {
  uint32_t old;
  asm volatile("atom.acq_rel.gpu.global.add.u32 %0, [%1], 1;" : "=r"(old) : "l"(g_cnt + CNT_DONE * 8) : "memory");
  return old == total - 1;
}
__device__ __forceinline__ void cnt_rearm() {
#pragma unroll
  for (int i = 0; i < CNT_N; i++) g_cnt[i * 8] = 0;
}
__device__ __forceinline__ void fence_proxy_async_global() { asm volatile("fence.proxy.async.global;" ::: "memory"); }
#define TL(role, code)
#define TL0(code)
#define TL_DECL
#define TR_DECL
#define TR(code)
#define TRI(id, code)
#define TW_DECL
#define TW(w, stmt) stmt
#define TW_FLUSH()
#define TW_END()

__device__ __forceinline__ uint32_t make_desc(uint32_t addr, uint32_t lbo_bytes) {
  return (addr >> 4) + ((lbo_bytes >> 4) << 16);
}

__device__ __forceinline__ void wgmma_ss_n128(float (&d)[64], uint32_t da, uint32_t db, int scale_d) {
  asm volatile("{\n.reg .pred p;\n.reg .b64 a, b;\nsetp.ne.b32 p, %66, 0;\nmov.b64 a, {%64, 0x40000040};\nmov.b64 b, {%65, 0x40000040};\n"
    "wgmma.mma_async.sync.aligned.m64n128k16.f32.bf16.bf16 {%0, %1, %2, %3, %4, %5, %6, %7, %8, %9, %10, %11, %12, %13, %14, %15, %16, %17, %18, %19, %20, %21, %22, %23, %24, %25, %26, %27, %28, %29, %30, %31, %32, %33, %34, %35, %36, %37, %38, %39, %40, %41, %42, %43, %44, %45, %46, %47, %48, %49, %50, %51, %52, %53, %54, %55, %56, %57, %58, %59, %60, %61, %62, %63}, a, b, p, 1, 1, 0, 0;\n}\n"
    : "+f"(d[0]), "+f"(d[1]), "+f"(d[2]), "+f"(d[3]), "+f"(d[4]), "+f"(d[5]), "+f"(d[6]), "+f"(d[7]), "+f"(d[8]), "+f"(d[9]), "+f"(d[10]), "+f"(d[11]), "+f"(d[12]), "+f"(d[13]), "+f"(d[14]), "+f"(d[15]), "+f"(d[16]), "+f"(d[17]), "+f"(d[18]), "+f"(d[19]), "+f"(d[20]), "+f"(d[21]), "+f"(d[22]), "+f"(d[23]), "+f"(d[24]), "+f"(d[25]), "+f"(d[26]), "+f"(d[27]), "+f"(d[28]), "+f"(d[29]), "+f"(d[30]), "+f"(d[31]), "+f"(d[32]), "+f"(d[33]), "+f"(d[34]), "+f"(d[35]), "+f"(d[36]), "+f"(d[37]), "+f"(d[38]), "+f"(d[39]), "+f"(d[40]), "+f"(d[41]), "+f"(d[42]), "+f"(d[43]), "+f"(d[44]), "+f"(d[45]), "+f"(d[46]), "+f"(d[47]), "+f"(d[48]), "+f"(d[49]), "+f"(d[50]), "+f"(d[51]), "+f"(d[52]), "+f"(d[53]), "+f"(d[54]), "+f"(d[55]), "+f"(d[56]), "+f"(d[57]), "+f"(d[58]), "+f"(d[59]), "+f"(d[60]), "+f"(d[61]), "+f"(d[62]), "+f"(d[63])
    : "r"(da), "r"(db), "r"(scale_d));
}
__device__ __forceinline__ void wgmma_ss_n64(float (&d)[32], uint32_t da, uint32_t db, int scale_d) {
  asm volatile("{\n.reg .pred p;\n.reg .b64 a, b;\nsetp.ne.b32 p, %34, 0;\nmov.b64 a, {%32, 0x40000040};\nmov.b64 b, {%33, 0x40000040};\n"
    "wgmma.mma_async.sync.aligned.m64n64k16.f32.bf16.bf16 {%0, %1, %2, %3, %4, %5, %6, %7, %8, %9, %10, %11, %12, %13, %14, %15, %16, %17, %18, %19, %20, %21, %22, %23, %24, %25, %26, %27, %28, %29, %30, %31}, a, b, p, 1, 1, 0, 0;\n}\n"
    : "+f"(d[0]), "+f"(d[1]), "+f"(d[2]), "+f"(d[3]), "+f"(d[4]), "+f"(d[5]), "+f"(d[6]), "+f"(d[7]), "+f"(d[8]), "+f"(d[9]), "+f"(d[10]), "+f"(d[11]), "+f"(d[12]), "+f"(d[13]), "+f"(d[14]), "+f"(d[15]), "+f"(d[16]), "+f"(d[17]), "+f"(d[18]), "+f"(d[19]), "+f"(d[20]), "+f"(d[21]), "+f"(d[22]), "+f"(d[23]), "+f"(d[24]), "+f"(d[25]), "+f"(d[26]), "+f"(d[27]), "+f"(d[28]), "+f"(d[29]), "+f"(d[30]), "+f"(d[31])
    : "r"(da), "r"(db), "r"(scale_d));
}
__device__ __forceinline__ void wgmma_rs_n128_tb(float (&d)[64], uint32_t a0, uint32_t a1, uint32_t a2, uint32_t a3, uint32_t db, int scale_d) {
  asm volatile("{\n.reg .pred p;\n.reg .b64 b;\nsetp.ne.b32 p, %69, 0;\nmov.b64 b, {%68, 0x40000040};\n"
    "wgmma.mma_async.sync.aligned.m64n128k16.f32.bf16.bf16 {%0, %1, %2, %3, %4, %5, %6, %7, %8, %9, %10, %11, %12, %13, %14, %15, %16, %17, %18, %19, %20, %21, %22, %23, %24, %25, %26, %27, %28, %29, %30, %31, %32, %33, %34, %35, %36, %37, %38, %39, %40, %41, %42, %43, %44, %45, %46, %47, %48, %49, %50, %51, %52, %53, %54, %55, %56, %57, %58, %59, %60, %61, %62, %63}, {%64, %65, %66, %67}, b, p, 1, 1, 1;\n}\n"
    : "+f"(d[0]), "+f"(d[1]), "+f"(d[2]), "+f"(d[3]), "+f"(d[4]), "+f"(d[5]), "+f"(d[6]), "+f"(d[7]), "+f"(d[8]), "+f"(d[9]), "+f"(d[10]), "+f"(d[11]), "+f"(d[12]), "+f"(d[13]), "+f"(d[14]), "+f"(d[15]), "+f"(d[16]), "+f"(d[17]), "+f"(d[18]), "+f"(d[19]), "+f"(d[20]), "+f"(d[21]), "+f"(d[22]), "+f"(d[23]), "+f"(d[24]), "+f"(d[25]), "+f"(d[26]), "+f"(d[27]), "+f"(d[28]), "+f"(d[29]), "+f"(d[30]), "+f"(d[31]), "+f"(d[32]), "+f"(d[33]), "+f"(d[34]), "+f"(d[35]), "+f"(d[36]), "+f"(d[37]), "+f"(d[38]), "+f"(d[39]), "+f"(d[40]), "+f"(d[41]), "+f"(d[42]), "+f"(d[43]), "+f"(d[44]), "+f"(d[45]), "+f"(d[46]), "+f"(d[47]), "+f"(d[48]), "+f"(d[49]), "+f"(d[50]), "+f"(d[51]), "+f"(d[52]), "+f"(d[53]), "+f"(d[54]), "+f"(d[55]), "+f"(d[56]), "+f"(d[57]), "+f"(d[58]), "+f"(d[59]), "+f"(d[60]), "+f"(d[61]), "+f"(d[62]), "+f"(d[63])
    : "r"(a0), "r"(a1), "r"(a2), "r"(a3), "r"(db), "r"(scale_d));
}
__device__ __forceinline__ void wgmma_ss_n72_init(float (&d)[36], uint32_t da, uint32_t db) {
  asm volatile("{\n.reg .pred p;\n.reg .b64 a, b;\nsetp.ne.b32 p, 0, 0;\nmov.b64 a, {%36, 0x40000040};\nmov.b64 b, {%37, 0x40000040};\n"
    "wgmma.mma_async.sync.aligned.m64n72k16.f32.bf16.bf16 {%0, %1, %2, %3, %4, %5, %6, %7, %8, %9, %10, %11, %12, %13, %14, %15, %16, %17, %18, %19, %20, %21, %22, %23, %24, %25, %26, %27, %28, %29, %30, %31, %32, %33, %34, %35}, a, b, p, 1, 1, 0, 0;\n}\n"
    : "=f"(d[0]), "=f"(d[1]), "=f"(d[2]), "=f"(d[3]), "=f"(d[4]), "=f"(d[5]), "=f"(d[6]), "=f"(d[7]), "=f"(d[8]), "=f"(d[9]), "=f"(d[10]), "=f"(d[11]), "=f"(d[12]), "=f"(d[13]), "=f"(d[14]), "=f"(d[15]), "=f"(d[16]), "=f"(d[17]), "=f"(d[18]), "=f"(d[19]), "=f"(d[20]), "=f"(d[21]), "=f"(d[22]), "=f"(d[23]), "=f"(d[24]), "=f"(d[25]), "=f"(d[26]), "=f"(d[27]), "=f"(d[28]), "=f"(d[29]), "=f"(d[30]), "=f"(d[31]), "=f"(d[32]), "=f"(d[33]), "=f"(d[34]), "=f"(d[35])
    : "r"(da), "r"(db));
}
__device__ __forceinline__ void wgmma_ss_n72(float (&d)[36], uint32_t da, uint32_t db, int scale_d) {
  asm volatile("{\n.reg .pred p;\n.reg .b64 a, b;\nsetp.ne.b32 p, %38, 0;\nmov.b64 a, {%36, 0x40000040};\nmov.b64 b, {%37, 0x40000040};\n"
    "wgmma.mma_async.sync.aligned.m64n72k16.f32.bf16.bf16 {%0, %1, %2, %3, %4, %5, %6, %7, %8, %9, %10, %11, %12, %13, %14, %15, %16, %17, %18, %19, %20, %21, %22, %23, %24, %25, %26, %27, %28, %29, %30, %31, %32, %33, %34, %35}, a, b, p, 1, 1, 0, 0;\n}\n"
    : "+f"(d[0]), "+f"(d[1]), "+f"(d[2]), "+f"(d[3]), "+f"(d[4]), "+f"(d[5]), "+f"(d[6]), "+f"(d[7]), "+f"(d[8]), "+f"(d[9]), "+f"(d[10]), "+f"(d[11]), "+f"(d[12]), "+f"(d[13]), "+f"(d[14]), "+f"(d[15]), "+f"(d[16]), "+f"(d[17]), "+f"(d[18]), "+f"(d[19]), "+f"(d[20]), "+f"(d[21]), "+f"(d[22]), "+f"(d[23]), "+f"(d[24]), "+f"(d[25]), "+f"(d[26]), "+f"(d[27]), "+f"(d[28]), "+f"(d[29]), "+f"(d[30]), "+f"(d[31]), "+f"(d[32]), "+f"(d[33]), "+f"(d[34]), "+f"(d[35])
    : "r"(da), "r"(db), "r"(scale_d));
}
template <int OA, int OB>
__device__ __forceinline__ void wgmma_ss_n128_tb(float (&d)[64], uint32_t da, uint32_t db, int scale_d) {
  asm volatile("{\n.reg .pred p;\n.reg .b64 a, b;\n.reg .b32 x, y;\nsetp.ne.b32 p, %66, 0;\nadd.u32 x, %64, %67;\nadd.u32 y, %65, %68;\nmov.b64 a, {x, 0x40000040};\nmov.b64 b, {y, 0x40000040};\n"
    "wgmma.mma_async.sync.aligned.m64n128k16.f32.bf16.bf16 {%0, %1, %2, %3, %4, %5, %6, %7, %8, %9, %10, %11, %12, %13, %14, %15, %16, %17, %18, %19, %20, %21, %22, %23, %24, %25, %26, %27, %28, %29, %30, %31, %32, %33, %34, %35, %36, %37, %38, %39, %40, %41, %42, %43, %44, %45, %46, %47, %48, %49, %50, %51, %52, %53, %54, %55, %56, %57, %58, %59, %60, %61, %62, %63}, a, b, p, 1, 1, 0, 1;\n}\n"
    : "+f"(d[0]), "+f"(d[1]), "+f"(d[2]), "+f"(d[3]), "+f"(d[4]), "+f"(d[5]), "+f"(d[6]), "+f"(d[7]), "+f"(d[8]), "+f"(d[9]), "+f"(d[10]), "+f"(d[11]), "+f"(d[12]), "+f"(d[13]), "+f"(d[14]), "+f"(d[15]), "+f"(d[16]), "+f"(d[17]), "+f"(d[18]), "+f"(d[19]), "+f"(d[20]), "+f"(d[21]), "+f"(d[22]), "+f"(d[23]), "+f"(d[24]), "+f"(d[25]), "+f"(d[26]), "+f"(d[27]), "+f"(d[28]), "+f"(d[29]), "+f"(d[30]), "+f"(d[31]), "+f"(d[32]), "+f"(d[33]), "+f"(d[34]), "+f"(d[35]), "+f"(d[36]), "+f"(d[37]), "+f"(d[38]), "+f"(d[39]), "+f"(d[40]), "+f"(d[41]), "+f"(d[42]), "+f"(d[43]), "+f"(d[44]), "+f"(d[45]), "+f"(d[46]), "+f"(d[47]), "+f"(d[48]), "+f"(d[49]), "+f"(d[50]), "+f"(d[51]), "+f"(d[52]), "+f"(d[53]), "+f"(d[54]), "+f"(d[55]), "+f"(d[56]), "+f"(d[57]), "+f"(d[58]), "+f"(d[59]), "+f"(d[60]), "+f"(d[61]), "+f"(d[62]), "+f"(d[63])
    : "r"(da), "r"(db), "r"(scale_d), "n"(OA), "n"(OB));
}
template <int OA, int OB>
__device__ __forceinline__ void wgmma_ss_n256_tbo(float (&d)[128], uint32_t da, uint32_t db, int scale_d) {
  asm volatile("{\n.reg .pred p;\n.reg .b64 a, b;\n.reg .b32 x, y;\nsetp.ne.b32 p, %130, 0;\nadd.u32 x, %128, %131;\nadd.u32 y, %129, %132;\nmov.b64 a, {x, 0x40000040};\nmov.b64 b, {y, 0x40000040};\n"
    "wgmma.mma_async.sync.aligned.m64n256k16.f32.bf16.bf16 {%0, %1, %2, %3, %4, %5, %6, %7, %8, %9, %10, %11, %12, %13, %14, %15, %16, %17, %18, %19, %20, %21, %22, %23, %24, %25, %26, %27, %28, %29, %30, %31, %32, %33, %34, %35, %36, %37, %38, %39, %40, %41, %42, %43, %44, %45, %46, %47, %48, %49, %50, %51, %52, %53, %54, %55, %56, %57, %58, %59, %60, %61, %62, %63, %64, %65, %66, %67, %68, %69, %70, %71, %72, %73, %74, %75, %76, %77, %78, %79, %80, %81, %82, %83, %84, %85, %86, %87, %88, %89, %90, %91, %92, %93, %94, %95, %96, %97, %98, %99, %100, %101, %102, %103, %104, %105, %106, %107, %108, %109, %110, %111, %112, %113, %114, %115, %116, %117, %118, %119, %120, %121, %122, %123, %124, %125, %126, %127}, a, b, p, 1, 1, 0, 1;\n}\n"
    : "+f"(d[0]), "+f"(d[1]), "+f"(d[2]), "+f"(d[3]), "+f"(d[4]), "+f"(d[5]), "+f"(d[6]), "+f"(d[7]), "+f"(d[8]), "+f"(d[9]), "+f"(d[10]), "+f"(d[11]), "+f"(d[12]), "+f"(d[13]), "+f"(d[14]), "+f"(d[15]), "+f"(d[16]), "+f"(d[17]), "+f"(d[18]), "+f"(d[19]), "+f"(d[20]), "+f"(d[21]), "+f"(d[22]), "+f"(d[23]), "+f"(d[24]), "+f"(d[25]), "+f"(d[26]), "+f"(d[27]), "+f"(d[28]), "+f"(d[29]), "+f"(d[30]), "+f"(d[31]), "+f"(d[32]), "+f"(d[33]), "+f"(d[34]), "+f"(d[35]), "+f"(d[36]), "+f"(d[37]), "+f"(d[38]), "+f"(d[39]), "+f"(d[40]), "+f"(d[41]), "+f"(d[42]), "+f"(d[43]), "+f"(d[44]), "+f"(d[45]), "+f"(d[46]), "+f"(d[47]), "+f"(d[48]), "+f"(d[49]), "+f"(d[50]), "+f"(d[51]), "+f"(d[52]), "+f"(d[53]), "+f"(d[54]), "+f"(d[55]), "+f"(d[56]), "+f"(d[57]), "+f"(d[58]), "+f"(d[59]), "+f"(d[60]), "+f"(d[61]), "+f"(d[62]), "+f"(d[63]), "+f"(d[64]), "+f"(d[65]), "+f"(d[66]), "+f"(d[67]), "+f"(d[68]), "+f"(d[69]), "+f"(d[70]), "+f"(d[71]), "+f"(d[72]), "+f"(d[73]), "+f"(d[74]), "+f"(d[75]), "+f"(d[76]), "+f"(d[77]), "+f"(d[78]), "+f"(d[79]), "+f"(d[80]), "+f"(d[81]), "+f"(d[82]), "+f"(d[83]), "+f"(d[84]), "+f"(d[85]), "+f"(d[86]), "+f"(d[87]), "+f"(d[88]), "+f"(d[89]), "+f"(d[90]), "+f"(d[91]), "+f"(d[92]), "+f"(d[93]), "+f"(d[94]), "+f"(d[95]), "+f"(d[96]), "+f"(d[97]), "+f"(d[98]), "+f"(d[99]), "+f"(d[100]), "+f"(d[101]), "+f"(d[102]), "+f"(d[103]), "+f"(d[104]), "+f"(d[105]), "+f"(d[106]), "+f"(d[107]), "+f"(d[108]), "+f"(d[109]), "+f"(d[110]), "+f"(d[111]), "+f"(d[112]), "+f"(d[113]), "+f"(d[114]), "+f"(d[115]), "+f"(d[116]), "+f"(d[117]), "+f"(d[118]), "+f"(d[119]), "+f"(d[120]), "+f"(d[121]), "+f"(d[122]), "+f"(d[123]), "+f"(d[124]), "+f"(d[125]), "+f"(d[126]), "+f"(d[127])
    : "r"(da), "r"(db), "r"(scale_d), "n"(OA), "n"(OB));
}

constexpr int NCTA = 132;
constexpr int NCLUSTER = 66;
constexpr int NPROB = 6;
#define DO_LOCAL true
#define DO_ATT true
#define NA_CL_ 32
#define NITEMS 512
constexpr int G1_MAX = 24, NA_CL = NA_CL_, NB_CTA = NCTA - 2 * NA_CL;
constexpr int TILE32K = 32768;
constexpr uint32_t DBASE = 1024;
constexpr int OFF_STG = 4 * TILE32K;
constexpr int OFF_A = 5 * TILE32K;
constexpr int OFF_BAR = 7 * TILE32K;
constexpr int L_K = 8192, L_V = L_K + 9216, L_P = L_V + 9216;
constexpr int SMEM_BYTES = OFF_BAR + 1024;
constexpr int B_GFULL = 0, B_GEMPTY = 32, B_AFULL = 64, B_AEMPTY = 104, B_QFULL = 144, B_QEMPTY = 160,
              B_SFULL = 176, B_SEMPTY = 208, B_OFULL = 240, B_STGFREE = 256, S_CODE = 272, B_SFULL2 = 304;
#define FS 2
#define HW 1
#define PACE 900u
#define REG_C 232
#define REG_P 40

struct Params {
  CUtensorMap ta[NPROB];
  CUtensorMap tb[NPROB];
  CUtensorMap tc[NPROB];
  CUtensorMap tq, tk, tv, to, tl, th;
  bf16* ob;
  uint16_t g[NCLUSTER][G1_MAX];
  uint16_t order[512];
};
__device__ __forceinline__ uint32_t tail_item(uint32_t code) {
  return (code & 0x7FFF) < 64 ? (5u << 8) | ((code & 4) << 4) | (code & 0x33) : 0xFFFFu;
}
#define HM 0x39383F00
#define HINT(b) ((HM >> (b) & 1) ? EV_FIRST : EV_NORMAL)
__device__ __forceinline__ uint32_t lds32(uint32_t a) {
  uint32_t v;
  asm volatile("ld.shared.u32 %0, [%1];" : "=r"(v) : "r"(a) : "memory");
  return v;
}
__device__ __forceinline__ uint4 lds128(uint32_t a) {
  uint4 v;
  asm volatile("ld.shared.v4.u32 {%0, %1, %2, %3}, [%4];" : "=r"(v.x), "=r"(v.y), "=r"(v.z), "=r"(v.w) : "r"(a) : "memory");
  return v;
}
__device__ __forceinline__ void sts64(uint32_t a, float x, float y) {
  asm volatile("st.shared.v2.f32 [%0], {%1, %2};" ::"r"(a), "f"(x), "f"(y) : "memory");
}
__device__ __forceinline__ void sts32(uint32_t a, uint32_t v) {
  asm volatile("st.shared.u32 [%0], %1;" ::"r"(a), "r"(v) : "memory");
}
__device__ __forceinline__ uint32_t opaque_tid() {
  uint32_t t;
  asm volatile("mov.u32 %0, %%tid.x;" : "=r"(t));
  return t;
}
__device__ __forceinline__ uint32_t stg_off(uint32_t tid) {
  return (tid >> 5) * 2048 + (tid & 15) * 128 + ((((tid >> 4) & 1) ^ (tid & 7)) << 4);
}
__device__ __forceinline__ int prob_nkb4(int prob) { return (0x4F4224 >> (prob * 4) & 15) + (prob == 4); }

constexpr float SM_C = 0.08838834764831845f * 1.4426950408889634f;
constexpr float SM_HI = 1099511627776.0f;
constexpr float SM_LO = 8.673617379884035e-19f;
__device__ __forceinline__ void softmax_max(const float (&s)[64], float& a0, float& a1) {
  a0 = fmaxf(s[0], s[1]);
  a1 = fmaxf(s[2], s[3]);
#pragma unroll
  for (int j = 1; j < 16; j++) {
    a0 = fmaxf(a0, fmaxf(s[4 * j], s[4 * j + 1]));
    a1 = fmaxf(a1, fmaxf(s[4 * j + 2], s[4 * j + 3]));
  }
  a0 = fmaxf(a0, __shfl_xor_sync(0xffffffffu, a0, 1));
  a1 = fmaxf(a1, __shfl_xor_sync(0xffffffffu, a1, 1));
  a0 = fmaxf(a0, __shfl_xor_sync(0xffffffffu, a0, 2));
  a1 = fmaxf(a1, __shfl_xor_sync(0xffffffffu, a1, 2));
}
template <int J0, int J1, bool OFS, int N>
__device__ __forceinline__ void softmax_exp(const float (&s)[64], float b0, float b1, uint32_t (&out)[N], float& t0,
                                            float& t1) {
#pragma unroll
  for (int j = J0; j < J1; j++) {
    const float e0 = ex2(OFS ? s[4 * j] + b0 : s[4 * j]);
    const float e1 = ex2(OFS ? s[4 * j + 1] + b0 : s[4 * j + 1]);
    const float e2 = ex2(OFS ? s[4 * j + 2] + b1 : s[4 * j + 2]);
    const float e3 = ex2(OFS ? s[4 * j + 3] + b1 : s[4 * j + 3]);
    t0 += e0 + e1;
    t1 += e2 + e3;
    out[2 * j] = pack_bf16(e0, e1);
    out[2 * j + 1] = pack_bf16(e2, e3);
  }
}

__device__ __forceinline__ uint32_t scale_q(uint32_t x) {
  uint32_t t, y;
  asm("mul.rn.bf16x2 %0, %1, %2;" : "=r"(t) : "r"(x), "r"(0xb9d8b9d8u));
  asm("fma.rn.bf16x2 %0, %1, %2, %3;" : "=r"(y) : "r"(x), "r"(0x3e033e03u), "r"(t));
  return y;
}

__global__ void __cluster_dims__(2, 1, 1) __launch_bounds__(384, 1) mega_kernel(const __grid_constant__ Params p) {
  extern __shared__ __align__(1024) uint8_t smem_raw[];
  const uint32_t sbase = smem_u32(smem_raw);
  const uint32_t s_bar = sbase + OFF_BAR;
  const int cluster_id = blockIdx.x >> 1;
  const bool isB = cluster_id >= NA_CL;
#define EARLY 1
  const int prob0 = isB ? 3 : cluster_id >> 4;
  const int ng0 = (isB ? (cluster_id - NA_CL) >> 3 : (cluster_id >> 3) & 1) * 4;
  const uint32_t t0 = clock();
  auto early = [&](int s) {
    const uint32_t full = s_bar + B_GFULL + 8 * s;
    mbar_expect_tx(full, 49152);
    tma_load_3d(sbase + OFF_A + s * 16384, &p.ta[prob0], 0, (blockIdx.x & 15) * 128, s, full, EV_NORMAL);
    tma_load_3d(sbase + s * TILE32K, &p.tb[prob0], 0, s * 64, ng0, full, EV_NORMAL);
    tma_load_3d(sbase + s * TILE32K + 16384, &p.tb[prob0], 0, s * 64, ng0 + 2, full, EV_NORMAL);
  };
  if ((threadIdx.x >> 5) == 8) {
    if (elect_one()) {
      mbar_init(s_bar + B_GFULL, 1);
      if (EARLY) early(0);
      for (int s = 1; s < 4; s++) mbar_init(s_bar + B_GFULL + 8 * s, 1);
      asm volatile("fence.mbarrier_init.release.cluster;" ::: "memory");
    }
    __syncwarp();
    named_bar_arrive(7, 288);
  }
  const int warp0 = __shfl_sync(0xffffffffu, threadIdx.x >> 5, 0);
  if (warp0 >= 8) reg_dealloc<REG_P>();
#define CLUSTER_ARRIVE() asm volatile("barrier.cluster.arrive.relaxed.aligned;" ::: "memory")
#define CLUSTER_WAIT() asm volatile("barrier.cluster.wait.acquire.aligned;" ::: "memory")

  if (warp0 >= 8) {
    if (warp0 == 10 && elect_one()) {
      if ((sbase & 0x3FFFFu) != DBASE) __trap();
      for (int s = 0; s < 4; s++) {
        mbar_init(s_bar + B_GEMPTY + 8 * s, 4);
        mbar_init(s_bar + B_SFULL + 8 * s, 4);
        mbar_init(s_bar + B_SFULL2 + 8 * s, 4);
        mbar_init(s_bar + B_SEMPTY + 8 * s, 1);
        mbar_init(s_bar + B_AFULL + 8 * s, 1);
        mbar_init(s_bar + B_AEMPTY + 8 * s, s == 1 && !isB ? 8 : 2);
      }
      for (int s = 0; s < 2; s++) {
        mbar_init(s_bar + B_QFULL + 8 * s, 1);
        mbar_init(s_bar + B_QEMPTY + 8 * s, 2);
      }
      mbar_init(s_bar + B_OFULL, 8);
      mbar_init(s_bar + B_STGFREE, 1);
      asm volatile("fence.mbarrier_init.release.cluster;" ::: "memory");
    }
    __syncwarp();
    CLUSTER_ARRIVE();
    if (EARLY && warp0 == 8 && elect_one()) {
#pragma unroll 1
      for (int s = 1; s < 4; s++) {
        while ((uint32_t)clock() - t0 < s * PACE) {}
        early(s);
      }
    }
    __syncwarp();
    CLUSTER_WAIT();
    const uint32_t rank = blockIdx.x & 1;
    if (warp0 == 8) {
      if (elect_one()) {
        TL_DECL;
        uint32_t gphase = 1 - EARLY;
        uint32_t tail = 0;
        int gi = 0;
        uint32_t rsel = rank, aswz = 0, lastq = 0, n = 0;
        for (int seg = 0; seg < 2; seg++) {
          for (;;) {
            uint32_t item = p.g[cluster_id][gi++];
            if (item == 0x500u) item = tail;
            if (item >= 0x600u) break;
            const int prob = item >> 8;
            const int rt = ((item >> 4) & 15) * 2 + rsel;
            const int ngrp0 = (item & 15) * 4;
            const int nkb4 = prob_nkb4(prob);
            const CUtensorMap* ta = &p.ta[prob];
            const CUtensorMap* tb = &p.tb[prob];
            const uint64_t ahint = p.g[cluster_id][gi] >= 0x400u ? EV_FIRST : EV_NORMAL;
            TL(1, item);
            if (prob == 5) {
              uint32_t seen = 0;
              cnt_wait_bit(CNT_OB + (rt >> 2), 32u << (rt & 3) * 8, seen);
              fence_proxy_async_global();
            }
            for (int kb4 = EARLY && gi == 1; kb4 < nkb4; kb4++) {
              uint32_t seen = 0;
#pragma unroll 1
              for (int s = 0; s < 4; s++) {
                const int bs = s ^ (n & 1);
                if (prob == 4 && !(s & 1)) {
                  cnt_wait_bit(CNT_CTX + kb4, 16u << (s * 8), seen);
                  fence_proxy_async_global();
                }
                if (prob == 5 && kb4 == 0) {
                  mbar_wait(s_bar + B_AEMPTY + 8 * bs, (~(n + (s & 1)) >> 1) & 1);
                  if (s == 2) mbar_wait(s_bar + B_QEMPTY + (aswz ? 0 : 8), lastq);
                }
                mbar_wait(s_bar + B_GEMPTY + 8 * s, gphase);
                const uint32_t full = s_bar + B_GFULL + 8 * s;
                mbar_expect_tx(full, 49152);
                tma_load_3d(sbase + OFF_A + ((s * 16384) ^ aswz), ta, 0, rt * 128, kb4 * 4 + s, full, ahint);
                if (prob == 5) {
                  tma_load_3d(sbase + bs * TILE32K, tb, 0, (kb4 * 4 + s) * 64, ngrp0, full, HINT(8 + prob));
                  tma_load_3d(sbase + bs * TILE32K + 16384, tb, 0, (kb4 * 4 + s) * 64, ngrp0 + 2, full, HINT(8 + prob));
                } else {
                  tma_load_3d_mc(sbase + s * TILE32K + rank * 16384, tb, 0, (kb4 * 4 + s) * 64, ngrp0 + rank * 2, full,
                                 (uint16_t)3, HINT(8 + prob));
                }
              }
              gphase ^= 1;
            }
          }
          if (seg == 0 && isB && DO_ATT) {
            int pv_row = 0, pv_col = 0;
            uint64_t pv_hint = 0;
#define ACQ_SLOT(slot, n)                                                              \
  {                                                                                    \
    if ((n) < 2) mbar_wait(s_bar + B_GEMPTY + 8 * (slot), gphase);                     \
    mbar_wait(s_bar + B_AEMPTY + 8 * (slot), (~(n) >> 1) & 1);                         \
  }
#define LOAD_V()                                                                       \
  {                                                                                    \
    const uint32_t vs = 3 - (n & 1);                                                   \
    ACQ_SLOT(vs, n - 1);                                                               \
    mbar_expect_tx(s_bar + B_AFULL + 8 * vs, TILE32K);                                 \
    tma_load_3d(sbase + vs * TILE32K, &p.tv, 0, pv_row, pv_col, s_bar + B_AFULL + 8 * vs, pv_hint); \
  }
#define NEXT_CODE() (nxt < 512 ? p.order[nxt] : nxt + (0x8000u - 512))
            uint32_t code = p.order[blockIdx.x - 2 * NA_CL];
            int it = 0;
            uint32_t seen = 0;
            for (;; it++) {
              if (it == 1) mbar_wait(s_bar + B_STGFREE, 0);
              if (code & 0x8000u) break;
              const int head = code >> 4;
              const int qt = code & 15;
              uint32_t nxt = 0;
              TL(1, 0x1000 | code);
              if (seen < 48) cnt_wait(CNT_QKV + (head >> 1), 48);
              fence_proxy_async_global();
              {
                const int b = it & 1;
                if (it < 2) {
                  mbar_wait(s_bar + B_GEMPTY + 16 * b, gphase);
                  mbar_wait(s_bar + B_GEMPTY + 16 * b + 8, gphase);
                }
                mbar_wait(s_bar + B_QEMPTY + 8 * b, ((it >> 1) & 1) ^ 1);
                mbar_expect_tx(s_bar + B_QFULL + 8 * b, TILE32K);
                tma_load_3d(sbase + OFF_A + b * TILE32K, &p.tq, 0, qt * 128, head * 2, s_bar + B_QFULL + 8 * b, HINT(24));
              }
#pragma unroll 1
              for (int t = qt; t >= 0; t--) {
                if (t == min(qt, 1)) nxt = cnt_next(CNT_QUEUE) + NB_CTA;
                if (t == 0) {
                  code = NEXT_CODE();
                  sts32(s_bar + S_CODE + 4 * ((it + 1) & 7), code);
                  seen = cnt_peek(CNT_QKV + ((code >> 5) & 15));
                }
                ACQ_SLOT(n & 1, n);
                mbar_expect_tx(s_bar + B_AFULL + 8 * (n & 1), TILE32K);
                tma_load_3d(sbase + (n & 1) * TILE32K, &p.tk, 0, t * 128, head * 2, s_bar + B_AFULL + 8 * (n & 1), HINT(t == qt ? 29 : 25));
                if (n) LOAD_V();
                n++;
                pv_row = t * 128;
                pv_col = head * 2;
                pv_hint = HINT(t == qt ? 29 : 26);
              }
            }
            ACQ_SLOT(n & 1, n);
            mbar_arrive(s_bar + B_AFULL + 8 * (n & 1));
            LOAD_V();
            tail = tail_item(code);
            aswz = (it & 1) * TILE32K;
            mbar_wait(s_bar + B_QEMPTY + 8 * (it & 1), ((it >> 1) & 1) ^ 1);
            rsel = (code >> 3) & 1;
            lastq = ((it - 1) >> 1) & 1;
          }
        }
        if (cnt_done(NCTA * 2)) cnt_rearm();
#pragma unroll 1
        for (int s = 0; s < 4; s++) mbar_wait(s_bar + B_GEMPTY + 8 * s, gphase);
        TL(1, 0xFFFF);
      }
    } else if (warp0 == 9) {
      if (elect_one()) {
        TL_DECL;
        uint32_t tail = 0;
        int gi = 0;
        uint32_t rsel = rank, aswz = 0;
        bool rearm = false;
        for (int seg = 0; seg < 2; seg++) {
          for (;;) {
            uint32_t item = p.g[cluster_id][gi++];
            if (item == 0x500u) item = tail;
            if (item >= 0x600u) break;
            const int prob = item >> 8;
            const int rt = ((item >> 4) & 15) * 2 + rsel;
            const int cg = (item & 15) * 4 + (prob == 5 ? 16 : 0);
            const CUtensorMap* tc = &p.tc[prob];
            const int nl = (p.g[cluster_id][gi] >> 8) == 4 && DO_LOCAL ? 8 : 1;
            const int grp = (blockIdx.x & 15) * 2 + ((blockIdx.x >> 4) & 1), r0 = (blockIdx.x >> 5) * 512;
            if (nl > 1) {
              cnt_wait(CNT_QKVB, 192);
              fence_proxy_async_global();
            }
            if (prob >= 4) rearm = cnt_done(NCTA * 2);
            const bool lastt = p.g[cluster_id][gi] >= 0x600u;
#pragma unroll 1
            for (int c = 0; c < 8; c++) {
              const int q = lastt ? c & 3 : c >> 1, w = lastt ? c >> 2 : c & 1;
              const int idx = w * 2 + (q & 1);
              const bool alt = lastt && q >= 2;
              mbar_wait(s_bar + (alt ? B_SFULL2 : B_SFULL) + 8 * idx, lastt ? seg : q >> 1);
              tma_store_4d(tc, sbase + (alt ? OFF_A + ((q * 16384) ^ aswz) + w * 8192 : OFF_STG + idx * 8192),
                           rt * 64 + w * 32, cg + q, HINT(16 + prob));
              bulk_commit();
              if (c > 0 && !lastt) {
                bulk_wait_read<1>();
                mbar_arrive(s_bar + B_SEMPTY + 8 * ((w ^ 1) * 2 + (((c - 1) >> 1) & 1)));
              }
            }
            bulk_wait_read<0>();
            mbar_arrive(s_bar + (lastt ? B_STGFREE : B_SEMPTY + 8 * 3));
#pragma unroll 1
            for (int c = 0; c < nl; c++) {
              if (nl > 1) {
                mbar_wait(s_bar + B_AEMPTY, (c & 1) ^ 1);
                mbar_expect_tx(s_bar + B_AFULL, L_V);
                tma_load_3d(sbase + OFF_STG, &p.tl, 0, r0 + c * 64, grp, s_bar + B_AFULL, HINT(28));
                tma_load_3d(sbase + OFF_STG + L_K, &p.th, 0, r0 + c * 64 - 8, 32 + grp, s_bar + B_AFULL, HINT(28));
                mbar_wait(s_bar + B_AEMPTY + 8, (c & 1) ^ 1);
                mbar_expect_tx(s_bar + B_AFULL + 8, 9216);
                tma_load_3d(sbase + OFF_STG + L_V, &p.th, 0, r0 + c * 64 - 8, 64 + grp, s_bar + B_AFULL + 8, HINT(28));
              }
              if (c) {
                mbar_wait(s_bar + B_OFULL, ~c & 1);
                cnt_signal(CNT_OB + (blockIdx.x >> 5) * 2 + ((c - 1) >> 2), 1u << ((c - 1) & 3) * 8);
              } else if (prob < 4) {
                bulk_wait<0>();
                cnt_signal_done(prob == 3 ? CNT_QKVB : CNT_QKV + (item & 15));
                TL(2, item);
              }
            }
            if (nl > 1) {
              mbar_wait(s_bar + B_OFULL, 1);
              cnt_signal(CNT_OB + (blockIdx.x >> 5) * 2 + 1, 1u << 24);
              TL(2, 0x600);
            }
          }
          if (seg == 0 && isB && DO_ATT) {
            uint32_t code = p.order[blockIdx.x - 2 * NA_CL];
            for (int it = 0; !(code & 0x8000u); it++) {
              aswz = (~it & 1) * TILE32K;
              mbar_wait(s_bar + B_OFULL, it & 1);
              tma_store_3d(&p.to, sbase + OFF_STG, 0, (code & 15) * 128, (code >> 4) * 2, HINT(27));
              bulk_commit();
              const uint32_t nxt = lds32(s_bar + S_CODE + 4 * ((it + 1) & 7));
              bulk_wait_read<0>();
              mbar_arrive(s_bar + B_STGFREE);
              bulk_wait<0>();
              cnt_signal_done(CNT_CTX + (code >> 5), 1u << (code & 16));
              TL(2, 0x1000 | code);
              code = nxt;
            }
            tail = tail_item(code);
            rsel = (code >> 3) & 1;
            if (tail == 0xFFFFu) rearm = cnt_done(NCTA * 2);
          }
        }
        if (rearm) cnt_rearm();
        TL(2, 0xFFFF);
      }
    }
  } else {
    CLUSTER_ARRIVE();
    reg_alloc<REG_C>();
    named_bar_sync(7, 288);
    const int warp = __shfl_sync(0xffffffffu, opaque_tid() >> 5, 0);
    const int wg = warp >> 2;
    const int lane = threadIdx.x & 31;
    TL_DECL;
    TR_DECL;
    uint32_t gphase = 0;
    uint32_t tail = 0, aswz = 0, rot = 0, etgt = warp & 1, stgpar = 1;
    int gi = 0;
    for (int seg = 0; seg < 2; seg++) {
      uint32_t item = p.g[cluster_id][gi++];
      if (item == 0x500u) item = tail;
      if (item < 0x600u) {
        float acc[128];
        uint32_t pk[64];
        int have = 0;
#define G_STORE_CHUNK(q)                                                                               \
  {                                                                                                    \
    const uint32_t st_base = sbase + OFF_STG + wg * 8192 + stg_off(opaque_tid());                      \
    if (have == 2) { _Pragma("unroll") for (int j = 0; j < 16; j++) pk[(q) * 16 + j] = scale_q(pk[(q) * 16 + j]); } \
    mbar_wait(s_bar + B_SEMPTY + 8 * (wg * 2 + ((q) & 1)), (((q) >> 1) & 1) ^ 1);                      \
    _Pragma("unroll") for (int j = 0; j < 4; j++)                                                      \
        stmatrix_x4((st_base ^ (j << 5)) + ((q) & 1) * 8192, pk[(q) * 16 + j * 4],                     \
                    pk[(q) * 16 + j * 4 + 1], pk[(q) * 16 + j * 4 + 2], pk[(q) * 16 + j * 4 + 3]);     \
    fence_proxy_async_smem();                                                                          \
    __syncwarp();                                                                                      \
    mbar_arrive_elect(s_bar + B_SFULL + 8 * (wg * 2 + ((q) & 1)), true);                              \
  }
#define G_STAGE(s) G_STAGE_Y(s, false, false, )
#define G_STAGE_X(s, ...) G_STAGE_Y(s, false, false, __VA_ARGS__)
#define G_STAGE_Y(s, first, last, ...)                                                                    \
  {                                                                                                       \
    mbar_wait_rest(s_bar + B_GFULL + 8 * (s), gphase, gok && (first));                                    \
    TR(9);                                                                                                \
    const uint32_t da = make_desc(DBASE + OFF_A + (((s) * 16384) ^ aswz) + wg * 8192, 16);                \
    const uint32_t db = make_desc(DBASE + ((s) ^ rot) * TILE32K, 8192);                                   \
    named_bar_sync_if(5 + wg, 256, !(first));                                                             \
    wgmma_fence();                                                                                        \
    _Pragma("unroll") for (int k = 0; k < 5; k++) {                                                       \
      __VA_ARGS__;                                                                                        \
      if (k == 0) wgmma_ss_n256_tbo<0, 0>(acc, da, db, !(first));                                         \
      if (k == 1) wgmma_ss_n256_tbo<2, 128>(acc, da, db, 1);                                              \
      if (k == 2) wgmma_ss_n256_tbo<4, 256>(acc, da, db, 1);                                              \
      if (k == 3) wgmma_ss_n256_tbo<6, 384>(acc, da, db, 1);                                              \
    }                                                                                                     \
    wgmma_commit();                                                                                       \
    named_bar_arrive_if(6 - wg, 256, !(wg ? (last) : (first)));                                           \
    if (!(first)) {                                                                                       \
      wgmma_wait<1>();                                                                                    \
      mbar_arrive_cluster_if(s_bar + B_GEMPTY + 8 * (((s) + 3) & 3), etgt, lane == 0 && (warp & 3) < 2);  \
    }                                                                                                     \
  }
        TL0(item);
        undef_regs(acc);
        {
          constexpr bool gok = false;
          G_STAGE_Y(0, true, false, )
        }
        if (seg == 0) CLUSTER_WAIT();
        undef_regs(pk);
        for (;;) {
          constexpr bool gok = false;
          const int nkb4 = prob_nkb4(item >> 8);
          const uint32_t next = p.g[cluster_id][gi++];
          G_STAGE(1)
          if (have) G_STORE_CHUNK(0)
          G_STAGE(2)
          G_STAGE(3)
          if (have) G_STORE_CHUNK(1)
          gphase ^= 1;
          G_STAGE(0)
          G_STAGE(1)
          if (have) G_STORE_CHUNK(2)
          G_STAGE(2)
          if (have) G_STORE_CHUNK(3)
          G_STAGE_Y(3, false, nkb4 == 2, )
          gphase ^= 1;
          int kb4 = 2;
          if (nkb4 == 16 && DO_LOCAL) {
            constexpr uint32_t aswz = 0, rot = 0;
            G_STAGE(0)
            G_STAGE(1)
            for (; kb4 < 10; kb4++) {
              float ls[36];
              TR(10);
              mbar_wait(s_bar + B_AFULL, kb4 & 1);
              TR(11);
              {
                const uint32_t dq = make_desc(DBASE + OFF_STG + wg * 64, 16);
                G_STAGE_X(2, if (k == 1) wgmma_ss_n72_init(ls, dq, dq + L_K / 16); if (k == 3) wgmma_ss_n72(ls, dq + 2, dq + L_K / 16 + 2, 1))
              }
              mbar_wait(s_bar + B_AFULL + 8, kb4 & 1);
              const int tid = opaque_tid();
              uint32_t vw[16];
              uint4 pw[8];
              {
                const uint32_t va = sbase + OFF_STG + L_V + ((tid >> 4) & 7) * 1024 + wg * 64 + (tid & 15) * 4;
#pragma unroll
                for (int j = 1; j < 16; j++) vw[j] = lds32((va ^ ((j & 7) << 4)) + j * 128);
              }
              G_STAGE(3)
              gphase ^= 1;
              fence_regs(ls);
              mbar_arrive_if(s_bar + B_AEMPTY, (threadIdx.x & 127) == 0);
              {
                const int d = (tid & 3) * 2 - ((tid >> 2) & 7);
                const bool p0 = d > 0, p1 = d >= 0;
                const int w = warp & 3;
                float x0, x1, y0, y1;
#define L_PICK(w_)                                   \
  {                                                  \
    x0 = p0 ? ls[8 * (w_)] : ls[8 * (w_) + 4];       \
    x1 = p1 ? ls[8 * (w_) + 1] : ls[8 * (w_) + 5];   \
    y0 = p0 ? ls[8 * (w_) + 6] : ls[8 * (w_) + 10];  \
    y1 = p1 ? ls[8 * (w_) + 7] : ls[8 * (w_) + 11];  \
  }
                if (w == 0) {
                  if (kb4 == 2 && blockIdx.x < 32) ls[0] = ls[1] = -INFINITY;
                  L_PICK(0)
                } else if (w == 1) L_PICK(1)
                else if (w == 2) L_PICK(2)
                else L_PICK(3)
                constexpr float C = 0.17677669529663687f * 1.4426950408889634f;
                float mx = fmaxf(x0, x1), my = fmaxf(y0, y1);
                mx = fmaxf(mx, __shfl_xor_sync(0xffffffffu, mx, 1));
                my = fmaxf(my, __shfl_xor_sync(0xffffffffu, my, 1));
                mx = -C * fmaxf(mx, __shfl_xor_sync(0xffffffffu, mx, 2));
                my = -C * fmaxf(my, __shfl_xor_sync(0xffffffffu, my, 2));
                x0 = ex2(fmaf(x0, C, mx));
                x1 = ex2(fmaf(x1, C, mx));
                y0 = ex2(fmaf(y0, C, my));
                y1 = ex2(fmaf(y1, C, my));
                float sx = x0 + x1, sy = y0 + y1;
                sx += __shfl_xor_sync(0xffffffffu, sx, 1);
                sy += __shfl_xor_sync(0xffffffffu, sy, 1);
                sx += __shfl_xor_sync(0xffffffffu, sx, 2);
                sy += __shfl_xor_sync(0xffffffffu, sy, 2);
                sx = rcp(sx);
                sy = rcp(sy);
                const uint32_t pa = sbase + OFF_STG + L_P + (tid >> 5) * 512 + (tid & 31) * 8;
                sts64(pa, x0 * sx, x1 * sx);
                sts64(pa + 256, y0 * sy, y1 * sy);
                __syncwarp();
              }
              const uint32_t pr = sbase + OFF_STG + L_P + (tid >> 4) * 256;
              uint32_t* dst = reinterpret_cast<uint32_t*>(p.ob) + (blockIdx.x & 15) * (SEQ * 32) + wg * 16 + (tid & 15) +
                              (((blockIdx.x >> 5) * 512 + (kb4 - 2) * 64 + ((tid >> 4) & 7) * 8) * 2 + ((blockIdx.x >> 4) & 1)) * 32;
#define L_PV(g0)                                                                                       \
  _Pragma("unroll") for (int g = (g0); g < (g0) + 4; g++) {                                            \
    const uint4 a = pw[2 * (g & 3)], b = pw[2 * (g & 3) + 1];                                          \
    const uint32_t w[8] = {a.x, a.y, a.z, a.w, b.x, b.y, b.z, b.w};                                    \
    float o0 = 0.f, o1 = 0.f;                                                                          \
    _Pragma("unroll") for (int c = 0; c < 8; c++) {                                                    \
      const uint32_t u = vw[c > g ? c : c + 8];                                                        \
      o0 = fmaf(__uint_as_float(w[c]), __uint_as_float(u << 16), o0);                                  \
      o1 = fmaf(__uint_as_float(w[c]), __uint_as_float(u & 0xFFFF0000u), o1);                          \
    }                                                                                                  \
    dst[g * 64] = pack_bf16(o0, o1);                                                                   \
  }
#pragma unroll
              for (int j = 0; j < 8; j++) pw[j] = lds128(pr + j * 16);
              mbar_arrive_elect(s_bar + B_AEMPTY + 8, true);
              G_STAGE(0)
              L_PV(0)
#pragma unroll
              for (int j = 0; j < 8; j++) pw[j] = lds128(pr + 128 + j * 16);
              G_STAGE(1)
              L_PV(4)
              __syncwarp();
              mbar_arrive_elect(s_bar + B_OFULL, true);
            }
            G_STAGE(2)
            G_STAGE(3)
            gphase ^= 1;
            kb4++;
          }
          const bool fin = next >= 0x600u;
          for (; kb4 < nkb4 - fin; kb4++) {
            G_STAGE(0)
            G_STAGE(1)
            G_STAGE(2)
            G_STAGE_Y(3, false, kb4 + 1 == nkb4, )
            gphase ^= 1;
          }
          if (fin) break;
          wgmma_wait<0>();
          mbar_arrive_cluster_if(s_bar + B_GEMPTY + 8 * 3, etgt, lane == 0 && (warp & 3) < 2);
          {
            const bool gok = mbar_test(s_bar + B_GFULL, gphase);
            fence_regs(acc);
#pragma unroll
            for (int j = 0; j < 64; j++) pk[j] = pack_bf16(acc[2 * j], acc[2 * j + 1]);
            have = item < 0x100u ? 2 : 1;
            item = next;
            TL0(item);
            G_STAGE_Y(0, true, false, )
          }
        }
        {
          constexpr bool gok = false;
          G_STAGE(0)
          G_STAGE(1)
          wgmma_wait<0>();
          mbar_arrive_cluster_if(s_bar + B_GEMPTY + 8 * (FS - 1), etgt, lane == 0 && (warp & 3) < 2);
          fence_regs(acc);
          float lo[64], hi[64];
#pragma unroll
          for (int j = 0; j < 64; j++) {
            asm volatile("mov.b32 %0, %1;" : "=f"(lo[j]) : "f"(acc[j]));
            asm volatile("mov.b32 %0, %1;" : "=f"(hi[j]) : "f"(acc[64 + j]));
          }
#pragma unroll
          for (int s = FS; s < 4; s++) {
            mbar_wait(s_bar + B_GFULL + 8 * s, gphase);
            const uint32_t da = make_desc(DBASE + OFF_A + ((s * 16384) ^ aswz) + wg * 8192, 16);
            const uint32_t db = make_desc(DBASE + (s ^ rot) * TILE32K, 8192);
            if (s == FS) named_bar_sync(5 + wg, 256);
            wgmma_fence();
            wgmma_ss_n128_tb<0, 0>(lo, da, db, 1);
            wgmma_ss_n128_tb<2, 128>(lo, da, db, 1);
            wgmma_ss_n128_tb<4, 256>(lo, da, db, 1);
            wgmma_ss_n128_tb<6, 384>(lo, da, db, 1);
            wgmma_commit();
          }
          wgmma_fence();
#pragma unroll
          for (int s = FS; s < 4; s++) {
            const uint32_t da = make_desc(DBASE + OFF_A + ((s * 16384) ^ aswz) + wg * 8192, 16);
            const uint32_t db = make_desc(DBASE + (s ^ rot) * TILE32K, 8192);
            wgmma_ss_n128_tb<0, 1024>(hi, da, db, 1);
            wgmma_ss_n128_tb<2, 1152>(hi, da, db, 1);
            wgmma_ss_n128_tb<4, 1280>(hi, da, db, 1);
            wgmma_ss_n128_tb<6, 1408>(hi, da, db, 1);
          }
          wgmma_commit();
          named_bar_arrive_if(6, 256, wg == 0);
          gphase ^= 1;
          const uint32_t so = sbase + stg_off(opaque_tid());
          mbar_wait(s_bar + B_STGFREE, stgpar);
          mbar_wait(s_bar + B_SEMPTY + 16 * wg, 1);
          mbar_wait(s_bar + B_SEMPTY + 16 * wg + 8, 1);
#define FIN_HALF(x, base, stride, bar)                                                                                \
  fence_regs(x);                                                                                                      \
  _Pragma("unroll") for (int j = 0; j < 8; j++)                                                                       \
      stmatrix_x4(((base) ^ ((j & 3) << 5)) + (j >> 2) * (stride), pack_bf16(x[8 * j], x[8 * j + 1]),                 \
                  pack_bf16(x[8 * j + 2], x[8 * j + 3]), pack_bf16(x[8 * j + 4], x[8 * j + 5]), pack_bf16(x[8 * j + 6], x[8 * j + 7])); \
  fence_proxy_async_smem();                                                                                           \
  __syncwarp();                                                                                                       \
  mbar_arrive_elect(s_bar + (bar) + 16 * wg, true);                                                                   \
  mbar_arrive_elect(s_bar + (bar) + 16 * wg + 8, true);
          wgmma_wait<1>();
          FIN_HALF(lo, so + OFF_STG + wg * 8192, 8192, B_SFULL)
          wgmma_wait<0>();
          TRI(12, 8);
#pragma unroll
          for (int s = FS; s < 4; s++) mbar_arrive_cluster_if(s_bar + B_GEMPTY + 8 * s, etgt, lane == 0 && (warp & 3) < 2);
          FIN_HALF(hi, so + OFF_A + (32768 ^ aswz), 16384, B_SFULL2)
          TRI(12, 10);
        }
      }
      if (seg == 0 && isB && DO_ATT) {
        float o[64], s[64];
        uint32_t pa[32], pb[32];
        undef_regs(o);
        undef_regs(s);
        undef_regs(pa);
        undef_regs(pb);
        uint32_t phase = 0;
        const bool sig = (threadIdx.x & 127) == 0;
        if (wg == 1) named_bar_arrive(1, 256);

#define ISSUE_PV(pr, slot_)                                                             \
  {                                                                                     \
    const uint32_t dv = make_desc(DBASE + (slot_) * TILE32K, 16384);                    \
    if (!(pfirst && wg == HW)) {                                                        \
      wgmma_fence();                                                                    \
      _Pragma("unroll") for (int k = 0; k < 8; k++)                                     \
          wgmma_rs_n128_tb(o, pr[4 * k], pr[4 * k + 1], pr[4 * k + 2], pr[4 * k + 3], dv + k * 128, (k != 0) || !pfirst); \
      wgmma_commit();                                                                   \
    } else {                                                                            \
      wgmma_fence();                                                                    \
      _Pragma("unroll") for (int k = 0; k < 4; k++)                                     \
          wgmma_rs_n128_tb(o, pr[16 + 4 * k], pr[17 + 4 * k], pr[18 + 4 * k], pr[19 + 4 * k], dv + k * 128, k != 0); \
      wgmma_commit();                                                                   \
    }                                                                                   \
  }
#define EPILOGUE(on_)                                                                             \
  _Pragma("unroll") for (int j = 0; j < 8; j++) {                                                 \
    const int b = j * 8;                                                                          \
    stmatrix_x4_p((st_o ^ ((j & 3) << 5)) + (j >> 2) * 16384,                                     \
                  pack_bf16(o[b] * sc0, o[b + 1] * sc0), pack_bf16(o[b + 2] * sc1, o[b + 3] * sc1),   \
                  pack_bf16(o[b + 4] * sc0, o[b + 5] * sc0), pack_bf16(o[b + 6] * sc1, o[b + 7] * sc1), on_); \
  }
#define PUBLISH_O()                                  \
  {                                                  \
    fence_proxy_async_smem();                        \
    __syncwarp();                                    \
    mbar_arrive_elect(s_bar + B_OFULL, true);        \
  }
#define FINAL_SCALE()     \
  {                                                    \
    sc0 += __shfl_xor_sync(0xffffffffu, sc0, 1);       \
    sc1 += __shfl_xor_sync(0xffffffffu, sc1, 1);       \
    sc0 += __shfl_xor_sync(0xffffffffu, sc0, 2);       \
    sc1 += __shfl_xor_sync(0xffffffffu, sc1, 2);       \
    sc0 = rcp(sc0);            \
    sc1 = rcp(sc1);                                    \
  }
        float l0 = 1.f, l1 = 1.f, t0 = 1.f, t1 = 1.f;
        float b0 = 0.f, b1 = 0.f, sc0 = 0.f, sc1 = 0.f;
        int gen = 0;
        int pfirst = 1;
        int fresh = 1;
        int opub = 0;
        int last = 0;
        float rdy = -0.f;
        float x0 = 0.f, x1 = 0.f, x2 = 0.f, x3 = 0.f;
        bool rs = false;
        uint32_t code = p.order[blockIdx.x - 2 * NA_CL];
        int it = -1, nit = 0, rem = -1;
        const float mrow = float((warp & 3) * 16 + (lane >> 2) - (lane & 3) * 2);
        const float lo0 = mrow < 0.f && wg == HW ? 0.f : SM_LO;
        const uint32_t st_o = sbase + OFF_STG + stg_off(opaque_tid() ^ (HW * 128));
#define MMA_PART(N_, acc_, PIN, PAR)                                                                       \
  {                                                                                                        \
    const uint32_t dq = make_desc(DBASE + OFF_A + (it & 1) * TILE32K + (wg ^ HW) * 8192, 16);              \
    const uint32_t dk = make_desc(DBASE + (PAR) * TILE32K, 16);                                            \
    TRI(0, fresh ? 7 : 0);                                                                                 \
    named_bar_sync(1 + wg, 256);                                                                           \
    TRI(1, fresh ? 6 : 1);                                                                                 \
    wgmma_fence();                                                                                         \
    uint32_t cv;                                                                                           \
    bool rv;                                                                                               \
    _Pragma("unroll") for (int k = 0; k < 8; k++) {                                                        \
      wgmma_ss_n##N_(acc_, dq + (k >> 2) * 1024 + (k & 3) * 2, dk + (k >> 2) * 1024 + (k & 3) * 2, k != 0 || gen); \
      if (k == 1) cv = lds32(s_bar + S_CODE + 4 * ((it + 1) & 7));        \
      if (k == 3) rv = mbar_test(s_bar + B_AFULL + 8 * (3 - (PAR)), phase ^ (1 - (PAR)));                  \
    }                                                                                                      \
    wgmma_commit();                                                                                        \
    code = __reduce_or_sync(0xffffffffu, cv);                                                              \
    if (N_ == 128 && opub) PUBLISH_O();                                                                    \
    if (N_ == 128 && fresh) FINAL_SCALE();                                                                 \
    last = rem == 0 && (code & 0x8000u);                                                                   \
    nit = it + (rem == 0 && !last);                                                                        \
    mbar_wait_rest(s_bar + B_AFULL + 8 * (3 - (PAR)), phase ^ (1 - (PAR)), rv);                            \
    ISSUE_PV(PIN, 3 - (PAR));                                                                              \
    named_bar_arrive(2 - wg, 256);                                                                         \
    TR(2);                                                                                                 \
    wgmma_wait<1>();                                                                                       \
    fence_regs(acc_);                                                                                      \
    TR(3);                                                                                                 \
    mbar_arrive_if(s_bar + B_AEMPTY + 8 * (PAR), sig);                                                     \
    mbar_arrive_if(s_bar + B_QEMPTY + 8 * (it & 1), sig && rem == 0);                                      \
    rs = mbar_test(s_bar + B_STGFREE, ~it & 1) | (it == 0);                                                \
    l0 = t0;                                                                                               \
    l1 = t1;                                                                                               \
  }
#define LOW_SUM() ((t0 < lo0) | (t1 < SM_LO))
#define SECOND_HALF(POUT, PAR, FRESH, ...)                                                                 \
  wgmma_wait<0>();                                                                                         \
  fence_regs(o);                                                                                           \
  mbar_arrive_if(s_bar + B_AEMPTY + 8 * (3 - (PAR)), sig && ((PAR) || !(FRESH) || it > 0));                \
  rdy = mbar_test2(s_bar + B_AFULL + 8 * (1 - (PAR)), phase ^ (PAR), s_bar + B_QFULL + 8 * (nit & 1), (nit >> 1) & 1); \
  TR(8);                                                                                                   \
  __VA_ARGS__;                                                                                             \
  t0 += x0 + x1;                                                                                           \
  t1 += x2 + x3;                                                                                           \
  POUT[16] = pack_bf16(x0, x1);                                                                            \
  POUT[17] = pack_bf16(x2, x3);                                                                            \
  softmax_exp<9, TPOS, false>(s, 0.f, 0.f, POUT, t0, t1);                                                  \
  t0 = addv(t0, rdy);                                                                                      \
  softmax_exp<TPOS, 16, false>(s, 0.f, 0.f, POUT, t0, t1);                                                 \
  opub = (FRESH) && it > 0 && wg != HW;                                                                    \
  pfirst = FRESH;                                                                                          \
  fresh = 0;                                                                                               \
  rem--;                                                                                                   \
  if (PAR) phase ^= 1;                                                                                     \
                                              \
  const float lim = __uint_as_float(__float_as_uint(rem < 0 || gen ? -1.f : SM_HI) | __float_as_uint(rdy)); \
  TR(4);
#define TPOS 14
#define STEP_END(POUT, PAR, NEXT, ...)                                                                     \
  if (fresh) {                                                                                             \
    __VA_ARGS__;                                                                                           \
    mbar_wait_rest(s_bar + B_STGFREE, ~it & 1, rs);                                                        \
    SECOND_HALF(POUT, PAR, 1, EPILOGUE(it > 0))                                                            \
    const bool nx = __any_sync(0xffffffffu, !(t0 + t1 <= lim) | LOW_SUM());                               \
    if (wg == HW && it > 0) PUBLISH_O();                                     \
    if (!nx) goto plain##NEXT;                                                                             \
  } else {                                                                                                 \
    SECOND_HALF(POUT, PAR, 0, )                                                                            \
    if (!__any_sync(0xffffffffu, !(t0 + t1 <= lim))) goto plain##NEXT;                                     \
  }
#define STEP_BEGIN(PIN, POUT, PAR, ...)                                                                    \
  {                                                                                                        \
    if (__any_sync(0xffffffffu, !(t0 + t1 <= SM_HI) | (LOW_SUM() & (pfirst != 0)))) {                           \
              \
      if (pfirst && wg == HW) { _Pragma("unroll") for (int j = 0; j < 32; j++) asm volatile("mov.b32 %0, 0xff800000;" : "=f"(s[j])); } \
      float d0, d1;                                                                                        \
      softmax_max(s, d0, d1);                                                                              \
      if (!pfirst) {                                                                                       \
        d0 = fmaxf(d0, 0.f);                                                                               \
        d1 = fmaxf(d1, 0.f);                                                                               \
      }                                                                                                    \
      const float r0 = pfirst ? 1.f : ex2(-d0), r1 = pfirst ? 1.f : ex2(-d1);                              \
      t0 = l0 * r0;                                                                                        \
      t1 = l1 * r1;                                                                                        \
      softmax_exp<0, 16, true>(s, -d0, -d1, PIN, t0, t1);                                                  \
      b0 -= d0;                                                                                            \
      b1 -= d1;                                                                                            \
      gen = 1;                                                                                             \
      _Pragma("unroll") for (int j = 0; j < 16; j++) {                                                     \
        o[4 * j] *= r0;                                                                                    \
        o[4 * j + 1] *= r0;                                                                                \
        o[4 * j + 2] *= r1;                                                                                \
        o[4 * j + 3] *= r1;                                                                                \
      }                                                                                                    \
    }                                                                                                      \
    if (last) {                                                                                            \
      __VA_ARGS__;                                                                                         \
      break;                                                                                               \
    }                                                                                                      \
    fresh = rem < 0;                                                                                       \
    it = nit;                                                                                              \
    if (fresh) {                                                                                           \
      TL0(0x1000 | code);                                                                                  \
      rem = code & 15;                                                                                     \
      sc0 = t0;                                                                                            \
      sc1 = t1;                                                                                            \
      t0 = t1 = 0.f;                                                                                       \
    }                                                                                                      \
    if (gen) {                                                      \
      _Pragma("unroll") for (int j = 0; j < 64; j++) asm volatile("mov.b32 %0, %1;" : "=f"(s[j]) : "f"((j & 2) ? b1 : b0)); \
    }                                                                                                      \
    mbar_wait_rest(s_bar + B_AFULL + 8 * (PAR), phase, __float_as_uint(rdy) == 0);                         \
    mbar_wait_rest(s_bar + B_QFULL + 8 * (it & 1), (it >> 1) & 1, __float_as_uint(rdy) == 0);              \
  }                                                                                                        \
  if (fresh && wg == HW) {                                                                                 \
                                                     \
    float sl[32];                                                                                          \
    _Pragma("unroll") for (int j = 0; j < 32; j++) asm volatile("mov.b32 %0, %1;" : "=f"(sl[j]) : "f"(s[32 + j])); \
    MMA_PART(64, sl, PIN, PAR)                                                                             \
    _Pragma("unroll") for (int j = 0; j < 32; j++) asm volatile("mov.b32 %0, %1;" : "=f"(s[32 + j]) : "f"(sl[j])); \
    FINAL_SCALE();                                                                                         \
    _Pragma("unroll") for (int j = 0; j < 8; j++) {                                                        \
      if (float(8 * j) > mrow) s[32 + 4 * j] = -3e38f;                                                     \
      if (float(8 * j + 1) > mrow) s[33 + 4 * j] = -3e38f;                                                 \
      if (float(8 * j - 8) > mrow) s[34 + 4 * j] = -3e38f;                                                 \
      if (float(8 * j - 7) > mrow) s[35 + 4 * j] = -3e38f;                                                 \
    }                                                                                                      \
    x0 = ex2v(s[32]), x1 = ex2v(s[33]), x2 = ex2v(s[34]), x3 = ex2v(s[35]);                                \
  } else {                                                                                                 \
  plain##PAR:                                                                                              \
    MMA_PART(128, s, PIN, PAR)                                                                             \
    if (fresh) {                                                                                           \
                                     \
      _Pragma("unroll") for (int j = 0; j < 8; j++) {                                                      \
        s[32 + 4 * j] = fmaf(__saturatef(float(8 * j) - mrow), -3e38f, s[32 + 4 * j]);                     \
        s[33 + 4 * j] = fmaf(__saturatef(float(8 * j + 1) - mrow), -3e38f, s[33 + 4 * j]);                 \
        s[34 + 4 * j] = fmaf(__saturatef(float(8 * j - 8) - mrow), -3e38f, s[34 + 4 * j]);                 \
        s[35 + 4 * j] = fmaf(__saturatef(float(8 * j - 7) - mrow), -3e38f, s[35 + 4 * j]);                 \
      }                                                                                                    \
      softmax_exp<0, 8, false>(s, 0.f, 0.f, POUT, t0, t1);                                                 \
      x0 = ex2v(s[32]), x1 = ex2v(s[33]), x2 = ex2v(s[34]), x3 = ex2v(s[35]);                              \
    } else {                                                                                               \
      softmax_exp<0, 8, false>(s, 0.f, 0.f, POUT, t0, t1);                                                 \
      x0 = ex2v(s[32]), x1 = ex2v(s[33]), x2 = ex2v(s[34]), x3 = ex2v(s[35]);                              \
    }                                                                                                      \
  }
        for (;;) {
          STEP_END(pa, 1, 0, if (it < 0) { wgmma_wait<0>(); goto begin0; })
        begin0:
          STEP_BEGIN(pa, pb, 0, rot = 0; phase ^= 1)
          STEP_END(pb, 0, 1, )
          STEP_BEGIN(pb, pa, 1, rot = 1; _Pragma("unroll") for (int j = 0; j < 32; j++) asm volatile("mov.b32 %0, %1;" : "=r"(pa[j]) : "r"(pb[j])))
        }
        {
          mbar_wait(s_bar + B_AFULL + 8 * (3 - rot), phase);
          TRI(12, 2);
          ISSUE_PV(pa, 3 - rot);
          if (opub) PUBLISH_O();
          sc0 = t0;
          sc1 = t1;
          FINAL_SCALE();
          mbar_wait(s_bar + B_STGFREE, it & 1);
          wgmma_wait<0>();
          fence_regs(o);
          TRI(12, 4);
          mbar_arrive_if(s_bar + B_AEMPTY + 8 * (3 - rot), sig);
          EPILOGUE(true);
          PUBLISH_O();
          TRI(12, 5);
          stgpar = ~it & 1;
          tail = tail_item(code);
          aswz = (~it & 1) * TILE32K;
          etgt = blockIdx.x & 1;
        }
      }
    }
    TL0(0xFFFF);
    TRI(15, 15);
  }
}

typedef CUresult (*EncodeFn)(CUtensorMap*, CUtensorMapDataType, cuuint32_t, void*, const cuuint64_t*,
                             const cuuint64_t*, const cuuint32_t*, const cuuint32_t*, CUtensorMapInterleave,
                             CUtensorMapSwizzle, CUtensorMapL2promotion, CUtensorMapFloatOOBfill);

EncodeFn get_encode() {
  static EncodeFn fn = nullptr;
  if (!fn) {
    void* p = nullptr;
    cudaDriverEntryPointQueryResult st;
    cudaGetDriverEntryPoint("cuTensorMapEncodeTiled", &p, cudaEnableDefault, &st);
    fn = (EncodeFn)p;
  }
  return fn;
}

void make_map(CUtensorMap* m, const void* ptr, int rows, int cols, int box_rows, int box_groups, bool blocked = false) {
  cuuint64_t dims[3] = {64, (cuuint64_t)rows, (cuuint64_t)(cols / 64)};
  cuuint64_t strides[2] = {(cuuint64_t)(blocked ? 128 : cols * 2), (cuuint64_t)(blocked ? rows * 128 : 128)};
  cuuint32_t box[3] = {64, (cuuint32_t)box_rows, (cuuint32_t)box_groups};
  cuuint32_t es[3] = {1, 1, 1};
  CUtensorMapL2promotion prom = blocked || box_groups == 1 ? CU_TENSOR_MAP_L2_PROMOTION_NONE : CU_TENSOR_MAP_L2_PROMOTION_L2_256B;
  get_encode()(m, CU_TENSOR_MAP_DATA_TYPE_BFLOAT16, 3, const_cast<void*>(ptr), dims, strides, box, es,
               CU_TENSOR_MAP_INTERLEAVE_NONE, CU_TENSOR_MAP_SWIZZLE_128B, prom,
               CU_TENSOR_MAP_FLOAT_OOB_FILL_NONE);
}

void make_store_map(CUtensorMap* m, const void* ptr, int cols, uint64_t s_par, uint64_t s_pair, uint64_t s_grp) {
  cuuint64_t dims[4] = {64, 2, SEQ / 2, (cuuint64_t)(cols / 64)};
  cuuint64_t strides[3] = {s_par, s_pair, s_grp};
  cuuint32_t box[4] = {64, 2, 32, 1};
  cuuint32_t es[4] = {1, 1, 1, 1};
  get_encode()(m, CU_TENSOR_MAP_DATA_TYPE_BFLOAT16, 4, const_cast<void*>(ptr), dims, strides, box, es,
               CU_TENSOR_MAP_INTERLEAVE_NONE, CU_TENSOR_MAP_SWIZZLE_128B, CU_TENSOR_MAP_L2_PROMOTION_NONE,
               CU_TENSOR_MAP_FLOAT_OOB_FILL_NONE);
}

#define PARAM(name, val) const int name = val
void build_schedule(Params& p) {
  PARAM(C_KB, 1028);
  PARAM(C_TILE, 10);
  PARAM(C_QX, 0);
  PARAM(C_START, 4500);
  PARAM(C_STEP, 2052);
  PARAM(C_ITEM, 300);
  PARAM(C_LAG, 8000);
  PARAM(C_SP, 5200);
  PARAM(C_TAIL, 22000);
  PARAM(C_SHORT, 0);
  PARAM(C_AT, 72);
  PARAM(C_LATE, 0);
  PARAM(C_LMASK, 0xAA0);
  PARAM(C_AM, 100);
  PARAM(C_ODD, 1300);
  PARAM(C_READY, 10000);
  auto gemm_cost = [&](int prob) {
    static const int nkb[NPROB] = {16, 8, 8, 16, 64, 16};
    return nkb[prob] * C_KB + C_TILE + (prob == 0 ? C_QX : 0);
  };
  memset(p.g, 0xFF, sizeof(p.g));
  int n1[NCLUSTER];
  long t1[NCLUSTER];
  long ready[16];
  for (int c = 0; c < NCLUSTER; c++) { n1[c] = 0; t1[c] = C_START; }
  for (int i = 0; i < 16; i++) ready[i] = 0;
  auto add = [&](int c, int prob, int mp, int nt) {
    p.g[c][n1[c]++] = (uint16_t)((prob << 8) | (mp << 4) | nt);
    t1[c] += gemm_cost(prob);
    if (prob < 3) {
      const long r = t1[c] + C_READY;
      if (r > ready[nt]) ready[nt] = r;
    }
  };
  for (int r = 0; r < 8; r++)
    for (int c = 0; c < NA_CL; c++) {
      const int mp = c & 7, nt = 2 * r + ((c >> 3) & 1);
      for (int j = 0; j < (c < 16 ? 1 : 2); j++) {
        add(c, c < 16 ? 0 : 1 + j, mp, nt);
      }
    }
  long tA = 0;
  for (int c = 0; c < NA_CL; c++) {
    if (t1[c] > tA) tA = t1[c];
    add(c, 4, c & 7, c >> 3);
  }
  for (int i = 0; i < 96; i++) add(NA_CL + i % (NCLUSTER - NA_CL), 3, i % 8, i / 8);
  for (int c = NA_CL; c < NCLUSTER; c++) {
    p.g[c][n1[c]++] = 0x600;
    p.g[c][n1[c]++] = 0x500;
  }
  long tf[NB_CTA];
  bool done[512], started[NB_CTA];
  long fin[16];
  for (int c = 0; c < NB_CTA; c++) { tf[c] = t1[NA_CL + (c >> 1)] + 2000; started[c] = false; }
  for (int i = 0; i < 512; i++) done[i] = false;
  for (int i = 0; i < 16; i++) fin[i] = 0;
  auto alen = [&](int qt) { return (long)(qt + 1) * C_STEP + C_ITEM + (qt < 2 ? C_SHORT : 0); };
  int nq = NB_CTA;
  for (int n = 0; n < 512; n++) {
    int cb = 0;
    for (int c = 1; c < NB_CTA; c++)
      if (tf[c] < tf[cb]) cb = c;
    int best = -1;
    long bkey = 0;
    for (int i = 0; i < 512; i++) {
      if (done[i]) continue;
      const int hp = i >> 5;
      long dl = -(long)(16 - hp) * C_SP - C_LAG + ((i >> 4) & 1) * C_ODD;
      if (dl > -C_TAIL) dl = -C_TAIL;
      long key = dl - alen(i & 15) * (dl == -C_TAIL ? C_AT : C_AM) / 100;
      if ((i >> 4) == 31 && (C_LMASK >> (i & 15) & 1)) key += C_LATE;
      if (ready[hp] > tf[cb]) key += (1L << 40) + (ready[hp] - tf[cb]) * 1024;
      if (best < 0 || key < bkey) { best = i; bkey = key; }
    }
    done[best] = true;
    if (!started[cb]) { p.order[cb] = (uint16_t)best; started[cb] = true; }
    else p.order[nq++] = (uint16_t)best;
    if (ready[best >> 5] > tf[cb]) tf[cb] = ready[best >> 5];
    tf[cb] += alen(best & 15);
    if (tf[cb] + C_LAG > fin[best >> 5]) fin[best >> 5] = tf[cb] + C_LAG;
  }
}

}

extern "C" void kernel_launch(void* const* d_in, const int* in_sizes, int n_in, void* d_out, int out_size) {
  const bf16* A_x = (const bf16*)d_in[0];
  const bf16* A_c = (const bf16*)d_in[1];
  const bf16* A_wq = (const bf16*)d_in[2];
  const bf16* A_wuk = (const bf16*)d_in[3];
  const bf16* A_wuv = (const bf16*)d_in[4];
  const bf16* A_wo = (const bf16*)d_in[5];
  const bf16* B_x = (const bf16*)d_in[6];
  const bf16* B_wqkv = (const bf16*)d_in[7];
  const bf16* B_wo = (const bf16*)d_in[8];
  bf16* out = (bf16*)d_out;

  static Params p;
  static bf16 *q, *k, *v, *ctx, *qkvb, *ob;
  static bool init = false;
  if (!init) {
    cudaGetSymbolAddress((void**)&q, g_q);
    cudaGetSymbolAddress((void**)&k, g_k);
    cudaGetSymbolAddress((void**)&v, g_v);
    cudaGetSymbolAddress((void**)&qkvb, g_qkvb);
    cudaGetSymbolAddress((void**)&ob, g_ob);
    cudaFuncSetAttribute(mega_kernel, cudaFuncAttributeMaxDynamicSharedMemorySize, SMEM_BYTES);
    build_schedule(p);
    ctx = q;
    init = true;
  }
  make_map(&p.ta[0], A_x, SEQ, DM, 128, 1);
  make_map(&p.tb[0], A_wq, DM, HHD, 64, 2);
  make_store_map(&p.tc[0], q, HHD, 128, 256, SEQ * 128);
  make_map(&p.ta[1], A_c, SEQ, DC, 128, 1);
  make_map(&p.tb[1], A_wuk, DC, HHD, 64, 2);
  make_store_map(&p.tc[1], k, HHD, 128, 256, SEQ * 128);
  make_map(&p.ta[2], A_c, SEQ, DC, 128, 1);
  make_map(&p.tb[2], A_wuv, DC, HHD, 64, 2);
  make_store_map(&p.tc[2], v, HHD, 128, 256, SEQ * 128);
  make_map(&p.ta[3], B_x, SEQ, DM, 128, 1);
  make_map(&p.tb[3], B_wqkv, DM, 3 * DM, 64, 2);
  make_store_map(&p.tc[3], qkvb, 3 * DM, SEQ * 64, 128, SEQ * 128);
  make_map(&p.ta[4], ctx, SEQ, HHD, 128, 1, true);
  make_map(&p.tb[4], A_wo, HHD, DM, 64, 2);
  make_store_map(&p.tc[4], out, 2 * DM, 4 * DM, 8 * DM, 128);
  make_map(&p.ta[5], ob, SEQ, DM, 128, 1, true);
  make_map(&p.tb[5], B_wo, DM, DM, 64, 2);
  make_store_map(&p.tc[5], out, 2 * DM, 4 * DM, 8 * DM, 128);
  make_map(&p.tq, q, SEQ, HHD, 128, 2, true);
  make_map(&p.tk, k, SEQ, HHD, 128, 2, true);
  make_map(&p.tv, v, SEQ, HHD, 128, 2, true);
  make_map(&p.tl, qkvb, SEQ / 2, 6 * DM, 64, 1, true);
  make_map(&p.th, qkvb, SEQ / 2, 6 * DM, 72, 1, true);
  make_map(&p.to, ctx, SEQ, HHD, 128, 2, true);
  p.ob = ob;
  mega_kernel<<<NCTA, 384, SMEM_BYTES, cudaStreamPerThread>>>(p);
}
```

```cpp
#include <cuda_runtime.h>
#include <cuda_bf16.h>
#include <cuda.h>
#include <stdint.h>
#include <string.h>

namespace {

typedef __nv_bfloat16 bf16;

constexpr int SEQ = 2048;
constexpr int NHEAD = 32;
constexpr int HD = 128;
constexpr int DM = 1024;
constexpr int DC = 512;
constexpr int HHD = NHEAD * HD;

__device__ __align__(1024) bf16 g_q[SEQ * HHD];
__device__ __align__(1024) bf16 g_k[SEQ * HHD];
__device__ __align__(1024) bf16 g_v[SEQ * HHD];
__device__ __align__(1024) bf16 g_qkvb[SEQ * 3 * DM];
__device__ __align__(1024) bf16 g_ob[SEQ * DM];
constexpr int CNT_QKV = 0, CNT_CTX = 16, CNT_QKVB = 32, CNT_DONE = 33, CNT_QUEUE = 34, CNT_OB = 35, CNT_N = 39;
__device__ uint32_t g_cnt[CNT_N * 8];
#ifdef TIMELINE
__device__ __align__(16) unsigned long long g_tl[132 * 4 * 64];
#endif


__device__ __forceinline__ uint32_t smem_u32(const void* p) {
  return static_cast<uint32_t>(__cvta_generic_to_shared(p));
}
__device__ __forceinline__ void mbar_init(uint32_t bar, uint32_t count) {
  asm volatile("mbarrier.init.shared::cta.b64 [%0], %1;" ::"r"(bar), "r"(count) : "memory");
}
__device__ __forceinline__ void mbar_expect_tx(uint32_t bar, uint32_t bytes) {
  asm volatile("mbarrier.arrive.expect_tx.shared::cta.b64 _, [%0], %1;" ::"r"(bar), "r"(bytes) : "memory");
}
__device__ __forceinline__ void mbar_arrive(uint32_t bar) {
  asm volatile("mbarrier.arrive.shared::cta.b64 _, [%0];" ::"r"(bar) : "memory");
}
__device__ __forceinline__ void mbar_arrive_if(uint32_t bar, bool on) {
  asm volatile("{\n.reg .pred p;\nsetp.ne.b32 p, %1, 0;\n@p mbarrier.arrive.shared::cta.b64 _, [%0];\n}" ::"r"(bar),
               "r"((int)on)
               : "memory");
}
__device__ __forceinline__ void mbar_arrive_cluster_if(uint32_t bar, uint32_t cta, bool on) {
  asm volatile(
      "{\n.reg .b32 ra;\n.reg .pred p;\nsetp.ne.b32 p, %2, 0;\nmapa.shared::cluster.u32 ra, %0, %1;\n"
      "@p mbarrier.arrive.shared::cluster.b64 _, [ra];\n}" ::"r"(bar),
      "r"(cta), "r"((int)on)
      : "memory");
}
__device__ __forceinline__ bool mbar_try_wait(uint32_t bar, uint32_t parity) {
  uint32_t ok;
  asm volatile(
      "{\n.reg .pred p;\nmbarrier.try_wait.parity.shared::cta.b64 p, [%1], %2;\nselp.u32 %0, 1, 0, p;\n}"
      : "=r"(ok)
      : "r"(bar), "r"(parity)
      : "memory");
  return ok != 0;
}
__device__ __forceinline__ bool mbar_test(uint32_t bar, uint32_t parity) {
  uint32_t ok;
  asm volatile(
      "{\n.reg .pred p;\nmbarrier.test_wait.parity.shared::cta.b64 p, [%1], %2;\nselp.u32 %0, 1, 0, p;\n}"
      : "=r"(ok)
      : "r"(bar), "r"(parity)
      : "memory");
  return ok != 0;
}
#ifdef DBGW
__device__ uint32_t* g_dbg;
__device__ __forceinline__ void mbar_wait_l(uint32_t bar, uint32_t parity, int line) {
  uint32_t t0 = clock();
  bool rec = false;
  while (!mbar_try_wait(bar, parity)) {
    uint32_t d = clock() - t0;
    if (d > (1u << 26) && !rec) { rec = true; g_dbg[blockIdx.x * 16 + (threadIdx.x >> 5)] = (bar & 1023) | (parity << 12) | (line << 16); __threadfence_system(); }
    if (d > (1u << 28)) __trap();
  }
}
#define mbar_wait(b, p) mbar_wait_l(b, p, __LINE__)
#define DBG(i, v) *(volatile uint32_t*)(g_dbg + blockIdx.x * 16 + (i)) = (v)
__device__ __forceinline__ void mbar_wait_unused(uint32_t bar, uint32_t parity) {
#else
#define DBG(i, v)
__device__ __forceinline__ void mbar_wait(uint32_t bar, uint32_t parity) {
#endif
  asm volatile(
      "{\n.reg .pred p;\n.reg .u32 t;\n"
      "mbarrier.try_wait.parity.shared::cta.b64 p, [%0], %1;\n"
      "@p bra DONE;\n"
      "mov.u32 t, 0x100000;\n"
      "LAB_WAIT:\n"
      "mbarrier.try_wait.parity.shared::cta.b64 p, [%0], %1;\n"
      "@p bra DONE;\n"
      "sub.u32 t, t, 1;\n"
      "setp.ne.u32 p, t, 0;\n"
      "@p bra LAB_WAIT;\n"
      "trap;\n"
      "DONE:\n}" ::"r"(bar),
      "r"(parity)
      : "memory");
}
constexpr uint64_t EV_NORMAL = 0x1000000000000000ull;
__device__ __forceinline__ uint64_t policy_first() {
  uint64_t p;
  asm("createpolicy.fractional.L2::evict_first.b64 %0, 1.0;" : "=l"(p));
  return p;
}
#define EV_FIRST policy_first()
__device__ __forceinline__ void tma_load_3d(uint32_t dst, const CUtensorMap* map, int c0, int c1, int c2,
                                            uint32_t bar, uint64_t hint) {
  asm volatile(
      "cp.async.bulk.tensor.3d.shared::cluster.global.mbarrier::complete_tx::bytes.L2::cache_hint [%0], [%1, {%3, %4, %5}], [%2], %6;" ::"r"(dst),
      "l"(map), "r"(bar), "r"(c0), "r"(c1), "r"(c2), "l"(hint)
      : "memory");
}
__device__ __forceinline__ void tma_load_3d_mc(uint32_t dst, const CUtensorMap* map, int c0, int c1, int c2,
                                               uint32_t bar, uint16_t mask, uint64_t hint) {
  asm volatile(
      "cp.async.bulk.tensor.3d.shared::cluster.global.mbarrier::complete_tx::bytes.multicast::cluster.L2::cache_hint [%0], [%1, {%3, %4, %5}], [%2], %6, %7;" ::"r"(dst),
      "l"(map), "r"(bar), "r"(c0), "r"(c1), "r"(c2), "h"(mask), "l"(hint)
      : "memory");
}
__device__ __forceinline__ void tma_store_3d(const CUtensorMap* map, uint32_t src, int c0, int c1, int c2, uint64_t hint) {
  asm volatile("cp.async.bulk.tensor.3d.global.shared::cta.bulk_group.L2::cache_hint [%0, {%2, %3, %4}], [%1], %5;" ::"l"(map),
               "r"(src), "r"(c0), "r"(c1), "r"(c2), "l"(hint)
               : "memory");
}
__device__ __forceinline__ void tma_store_4d(const CUtensorMap* map, uint32_t src, int c2, int c3, uint64_t hint) {
  asm volatile("cp.async.bulk.tensor.4d.global.shared::cta.bulk_group.L2::cache_hint [%0, {%2, %2, %3, %4}], [%1], %5;" ::"l"(map),
               "r"(src), "r"(0), "r"(c2), "r"(c3), "l"(hint)
               : "memory");
}
__device__ __forceinline__ void bulk_commit() { asm volatile("cp.async.bulk.commit_group;" ::: "memory"); }
template <int N>
__device__ __forceinline__ void bulk_wait_read() {
  asm volatile("cp.async.bulk.wait_group.read %0;" ::"n"(N) : "memory");
}
template <int N>
__device__ __forceinline__ void bulk_wait() {
  asm volatile("cp.async.bulk.wait_group %0;" ::"n"(N) : "memory");
}
__device__ __forceinline__ void fence_proxy_async_smem() {
  asm volatile("fence.proxy.async.shared::cta;" ::: "memory");
}
__device__ __forceinline__ bool elect_one() {
  uint32_t pred;
  asm volatile("{\n.reg .pred P;\nelect.sync _|P, 0xffffffff;\nselp.b32 %0, 1, 0, P;\n}" : "=r"(pred));
  return pred != 0;
}
__device__ __forceinline__ void named_bar_sync(int id, int n) {
  asm volatile("bar.sync %0, %1;" ::"r"(id), "r"(n) : "memory");
}
__device__ __forceinline__ void named_bar_arrive(int id, int n) {
  asm volatile("bar.arrive %0, %1;" ::"r"(id), "r"(n) : "memory");
}
__device__ __forceinline__ void named_bar_sync_if(int id, int n, bool on) {
  asm volatile("{\n.reg .pred p;\nsetp.ne.b32 p, %2, 0;\n@p bar.sync %0, %1;\n}" ::"r"(id), "r"(n), "r"((int)on) : "memory");
}
__device__ __forceinline__ void named_bar_arrive_if(int id, int n, bool on) {
  asm volatile("{\n.reg .pred p;\nsetp.ne.b32 p, %2, 0;\n@p bar.arrive %0, %1;\n}" ::"r"(id), "r"(n), "r"((int)on) : "memory");
}
template <int N>
__device__ __forceinline__ void reg_alloc() {
  asm volatile("setmaxnreg.inc.sync.aligned.u32 %0;" ::"n"(N));
}
template <int N>
__device__ __forceinline__ void reg_dealloc() {
  asm volatile("setmaxnreg.dec.sync.aligned.u32 %0;" ::"n"(N));
}
__device__ __forceinline__ void wgmma_fence() { asm volatile("wgmma.fence.sync.aligned;" ::: "memory"); }
__device__ __forceinline__ void wgmma_commit() { asm volatile("wgmma.commit_group.sync.aligned;" ::: "memory"); }
template <int N>
__device__ __forceinline__ void wgmma_wait() {
  asm volatile("wgmma.wait_group.sync.aligned %0;" ::"n"(N) : "memory");
}
template <int N>
__device__ __forceinline__ void fence_regs(float (&d)[N]) {
#pragma unroll
  for (int i = 0; i < N; i++) asm volatile("" : "+f"(d[i])::"memory");
}
__device__ __forceinline__ void fence_regs(uint32_t (&d)[32]) {
#pragma unroll
  for (int i = 0; i < 16; i++) asm volatile("" : "+r"(d[i])::"memory");
}
template <int N>
__device__ __forceinline__ void undef_regs(float (&d)[N]) {
#pragma unroll
  for (int i = 0; i < N; i++) d[i] = 0.f;
}
template <int N>
__device__ __forceinline__ void undef_regs(uint32_t (&d)[N]) {
#pragma unroll
  for (int i = 0; i < N; i++) d[i] = 0u;
}
__device__ __forceinline__ uint32_t pack_bf16(float lo, float hi) {
  uint32_t r;
  asm("cvt.rn.bf16x2.f32 %0, %1, %2;" : "=r"(r) : "f"(hi), "f"(lo));
  return r;
}
__device__ __forceinline__ void stmatrix_x4(uint32_t addr, uint32_t r0, uint32_t r1, uint32_t r2, uint32_t r3) {
  asm volatile("stmatrix.sync.aligned.m8n8.x4.shared.b16 [%0], {%1, %2, %3, %4};" ::"r"(addr), "r"(r0), "r"(r1),
               "r"(r2), "r"(r3)
               : "memory");
}
__device__ __forceinline__ void stmatrix_x4_p(uint32_t addr, uint32_t r0, uint32_t r1, uint32_t r2, uint32_t r3,
                                              bool on) {
  asm volatile("{\n.reg .pred p;\nsetp.ne.b32 p, %5, 0;\n@p stmatrix.sync.aligned.m8n8.x4.shared.b16 [%0], {%1, %2, %3, %4};\n}" ::"r"(addr),
               "r"(r0), "r"(r1), "r"(r2), "r"(r3), "r"((int)on)
               : "memory");
}
__device__ __forceinline__ float ex2(float x) {
  float y;
  asm("ex2.approx.ftz.f32 %0, %1;" : "=f"(y) : "f"(x));
  return y;
}
__device__ __forceinline__ float rcp(float x) {
  float y;
  asm("rcp.approx.ftz.f32 %0, %1;" : "=f"(y) : "f"(x));
  return y;
}
__device__ __forceinline__ float ex2v(float x) {
  float y;
  asm volatile("ex2.approx.ftz.f32 %0, %1;" : "=f"(y) : "f"(x));
  return y;
}
__device__ __forceinline__ float addv(float a, float b) {
  float y;
  asm volatile("add.f32 %0, %1, %2;" : "=f"(y) : "f"(a), "f"(b));
  return y;
}
__device__ __forceinline__ void mbar_arrive_elect(uint32_t bar, bool on) {
  asm volatile("{\n.reg .pred p, q;\nelect.sync _|q, 0xffffffff;\nsetp.ne.and.b32 p, %1, 0, q;\n@p mbarrier.arrive.shared::cta.b64 _, [%0];\n}" ::"r"(bar),
               "r"((int)on)
               : "memory");
}
__device__ __forceinline__ float mbar_test2(uint32_t bar0, uint32_t par0, uint32_t bar1, uint32_t par1) {
  float f;
  asm volatile(
      "{\n.reg .pred p, q;\nmbarrier.test_wait.parity.shared::cta.b64 p, [%1], %2;\n"
      "mbarrier.test_wait.parity.shared::cta.b64 q, [%3], %4;\nand.pred p, p, q;\nselp.f32 %0, 0f00000000, 0f80000000, p;\n}"
      : "=f"(f)
      : "r"(bar0), "r"(par0), "r"(bar1), "r"(par1)
      : "memory");
  return f;
}
__device__ __forceinline__ void mbar_wait_rest(uint32_t bar, uint32_t parity, bool ok) {
  asm volatile(
      "{\n.reg .pred p;\n.reg .u32 t;\n"
      "setp.ne.b32 p, %2, 0;\n"
      "@p bra DONE;\n"
      "mov.u32 t, 0x100000;\n"
      "LAB_WAIT:\n"
      "mbarrier.try_wait.parity.shared::cta.b64 p, [%0], %1;\n"
      "@p bra DONE;\n"
      "sub.u32 t, t, 1;\n"
      "setp.ne.u32 p, t, 0;\n"
      "@p bra LAB_WAIT;\n"
      "trap;\n"
      "DONE:\n}" ::"r"(bar),
      "r"(parity), "r"((int)ok)
      : "memory");
}
__device__ __forceinline__ void send_peer(uint32_t addr, uint32_t bar, uint32_t v) {
  asm volatile(
      "{\n.reg .b32 ra, rb;\nmapa.shared::cluster.u32 ra, %0, 1;\nmapa.shared::cluster.u32 rb, %1, 1;\n"
      "st.async.weak.shared::cluster.mbarrier::complete_tx::bytes.b32 [ra], %2, [rb];\n}" ::"r"(addr),
      "r"(bar), "r"(v)
      : "memory");
}
__device__ __forceinline__ void cnt_signal(int idx, uint32_t inc = 1) {
  asm volatile("red.release.gpu.global.add.u32 [%0], %1;" ::"l"(g_cnt + idx * 8), "r"(inc) : "memory");
}
__device__ __forceinline__ void cnt_signal_done(int idx, uint32_t inc = 1) {
  asm volatile("fence.proxy.async.global;" ::: "memory");
  cnt_signal(idx, inc);
}
__device__ __forceinline__ uint32_t cnt_next(int idx) {
  uint32_t v;
  asm volatile("atom.relaxed.gpu.global.add.u32 %0, [%1], 1;" : "=r"(v) : "l"(g_cnt + idx * 8) : "memory");
  return v;
}
__device__ __forceinline__ uint32_t cnt_peek(int idx) {
  uint32_t v;
  asm volatile("ld.acquire.gpu.global.u32 %0, [%1];" : "=r"(v) : "l"(g_cnt + idx * 8) : "memory");
  return v;
}
__device__ __forceinline__ void cnt_wait(int idx, uint32_t target) {
  asm volatile(
      "{\n.reg .pred p;\n.reg .u32 v, t0, t1;\n"
      "ld.acquire.gpu.global.u32 v, [%0];\n"
      "setp.ge.u32 p, v, %1;\n"
      "@p bra DONE;\n"
      "mov.u32 t0, %%clock;\n"
      "LAB_WAIT:\n"
      "nanosleep.u32 100;\n"
      "ld.acquire.gpu.global.u32 v, [%0];\n"
      "setp.ge.u32 p, v, %1;\n"
      "@p bra DONE;\n"
      "mov.u32 t1, %%clock;\n"
      "sub.u32 t1, t1, t0;\n"
      "setp.lt.u32 p, t1, 0x80000000;\n"
      "@p bra LAB_WAIT;\n"
      "trap;\n"
      "DONE:\n}" ::"l"(g_cnt + idx * 8),
      "r"(target)
      : "memory");
}
__device__ __forceinline__ void cnt_wait_bit(int idx, uint32_t bit, uint32_t& v) {
  asm volatile(
      "{\n.reg .pred p;\n.reg .u32 x, t0, t1;\n"
      "and.b32 x, %0, %2;\n"
      "setp.ne.u32 p, x, 0;\n"
      "@p bra DONE;\n"
      "mov.u32 t0, %%clock;\n"
      "LAB_WAIT:\n"
      "ld.acquire.gpu.global.u32 %0, [%1];\n"
      "and.b32 x, %0, %2;\n"
      "setp.ne.u32 p, x, 0;\n"
      "@p bra DONE;\n"
      "nanosleep.u32 64;\n"
      "mov.u32 t1, %%clock;\n"
      "sub.u32 t1, t1, t0;\n"
      "setp.lt.u32 p, t1, 0x80000000;\n"
      "@p bra LAB_WAIT;\n"
      "trap;\n"
      "DONE:\n}" : "+r"(v) : "l"(g_cnt + idx * 8),
      "r"(bit)
      : "memory");
}
__device__ __forceinline__ bool cnt_done(uint32_t total) {
  uint32_t old;
  asm volatile("atom.acq_rel.gpu.global.add.u32 %0, [%1], 1;" : "=r"(old) : "l"(g_cnt + CNT_DONE * 8) : "memory");
  return old == total - 1;
}
__device__ __forceinline__ void cnt_rearm() {
#pragma unroll
  for (int i = 0; i < CNT_N; i++) g_cnt[i * 8] = 0;
}
__device__ __forceinline__ void fence_proxy_async_global() { asm volatile("fence.proxy.async.global;" ::: "memory"); }
#ifdef TIMELINE
__device__ __forceinline__ void tl_rec(int role, int& n, uint32_t code) {
  unsigned long long t;
  asm volatile("mov.u64 %0, %%globaltimer;" : "=l"(t));
  uint32_t c;
  asm volatile("mov.u32 %0, %%clock;" : "=r"(c));
  if (n < 32) {
    g_tl[(blockIdx.x * 4 + role) * 64 + 2 * n] = t;
    g_tl[(blockIdx.x * 4 + role) * 64 + 2 * n + 1] = ((unsigned long long)code << 32) | c;
  }
  n++;
}
#define TL(role, code) tl_rec(role, tln, code)
__device__ __forceinline__ void tl_rec_p(int role, int& n, uint32_t code, bool on) {
  unsigned long long t;
  asm volatile("mov.u64 %0, %%globaltimer;" : "=l"(t));
  uint32_t c;
  asm volatile("mov.u32 %0, %%clock;" : "=r"(c));
  asm volatile("{\n.reg .pred p;\nsetp.ne.b32 p, %3, 0;\n@p st.global.v2.u64 [%0], {%1, %2};\n}" ::"l"(g_tl + (blockIdx.x * 4 + role) * 64 + 2 * n),
               "l"(t), "l"(((unsigned long long)code << 32) | c), "r"((int)(on && n < 32)) : "memory");
  n++;
}
#define TL0(code) tl_rec_p(0, tln, code, threadIdx.x == 0)
#define TL_DECL int tln = 0
#ifdef TLWAIT
#define TW_DECL uint32_t w0 = 0, w1 = 0, w2 = 0, w3 = 0; int tln3 = 0
#define TW(w, stmt) { uint32_t c0_ = clock(); stmt; w += clock() - c0_; }
#define TW_FLUSH() { tl_rec_p(3, tln3, (min(w0, 65534u) << 16) | min(w1, 65534u), threadIdx.x == TLWAIT); tl_rec_p(3, tln3, (min(w2, 65534u) << 16) | min(w3, 65534u), threadIdx.x == TLWAIT); w0 = w1 = w2 = w3 = 0; }
#define TW_END() tl_rec_p(3, tln3, 0xFFFF, threadIdx.x == TLWAIT)
#endif
#else
#define TL(role, code)
#define TL0(code)
#define TL_DECL
#endif
#ifdef TRACE
__device__ uint32_t g_tr[2 * 2 * 4096];
#define TR_DECL int trn = 0; const bool tron = (blockIdx.x == TRACE || blockIdx.x == TRACE2) && (threadIdx.x & 127) == TRW * 32; uint32_t* trp = g_tr + ((blockIdx.x == TRACE ? 0 : 2) + (threadIdx.x >> 7)) * 4096
#ifndef TRW
#define TRW 0
#endif
#ifndef TRM
#define TRM 0xFFFF
#endif
#define TRI(id, code) if ((TRM >> (id)) & 1) { asm volatile("{\n.reg .pred p;\nsetp.ne.b32 p, %2, 0;\n@p st.global.u32 [%0], %1;\n}" ::"l"(trp + trn), "r"(((uint32_t)clock() << 4) | (code)), "r"((int)(tron && trn < 4095)) : "memory"); trn++; }
#define TR(code) TRI(code, code)
#else
#define TR_DECL
#define TR(code)
#define TRI(id, code)
#endif
#ifndef TLWAIT
#define TW_DECL
#define TW(w, stmt) stmt
#define TW_FLUSH()
#define TW_END()
#endif

__device__ __forceinline__ uint32_t make_desc(uint32_t addr, uint32_t lbo_bytes) {
  return (addr >> 4) + ((lbo_bytes >> 4) << 16);
}

__device__ __forceinline__ void wgmma_ss_n128(float (&d)[64], uint32_t da, uint32_t db, int scale_d) {
  asm volatile("{\n.reg .pred p;\n.reg .b64 a, b;\nsetp.ne.b32 p, %66, 0;\nmov.b64 a, {%64, 0x40000040};\nmov.b64 b, {%65, 0x40000040};\n"
    "wgmma.mma_async.sync.aligned.m64n128k16.f32.bf16.bf16 {%0, %1, %2, %3, %4, %5, %6, %7, %8, %9, %10, %11, %12, %13, %14, %15, %16, %17, %18, %19, %20, %21, %22, %23, %24, %25, %26, %27, %28, %29, %30, %31, %32, %33, %34, %35, %36, %37, %38, %39, %40, %41, %42, %43, %44, %45, %46, %47, %48, %49, %50, %51, %52, %53, %54, %55, %56, %57, %58, %59, %60, %61, %62, %63}, a, b, p, 1, 1, 0, 0;\n}\n"
    : "+f"(d[0]), "+f"(d[1]), "+f"(d[2]), "+f"(d[3]), "+f"(d[4]), "+f"(d[5]), "+f"(d[6]), "+f"(d[7]), "+f"(d[8]), "+f"(d[9]), "+f"(d[10]), "+f"(d[11]), "+f"(d[12]), "+f"(d[13]), "+f"(d[14]), "+f"(d[15]), "+f"(d[16]), "+f"(d[17]), "+f"(d[18]), "+f"(d[19]), "+f"(d[20]), "+f"(d[21]), "+f"(d[22]), "+f"(d[23]), "+f"(d[24]), "+f"(d[25]), "+f"(d[26]), "+f"(d[27]), "+f"(d[28]), "+f"(d[29]), "+f"(d[30]), "+f"(d[31]), "+f"(d[32]), "+f"(d[33]), "+f"(d[34]), "+f"(d[35]), "+f"(d[36]), "+f"(d[37]), "+f"(d[38]), "+f"(d[39]), "+f"(d[40]), "+f"(d[41]), "+f"(d[42]), "+f"(d[43]), "+f"(d[44]), "+f"(d[45]), "+f"(d[46]), "+f"(d[47]), "+f"(d[48]), "+f"(d[49]), "+f"(d[50]), "+f"(d[51]), "+f"(d[52]), "+f"(d[53]), "+f"(d[54]), "+f"(d[55]), "+f"(d[56]), "+f"(d[57]), "+f"(d[58]), "+f"(d[59]), "+f"(d[60]), "+f"(d[61]), "+f"(d[62]), "+f"(d[63])
    : "r"(da), "r"(db), "r"(scale_d));
}
__device__ __forceinline__ void wgmma_ss_n64(float (&d)[32], uint32_t da, uint32_t db, int scale_d) {
  asm volatile("{\n.reg .pred p;\n.reg .b64 a, b;\nsetp.ne.b32 p, %34, 0;\nmov.b64 a, {%32, 0x40000040};\nmov.b64 b, {%33, 0x40000040};\n"
    "wgmma.mma_async.sync.aligned.m64n64k16.f32.bf16.bf16 {%0, %1, %2, %3, %4, %5, %6, %7, %8, %9, %10, %11, %12, %13, %14, %15, %16, %17, %18, %19, %20, %21, %22, %23, %24, %25, %26, %27, %28, %29, %30, %31}, a, b, p, 1, 1, 0, 0;\n}\n"
    : "+f"(d[0]), "+f"(d[1]), "+f"(d[2]), "+f"(d[3]), "+f"(d[4]), "+f"(d[5]), "+f"(d[6]), "+f"(d[7]), "+f"(d[8]), "+f"(d[9]), "+f"(d[10]), "+f"(d[11]), "+f"(d[12]), "+f"(d[13]), "+f"(d[14]), "+f"(d[15]), "+f"(d[16]), "+f"(d[17]), "+f"(d[18]), "+f"(d[19]), "+f"(d[20]), "+f"(d[21]), "+f"(d[22]), "+f"(d[23]), "+f"(d[24]), "+f"(d[25]), "+f"(d[26]), "+f"(d[27]), "+f"(d[28]), "+f"(d[29]), "+f"(d[30]), "+f"(d[31])
    : "r"(da), "r"(db), "r"(scale_d));
}
__device__ __forceinline__ void wgmma_rs_n128_tb(float (&d)[64], uint32_t a0, uint32_t a1, uint32_t a2, uint32_t a3, uint32_t db, int scale_d) {
  asm volatile("{\n.reg .pred p;\n.reg .b64 b;\nsetp.ne.b32 p, %69, 0;\nmov.b64 b, {%68, 0x40000040};\n"
    "wgmma.mma_async.sync.aligned.m64n128k16.f32.bf16.bf16 {%0, %1, %2, %3, %4, %5, %6, %7, %8, %9, %10, %11, %12, %13, %14, %15, %16, %17, %18, %19, %20, %21, %22, %23, %24, %25, %26, %27, %28, %29, %30, %31, %32, %33, %34, %35, %36, %37, %38, %39, %40, %41, %42, %43, %44, %45, %46, %47, %48, %49, %50, %51, %52, %53, %54, %55, %56, %57, %58, %59, %60, %61, %62, %63}, {%64, %65, %66, %67}, b, p, 1, 1, 1;\n}\n"
    : "+f"(d[0]), "+f"(d[1]), "+f"(d[2]), "+f"(d[3]), "+f"(d[4]), "+f"(d[5]), "+f"(d[6]), "+f"(d[7]), "+f"(d[8]), "+f"(d[9]), "+f"(d[10]), "+f"(d[11]), "+f"(d[12]), "+f"(d[13]), "+f"(d[14]), "+f"(d[15]), "+f"(d[16]), "+f"(d[17]), "+f"(d[18]), "+f"(d[19]), "+f"(d[20]), "+f"(d[21]), "+f"(d[22]), "+f"(d[23]), "+f"(d[24]), "+f"(d[25]), "+f"(d[26]), "+f"(d[27]), "+f"(d[28]), "+f"(d[29]), "+f"(d[30]), "+f"(d[31]), "+f"(d[32]), "+f"(d[33]), "+f"(d[34]), "+f"(d[35]), "+f"(d[36]), "+f"(d[37]), "+f"(d[38]), "+f"(d[39]), "+f"(d[40]), "+f"(d[41]), "+f"(d[42]), "+f"(d[43]), "+f"(d[44]), "+f"(d[45]), "+f"(d[46]), "+f"(d[47]), "+f"(d[48]), "+f"(d[49]), "+f"(d[50]), "+f"(d[51]), "+f"(d[52]), "+f"(d[53]), "+f"(d[54]), "+f"(d[55]), "+f"(d[56]), "+f"(d[57]), "+f"(d[58]), "+f"(d[59]), "+f"(d[60]), "+f"(d[61]), "+f"(d[62]), "+f"(d[63])
    : "r"(a0), "r"(a1), "r"(a2), "r"(a3), "r"(db), "r"(scale_d));
}
__device__ __forceinline__ void wgmma_ss_n72_init(float (&d)[36], uint32_t da, uint32_t db) {
  asm volatile("{\n.reg .pred p;\n.reg .b64 a, b;\nsetp.ne.b32 p, 0, 0;\nmov.b64 a, {%36, 0x40000040};\nmov.b64 b, {%37, 0x40000040};\n"
    "wgmma.mma_async.sync.aligned.m64n72k16.f32.bf16.bf16 {%0, %1, %2, %3, %4, %5, %6, %7, %8, %9, %10, %11, %12, %13, %14, %15, %16, %17, %18, %19, %20, %21, %22, %23, %24, %25, %26, %27, %28, %29, %30, %31, %32, %33, %34, %35}, a, b, p, 1, 1, 0, 0;\n}\n"
    : "=f"(d[0]), "=f"(d[1]), "=f"(d[2]), "=f"(d[3]), "=f"(d[4]), "=f"(d[5]), "=f"(d[6]), "=f"(d[7]), "=f"(d[8]), "=f"(d[9]), "=f"(d[10]), "=f"(d[11]), "=f"(d[12]), "=f"(d[13]), "=f"(d[14]), "=f"(d[15]), "=f"(d[16]), "=f"(d[17]), "=f"(d[18]), "=f"(d[19]), "=f"(d[20]), "=f"(d[21]), "=f"(d[22]), "=f"(d[23]), "=f"(d[24]), "=f"(d[25]), "=f"(d[26]), "=f"(d[27]), "=f"(d[28]), "=f"(d[29]), "=f"(d[30]), "=f"(d[31]), "=f"(d[32]), "=f"(d[33]), "=f"(d[34]), "=f"(d[35])
    : "r"(da), "r"(db));
}
__device__ __forceinline__ void wgmma_ss_n72(float (&d)[36], uint32_t da, uint32_t db, int scale_d) {
  asm volatile("{\n.reg .pred p;\n.reg .b64 a, b;\nsetp.ne.b32 p, %38, 0;\nmov.b64 a, {%36, 0x40000040};\nmov.b64 b, {%37, 0x40000040};\n"
    "wgmma.mma_async.sync.aligned.m64n72k16.f32.bf16.bf16 {%0, %1, %2, %3, %4, %5, %6, %7, %8, %9, %10, %11, %12, %13, %14, %15, %16, %17, %18, %19, %20, %21, %22, %23, %24, %25, %26, %27, %28, %29, %30, %31, %32, %33, %34, %35}, a, b, p, 1, 1, 0, 0;\n}\n"
    : "+f"(d[0]), "+f"(d[1]), "+f"(d[2]), "+f"(d[3]), "+f"(d[4]), "+f"(d[5]), "+f"(d[6]), "+f"(d[7]), "+f"(d[8]), "+f"(d[9]), "+f"(d[10]), "+f"(d[11]), "+f"(d[12]), "+f"(d[13]), "+f"(d[14]), "+f"(d[15]), "+f"(d[16]), "+f"(d[17]), "+f"(d[18]), "+f"(d[19]), "+f"(d[20]), "+f"(d[21]), "+f"(d[22]), "+f"(d[23]), "+f"(d[24]), "+f"(d[25]), "+f"(d[26]), "+f"(d[27]), "+f"(d[28]), "+f"(d[29]), "+f"(d[30]), "+f"(d[31]), "+f"(d[32]), "+f"(d[33]), "+f"(d[34]), "+f"(d[35])
    : "r"(da), "r"(db), "r"(scale_d));
}
template <int OA, int OB>
__device__ __forceinline__ void wgmma_ss_n128_tb(float (&d)[64], uint32_t da, uint32_t db, int scale_d) {
  asm volatile("{\n.reg .pred p;\n.reg .b64 a, b;\n.reg .b32 x, y;\nsetp.ne.b32 p, %66, 0;\nadd.u32 x, %64, %67;\nadd.u32 y, %65, %68;\nmov.b64 a, {x, 0x40000040};\nmov.b64 b, {y, 0x40000040};\n"
    "wgmma.mma_async.sync.aligned.m64n128k16.f32.bf16.bf16 {%0, %1, %2, %3, %4, %5, %6, %7, %8, %9, %10, %11, %12, %13, %14, %15, %16, %17, %18, %19, %20, %21, %22, %23, %24, %25, %26, %27, %28, %29, %30, %31, %32, %33, %34, %35, %36, %37, %38, %39, %40, %41, %42, %43, %44, %45, %46, %47, %48, %49, %50, %51, %52, %53, %54, %55, %56, %57, %58, %59, %60, %61, %62, %63}, a, b, p, 1, 1, 0, 1;\n}\n"
    : "+f"(d[0]), "+f"(d[1]), "+f"(d[2]), "+f"(d[3]), "+f"(d[4]), "+f"(d[5]), "+f"(d[6]), "+f"(d[7]), "+f"(d[8]), "+f"(d[9]), "+f"(d[10]), "+f"(d[11]), "+f"(d[12]), "+f"(d[13]), "+f"(d[14]), "+f"(d[15]), "+f"(d[16]), "+f"(d[17]), "+f"(d[18]), "+f"(d[19]), "+f"(d[20]), "+f"(d[21]), "+f"(d[22]), "+f"(d[23]), "+f"(d[24]), "+f"(d[25]), "+f"(d[26]), "+f"(d[27]), "+f"(d[28]), "+f"(d[29]), "+f"(d[30]), "+f"(d[31]), "+f"(d[32]), "+f"(d[33]), "+f"(d[34]), "+f"(d[35]), "+f"(d[36]), "+f"(d[37]), "+f"(d[38]), "+f"(d[39]), "+f"(d[40]), "+f"(d[41]), "+f"(d[42]), "+f"(d[43]), "+f"(d[44]), "+f"(d[45]), "+f"(d[46]), "+f"(d[47]), "+f"(d[48]), "+f"(d[49]), "+f"(d[50]), "+f"(d[51]), "+f"(d[52]), "+f"(d[53]), "+f"(d[54]), "+f"(d[55]), "+f"(d[56]), "+f"(d[57]), "+f"(d[58]), "+f"(d[59]), "+f"(d[60]), "+f"(d[61]), "+f"(d[62]), "+f"(d[63])
    : "r"(da), "r"(db), "r"(scale_d), "n"(OA), "n"(OB));
}
template <int OA, int OB>
__device__ __forceinline__ void wgmma_ss_n256_tbo(float (&d)[128], uint32_t da, uint32_t db, int scale_d) {
  asm volatile("{\n.reg .pred p;\n.reg .b64 a, b;\n.reg .b32 x, y;\nsetp.ne.b32 p, %130, 0;\nadd.u32 x, %128, %131;\nadd.u32 y, %129, %132;\nmov.b64 a, {x, 0x40000040};\nmov.b64 b, {y, 0x40000040};\n"
    "wgmma.mma_async.sync.aligned.m64n256k16.f32.bf16.bf16 {%0, %1, %2, %3, %4, %5, %6, %7, %8, %9, %10, %11, %12, %13, %14, %15, %16, %17, %18, %19, %20, %21, %22, %23, %24, %25, %26, %27, %28, %29, %30, %31, %32, %33, %34, %35, %36, %37, %38, %39, %40, %41, %42, %43, %44, %45, %46, %47, %48, %49, %50, %51, %52, %53, %54, %55, %56, %57, %58, %59, %60, %61, %62, %63, %64, %65, %66, %67, %68, %69, %70, %71, %72, %73, %74, %75, %76, %77, %78, %79, %80, %81, %82, %83, %84, %85, %86, %87, %88, %89, %90, %91, %92, %93, %94, %95, %96, %97, %98, %99, %100, %101, %102, %103, %104, %105, %106, %107, %108, %109, %110, %111, %112, %113, %114, %115, %116, %117, %118, %119, %120, %121, %122, %123, %124, %125, %126, %127}, a, b, p, 1, 1, 0, 1;\n}\n"
    : "+f"(d[0]), "+f"(d[1]), "+f"(d[2]), "+f"(d[3]), "+f"(d[4]), "+f"(d[5]), "+f"(d[6]), "+f"(d[7]), "+f"(d[8]), "+f"(d[9]), "+f"(d[10]), "+f"(d[11]), "+f"(d[12]), "+f"(d[13]), "+f"(d[14]), "+f"(d[15]), "+f"(d[16]), "+f"(d[17]), "+f"(d[18]), "+f"(d[19]), "+f"(d[20]), "+f"(d[21]), "+f"(d[22]), "+f"(d[23]), "+f"(d[24]), "+f"(d[25]), "+f"(d[26]), "+f"(d[27]), "+f"(d[28]), "+f"(d[29]), "+f"(d[30]), "+f"(d[31]), "+f"(d[32]), "+f"(d[33]), "+f"(d[34]), "+f"(d[35]), "+f"(d[36]), "+f"(d[37]), "+f"(d[38]), "+f"(d[39]), "+f"(d[40]), "+f"(d[41]), "+f"(d[42]), "+f"(d[43]), "+f"(d[44]), "+f"(d[45]), "+f"(d[46]), "+f"(d[47]), "+f"(d[48]), "+f"(d[49]), "+f"(d[50]), "+f"(d[51]), "+f"(d[52]), "+f"(d[53]), "+f"(d[54]), "+f"(d[55]), "+f"(d[56]), "+f"(d[57]), "+f"(d[58]), "+f"(d[59]), "+f"(d[60]), "+f"(d[61]), "+f"(d[62]), "+f"(d[63]), "+f"(d[64]), "+f"(d[65]), "+f"(d[66]), "+f"(d[67]), "+f"(d[68]), "+f"(d[69]), "+f"(d[70]), "+f"(d[71]), "+f"(d[72]), "+f"(d[73]), "+f"(d[74]), "+f"(d[75]), "+f"(d[76]), "+f"(d[77]), "+f"(d[78]), "+f"(d[79]), "+f"(d[80]), "+f"(d[81]), "+f"(d[82]), "+f"(d[83]), "+f"(d[84]), "+f"(d[85]), "+f"(d[86]), "+f"(d[87]), "+f"(d[88]), "+f"(d[89]), "+f"(d[90]), "+f"(d[91]), "+f"(d[92]), "+f"(d[93]), "+f"(d[94]), "+f"(d[95]), "+f"(d[96]), "+f"(d[97]), "+f"(d[98]), "+f"(d[99]), "+f"(d[100]), "+f"(d[101]), "+f"(d[102]), "+f"(d[103]), "+f"(d[104]), "+f"(d[105]), "+f"(d[106]), "+f"(d[107]), "+f"(d[108]), "+f"(d[109]), "+f"(d[110]), "+f"(d[111]), "+f"(d[112]), "+f"(d[113]), "+f"(d[114]), "+f"(d[115]), "+f"(d[116]), "+f"(d[117]), "+f"(d[118]), "+f"(d[119]), "+f"(d[120]), "+f"(d[121]), "+f"(d[122]), "+f"(d[123]), "+f"(d[124]), "+f"(d[125]), "+f"(d[126]), "+f"(d[127])
    : "r"(da), "r"(db), "r"(scale_d), "n"(OA), "n"(OB));
}

constexpr int NCTA = 132;
constexpr int NCLUSTER = 66;
constexpr int NPROB = 6;
#ifdef GEMM_ONLY
#define DO_LOCAL false
#define DO_ATT false
#else
#define DO_LOCAL true
#define DO_ATT true
#endif
#ifdef ATT_ONLY
#define NA_CL_ 0
#define NITEMS 768
#else
#define NA_CL_ 32
#define NITEMS 256
#endif
constexpr int G1_MAX = 24, NA_CL = NA_CL_, NB_CL = NCLUSTER - NA_CL;
constexpr int TILE32K = 32768;
constexpr uint32_t DBASE = 1024;
constexpr int OFF_STG = 4 * TILE32K;
constexpr int OFF_A = 5 * TILE32K;
constexpr int OFF_BAR = 7 * TILE32K;
constexpr int L_K = 8192, L_V = L_K + 9216, L_P = L_V + 9216;
constexpr int SMEM_BYTES = OFF_BAR + 1024;
constexpr int B_GFULL = 0, B_GEMPTY = 32, B_AFULL = 64, B_AEMPTY = 104, B_QFULL = 144, B_QEMPTY = 160,
              B_SFULL = 176, B_SEMPTY = 208, B_OFULL = 240, B_STGFREE = 256, S_CODE = 272, B_SFULL2 = 304,
              B_MAIL = 336, S_MAIL = 368;
#ifndef FS
#define FS 2
#endif
#ifndef HW
#define HW 1
#endif
#ifndef PACE
#define PACE 900u
#endif
#ifndef REG_C
#define REG_C 232
#define REG_P 40
#endif

struct Params {
  CUtensorMap ta[NPROB];
  CUtensorMap tb[NPROB];
  CUtensorMap tc[NPROB];
  CUtensorMap tq, tk, tv, to, tl, th;
  bf16* ob;
  uint16_t g[NCLUSTER][G1_MAX];
  uint16_t order[256];
};
__device__ __forceinline__ uint32_t tail_item(uint32_t code) {
  return (code & 0x7FFF) < 32 ? (5u << 8) | ((code & 4) << 4) | ((code & 0x18) << 1) | (code & 3) : 0xFFFFu;
}
#ifndef HM
#define HM 0x39383F00
#endif
#define HINT(b) ((HM >> (b) & 1) ? EV_FIRST : EV_NORMAL)
__device__ __forceinline__ uint32_t lds32(uint32_t a) {
  uint32_t v;
  asm volatile("ld.shared.u32 %0, [%1];" : "=r"(v) : "r"(a) : "memory");
  return v;
}
__device__ __forceinline__ uint4 lds128(uint32_t a) {
  uint4 v;
  asm volatile("ld.shared.v4.u32 {%0, %1, %2, %3}, [%4];" : "=r"(v.x), "=r"(v.y), "=r"(v.z), "=r"(v.w) : "r"(a) : "memory");
  return v;
}
__device__ __forceinline__ void sts64(uint32_t a, float x, float y) {
  asm volatile("st.shared.v2.f32 [%0], {%1, %2};" ::"r"(a), "f"(x), "f"(y) : "memory");
}
__device__ __forceinline__ void sts32(uint32_t a, uint32_t v) {
  asm volatile("st.shared.u32 [%0], %1;" ::"r"(a), "r"(v) : "memory");
}
__device__ __forceinline__ uint32_t opaque_tid() {
  uint32_t t;
  asm volatile("mov.u32 %0, %%tid.x;" : "=r"(t));
  return t;
}
__device__ __forceinline__ uint32_t stg_off(uint32_t tid) {
  return (tid >> 5) * 2048 + (tid & 15) * 128 + ((((tid >> 4) & 1) ^ (tid & 7)) << 4);
}
__device__ __forceinline__ int prob_nkb4(int prob) { return (0x4F4224 >> (prob * 4) & 15) + (prob == 4); }

constexpr float SM_C = 0.08838834764831845f * 1.4426950408889634f;
constexpr float SM_HI = 1099511627776.0f;
constexpr float SM_LO = 8.673617379884035e-19f;
__device__ __forceinline__ void softmax_max(const float (&s)[64], float& a0, float& a1) {
  a0 = fmaxf(s[0], s[1]);
  a1 = fmaxf(s[2], s[3]);
#pragma unroll
  for (int j = 1; j < 16; j++) {
    a0 = fmaxf(a0, fmaxf(s[4 * j], s[4 * j + 1]));
    a1 = fmaxf(a1, fmaxf(s[4 * j + 2], s[4 * j + 3]));
  }
  a0 = fmaxf(a0, __shfl_xor_sync(0xffffffffu, a0, 1));
  a1 = fmaxf(a1, __shfl_xor_sync(0xffffffffu, a1, 1));
  a0 = fmaxf(a0, __shfl_xor_sync(0xffffffffu, a0, 2));
  a1 = fmaxf(a1, __shfl_xor_sync(0xffffffffu, a1, 2));
}
template <int J0, int J1, bool OFS, int N>
__device__ __forceinline__ void softmax_exp(const float (&s)[64], float b0, float b1, uint32_t (&out)[N], float& t0,
                                            float& t1) {
#pragma unroll
  for (int j = J0; j < J1; j++) {
    const float e0 = ex2(OFS ? s[4 * j] + b0 : s[4 * j]);
    const float e1 = ex2(OFS ? s[4 * j + 1] + b0 : s[4 * j + 1]);
    const float e2 = ex2(OFS ? s[4 * j + 2] + b1 : s[4 * j + 2]);
    const float e3 = ex2(OFS ? s[4 * j + 3] + b1 : s[4 * j + 3]);
    t0 += e0 + e1;
    t1 += e2 + e3;
    out[2 * j] = pack_bf16(e0, e1);
    out[2 * j + 1] = pack_bf16(e2, e3);
  }
}

__device__ __forceinline__ uint32_t scale_q(uint32_t x) {
  uint32_t t, y;
  asm("mul.rn.bf16x2 %0, %1, %2;" : "=r"(t) : "r"(x), "r"(0xb9d8b9d8u));
  asm("fma.rn.bf16x2 %0, %1, %2, %3;" : "=r"(y) : "r"(x), "r"(0x3e033e03u), "r"(t));
  return y;
}

__global__ void __cluster_dims__(2, 1, 1) __launch_bounds__(384, 1) mega_kernel(const __grid_constant__ Params p) {
  extern __shared__ __align__(1024) uint8_t smem_raw[];
#ifdef TRACE
  const uint32_t c_entry = clock();
#endif
  const uint32_t sbase = smem_u32(smem_raw);
  const uint32_t s_bar = sbase + OFF_BAR;
  const int cluster_id = blockIdx.x >> 1;
  const bool isB = cluster_id >= NA_CL;
#if !defined(ATT_ONLY) && !defined(GEMM_ONLY)
#define EARLY 1
#else
#define EARLY 0
#endif
  const int prob0 = isB ? 3 : cluster_id >> 4;
  const int ng0 = (isB ? (cluster_id - NA_CL) >> 3 : (cluster_id >> 3) & 1) * 4;
  const uint32_t t0 = clock();
  auto early = [&](int s) {
    const uint32_t full = s_bar + B_GFULL + 8 * s;
    mbar_expect_tx(full, 49152);
    tma_load_3d(sbase + OFF_A + s * 16384, &p.ta[prob0], 0, (blockIdx.x & 15) * 128, s, full, EV_NORMAL);
    tma_load_3d(sbase + s * TILE32K, &p.tb[prob0], 0, s * 64, ng0, full, EV_NORMAL);
    tma_load_3d(sbase + s * TILE32K + 16384, &p.tb[prob0], 0, s * 64, ng0 + 2, full, EV_NORMAL);
  };
  if ((threadIdx.x >> 5) == 8) {
    if (elect_one()) {
      mbar_init(s_bar + B_GFULL, 1);
      asm volatile("fence.mbarrier_init.release.cluster;" ::: "memory");
      if (EARLY) early(0);
      for (int s = 1; s < 4; s++) mbar_init(s_bar + B_GFULL + 8 * s, 1);
      asm volatile("fence.mbarrier_init.release.cluster;" ::: "memory");
    }
    __syncwarp();
    named_bar_arrive(7, 288);
  }
  const int warp0 = __shfl_sync(0xffffffffu, threadIdx.x >> 5, 0);
  if (warp0 >= 8) reg_dealloc<REG_P>();
#define CLUSTER_ARRIVE() asm volatile("barrier.cluster.arrive.relaxed.aligned;" ::: "memory")
#define CLUSTER_WAIT() asm volatile("barrier.cluster.wait.acquire.aligned;" ::: "memory")

  if (warp0 >= 8) {
    if (warp0 == 10 && elect_one()) {
      if ((sbase & 0x3FFFFu) != DBASE) __trap();
      for (int s = 0; s < 4; s++) {
        mbar_init(s_bar + B_GEMPTY + 8 * s, 4);
        mbar_init(s_bar + B_SFULL + 8 * s, 4);
        mbar_init(s_bar + B_SFULL2 + 8 * s, 4);
        mbar_init(s_bar + B_SEMPTY + 8 * s, 1);
        mbar_init(s_bar + B_AFULL + 8 * s, 1);
        mbar_init(s_bar + B_AEMPTY + 8 * s, isB ? 4 : s ? 8 : 2);
        mbar_init(s_bar + B_MAIL + 8 * s, 1);
      }
      for (int s = 0; s < 2; s++) {
        mbar_init(s_bar + B_QFULL + 8 * s, 1);
        mbar_init(s_bar + B_QEMPTY + 8 * s, 2);
      }
      mbar_init(s_bar + B_OFULL, 8);
      mbar_init(s_bar + B_STGFREE, 1);
      asm volatile("fence.mbarrier_init.release.cluster;" ::: "memory");
    }
    __syncwarp();
    CLUSTER_ARRIVE();
    if (EARLY && warp0 == 8 && elect_one()) {
#pragma unroll 1
      for (int s = 1; s < 4; s++) {
        while ((uint32_t)clock() - t0 < s * PACE) {}
        early(s);
      }
    }
    __syncwarp();
    CLUSTER_WAIT();
    const uint32_t rank = blockIdx.x & 1;
    if (warp0 == 8) {
      if (elect_one()) {
        TL_DECL;
        uint32_t gphase = 1 - EARLY;
        uint32_t tail = 0;
        int gi = 0;
        uint32_t aswz = 0, lastq = 0, n = 0;
        uint32_t aprev = ~0u;
        for (int seg = 0; seg < 2; seg++) {
          for (;;) {
            uint32_t item = p.g[cluster_id][gi++];
            if (item == 0x500u) item = tail;
            if (item >= 0x600u) break;
            const int prob = item >> 8;
            const int rt = ((item >> 4) & 15) * 2 + rank;
            const int ngrp0 = (item & 15) * 4;
            const int nkb4 = prob_nkb4(prob);
            const CUtensorMap* ta = &p.ta[prob];
            const CUtensorMap* tb = &p.tb[prob];
            const uint64_t ahint = p.g[cluster_id][gi] >= 0x400u ? EV_FIRST : EV_NORMAL;
            const int rot4 = prob < 4 ? 1 - gi : 0;
            const uint32_t akey = (item + 0x100u) & 0x6F0u;
            const bool keep = akey == aprev;
            aprev = akey;
            TL(1, item);
            if (prob == 5) {
              uint32_t seen = 0;
              cnt_wait_bit(CNT_OB + (rt >> 2), 32u << (rt & 3) * 8, seen);
              fence_proxy_async_global();
            }
            for (int kb4 = EARLY && gi == 1; kb4 < nkb4; kb4++) {
              uint32_t seen = 0;
#pragma unroll 1
              for (int s = 0; s < 4; s++) {
                const int bs = s ^ (n & 1);
                if (prob == 4 && !(s & 1)) {
                  cnt_wait_bit(CNT_CTX + kb4, 16u << (s * 8), seen);
                  fence_proxy_async_global();
                }
                if (prob == 5 && kb4 == 0) {
                  mbar_wait(s_bar + B_AEMPTY + 8 * bs, (~(n + (s & 1)) >> 1) & 1);
                  if (s == 2) mbar_wait(s_bar + B_QEMPTY + (aswz ? 0 : 8), lastq);
                }
                mbar_wait(s_bar + B_GEMPTY + 8 * s, gphase);
                const uint32_t full = s_bar + B_GFULL + 8 * s;
                const int kb = ((kb4 + rot4) & (nkb4 - 1)) * 4 + s;
                if (keep && kb4 == 0) {
                  mbar_expect_tx(full, 32768);
                } else {
                  mbar_expect_tx(full, 49152);
                  tma_load_3d(sbase + OFF_A + ((s * 16384) ^ aswz), ta, 0, rt * 128, kb, full, ahint);
                }
                tma_load_3d_mc(sbase + bs * TILE32K + rank * 16384, tb, 0, kb * 64, ngrp0 + rank * 2, full,
                               (uint16_t)3, HINT(8 + prob));
              }
              gphase ^= 1;
            }
          }
          if (seg == 0 && isB && DO_ATT) {
            int pv_row = 0, pv_col = 0;
            uint64_t pv_hint = 0;
            bool pv_own = false;
#define ACQ_SLOT(slot, n)                                                              \
  {                                                                                    \
    if ((n) < 2) mbar_wait(s_bar + B_GEMPTY + 8 * (slot), gphase);                     \
    mbar_wait(s_bar + B_AEMPTY + 8 * (slot), (~(n) >> 1) & 1);                         \
  }
#define LOAD_KV(map, slot, row, col, own, hint)                                        \
  {                                                                                    \
    const uint32_t full = s_bar + B_AFULL + 8 * (slot);                                \
    mbar_expect_tx(full, TILE32K);                                                     \
    if (own) {                                                                         \
      tma_load_3d(sbase + (slot) * TILE32K, map, 0, row, col, full, hint);             \
      tma_load_3d(sbase + (slot) * TILE32K + 16384, map, 0, row, (col) + 1, full, hint); \
    } else {                                                                           \
      tma_load_3d_mc(sbase + (slot) * TILE32K + rank * 16384, map, 0, row, (col) + rank, full, (uint16_t)3, hint); \
    }                                                                                  \
  }
#define LOAD_V()                                                                       \
  {                                                                                    \
    const uint32_t vs = 3 - (n & 1);                                                   \
    ACQ_SLOT(vs, n - 1);                                                               \
    LOAD_KV(&p.tv, vs, pv_row, pv_col, pv_own, pv_hint)                                \
  }
#ifdef ATT_ONLY
#define NEXT_CODE() (nxt < NITEMS ? p.order[nxt & 255] : 0x8000u + 64)
#else
#define NEXT_CODE() (nxt < 256 ? p.order[nxt] : nxt + (0x8000u - 256))
#endif
            uint32_t code = p.order[cluster_id - NA_CL];
            int it = 0;
            uint32_t seen = 0;
            for (;; it++) {
              if (it == 1) mbar_wait(s_bar + B_STGFREE, 0);
              if (code & 0x8000u) break;
              const int head = code >> 4;
              const int q0 = code & 15, up = rank == (it & 1);
              uint32_t nxt = 0;
              TL(1, 0x1000 | code | up);
#ifndef ATT_ONLY
              if (seen < 48) cnt_wait(CNT_QKV + (head >> 1), 48);
#endif
              fence_proxy_async_global();
              {
                const int b = it & 1;
                if (it < 2) {
                  mbar_wait(s_bar + B_GEMPTY + 16 * b, gphase);
                  mbar_wait(s_bar + B_GEMPTY + 16 * b + 8, gphase);
                }
                mbar_wait(s_bar + B_QEMPTY + 8 * b, ((it >> 1) & 1) ^ 1);
                mbar_expect_tx(s_bar + B_QFULL + 8 * b, TILE32K);
                tma_load_3d(sbase + OFF_A + b * TILE32K, &p.tq, 0, (q0 + up) * 128, head * 2, s_bar + B_QFULL + 8 * b, HINT(24));
              }
#pragma unroll 1
              for (int i = q0 + (up & it); i >= -(up & ~it); i--) {
                const int t = i < 0 ? q0 + 1 : i;
                if (rank == 0 && i == min(q0, 1)) nxt = cnt_next(CNT_QUEUE) + NB_CL;
                if (i == 0) {
                  if (rank == 0) {
                    code = NEXT_CODE();
                    send_peer(s_bar + S_MAIL + 4 * (it & 3), s_bar + B_MAIL + 8 * (it & 3), code);
                  } else {
                    mbar_expect_tx(s_bar + B_MAIL + 8 * (it & 3), 4);
                    mbar_wait(s_bar + B_MAIL + 8 * (it & 3), (it >> 2) & 1);
                    code = lds32(s_bar + S_MAIL + 4 * (it & 3));
                  }
                  sts32(s_bar + S_CODE + 4 * ((it + 1) & 7), code);
                  seen = cnt_peek(CNT_QKV + ((code >> 5) & 15));
                }
                ACQ_SLOT(n & 1, n);
                LOAD_KV(&p.tk, n & 1, t * 128, head * 2, t > q0, HINT(t >= q0 ? 29 : 25))
                if (n) LOAD_V();
                n++;
                pv_row = t * 128;
                pv_col = head * 2;
                pv_own = t > q0;
                pv_hint = HINT(t >= q0 ? 29 : 26);
              }
            }
            ACQ_SLOT(n & 1, n);
            mbar_arrive(s_bar + B_AFULL + 8 * (n & 1));
            LOAD_V();
            if (rank & it) {
              ACQ_SLOT(2 + (n & 1), n);
#pragma unroll 1
              for (int i = 0; i < 8; i++) mbar_arrive_cluster_if(s_bar + B_AEMPTY + 8 * ((n & 1) + (i & 2)), i & 1, true);
              n++;
            }
            tail = tail_item(code);
            aswz = (it & 1) * TILE32K;
            mbar_wait(s_bar + B_QEMPTY + 8 * (it & 1), ((it >> 1) & 1) ^ 1);
            lastq = ((it - 1) >> 1) & 1;
            if (tail == 0xFFFFu) {
#pragma unroll 1
              for (int s = 0; s < 4; s++) mbar_wait(s_bar + B_AEMPTY + 8 * (s ^ (n & 1)), (~(n + (s & 1)) >> 1) & 1);
            }
          }
        }
        if (cnt_done(NCTA * 2)) cnt_rearm();
#pragma unroll 1
        for (int s = 0; s < 4; s++) mbar_wait(s_bar + B_GEMPTY + 8 * s, gphase);
        TL(1, 0xFFFF);
      }
    } else if (warp0 == 9) {
      if (elect_one()) {
        TL_DECL;
        uint32_t tail = 0;
        int gi = 0;
        uint32_t aswz = 0;
        bool rearm = false;
        for (int seg = 0; seg < 2; seg++) {
          for (;;) {
            uint32_t item = p.g[cluster_id][gi++];
            if (item == 0x500u) item = tail;
            if (item >= 0x600u) break;
            const int prob = item >> 8;
            const int rt = ((item >> 4) & 15) * 2 + rank;
            const int cg = (item & 15) * 4 + (prob == 5 ? 16 : 0);
            const CUtensorMap* tc = &p.tc[prob];
            const int nl = (p.g[cluster_id][gi] >> 8) == 4 && DO_LOCAL ? 8 : 1;
            const int grp = (blockIdx.x & 15) * 2 + ((blockIdx.x >> 4) & 1), r0 = (blockIdx.x >> 5) * 512;
            if (nl > 1) {
              cnt_wait(CNT_QKVB, 192);
              fence_proxy_async_global();
            }
            if (prob >= 4) rearm = cnt_done(NCTA * 2);
            const bool lastt = p.g[cluster_id][gi] >= 0x600u;
#pragma unroll 1
            for (int c = 0; c < 8; c++) {
              const int q = lastt ? c & 3 : c >> 1, w = lastt ? c >> 2 : c & 1;
              const int idx = w * 2 + (q & 1);
              const bool alt = lastt && q >= 2;
              mbar_wait(s_bar + (alt ? B_SFULL2 : B_SFULL) + 8 * idx, lastt ? seg : q >> 1);
              tma_store_4d(tc, sbase + (alt ? OFF_A + ((q * 16384) ^ aswz) + w * 8192 : OFF_STG + idx * 8192),
                           rt * 64 + w * 32, cg + q, HINT(16 + prob));
              bulk_commit();
              if (c > 0 && !lastt) {
                bulk_wait_read<1>();
                mbar_arrive(s_bar + B_SEMPTY + 8 * ((w ^ 1) * 2 + (((c - 1) >> 1) & 1)));
              }
            }
            bulk_wait_read<0>();
            mbar_arrive(s_bar + (lastt ? B_STGFREE : B_SEMPTY + 8 * 3));
#pragma unroll 1
            for (int c = 0; c < nl; c++) {
              if (nl > 1) {
                mbar_wait(s_bar + B_AEMPTY, (c & 1) ^ 1);
                mbar_expect_tx(s_bar + B_AFULL, L_V);
                tma_load_3d(sbase + OFF_STG, &p.tl, 0, r0 + c * 64, grp, s_bar + B_AFULL, HINT(28));
                tma_load_3d(sbase + OFF_STG + L_K, &p.th, 0, r0 + c * 64 - 8, 32 + grp, s_bar + B_AFULL, HINT(28));
                mbar_wait(s_bar + B_AEMPTY + 8, (c & 1) ^ 1);
                mbar_expect_tx(s_bar + B_AFULL + 8, 9216);
                tma_load_3d(sbase + OFF_STG + L_V, &p.th, 0, r0 + c * 64 - 8, 64 + grp, s_bar + B_AFULL + 8, HINT(28));
              }
              if (c) {
                mbar_wait(s_bar + B_OFULL, ~c & 1);
                cnt_signal(CNT_OB + (blockIdx.x >> 5) * 2 + ((c - 1) >> 2), 1u << ((c - 1) & 3) * 8);
              } else if (prob < 4) {
                bulk_wait<0>();
                cnt_signal_done(prob == 3 ? CNT_QKVB : CNT_QKV + (item & 15));
                TL(2, item);
              }
            }
            if (nl > 1) {
              mbar_wait(s_bar + B_OFULL, 1);
              cnt_signal(CNT_OB + (blockIdx.x >> 5) * 2 + 1, 1u << 24);
              TL(2, 0x600);
            }
          }
          if (seg == 0 && isB && DO_ATT) {
#ifdef ATT_ONLY
            mbar_arrive(s_bar + B_STGFREE);
#endif
            uint32_t code = p.order[cluster_id - NA_CL];
            for (int it = 0; !(code & 0x8000u); it++) {
              code |= rank == (it & 1);
              aswz = (~it & 1) * TILE32K;
              mbar_wait(s_bar + B_OFULL, it & 1);
              tma_store_3d(&p.to, sbase + OFF_STG, 0, (code & 15) * 128, (code >> 4) * 2, HINT(27));
              bulk_commit();
              const uint32_t nxt = lds32(s_bar + S_CODE + 4 * ((it + 1) & 7));
              bulk_wait_read<0>();
              mbar_arrive(s_bar + B_STGFREE);
              bulk_wait<0>();
              cnt_signal_done(CNT_CTX + (code >> 5), 1u << (code & 16));
              TL(2, 0x1000 | code);
              code = nxt;
            }
            tail = tail_item(code);
            if (tail == 0xFFFFu) rearm = cnt_done(NCTA * 2);
          }
        }
        if (rearm) cnt_rearm();
        TL(2, 0xFFFF);
      }
    }
  } else {
    CLUSTER_ARRIVE();
    reg_alloc<REG_C>();
    named_bar_sync(7, 288);
    const int warp = __shfl_sync(0xffffffffu, opaque_tid() >> 5, 0);
    const int wg = warp >> 2;
    const int lane = threadIdx.x & 31;
    TL_DECL;
    TR_DECL;
#ifdef TRACE
    if (tron) trp[trn] = (c_entry << 4) | 12;
    trn++;
    TRI(9, 13);
#endif
    uint32_t gphase = 0;
    uint32_t tail = 0, aswz = 0, rot = 0, stgpar = 1;
    const uint32_t etgt = warp & 1;
    int gi = 0;
    for (int seg = 0; seg < 2; seg++) {
      uint32_t item = p.g[cluster_id][gi++];
      if (item == 0x500u) item = tail;
      if (item < 0x600u) {
        float acc[128];
        uint32_t pk[64];
        int have = 0;
#define G_STORE_CHUNK(q)                                                                               \
  {                                                                                                    \
    const uint32_t st_base = sbase + OFF_STG + wg * 8192 + stg_off(opaque_tid());                      \
    if (have == 2) { _Pragma("unroll") for (int j = 0; j < 16; j++) pk[(q) * 16 + j] = scale_q(pk[(q) * 16 + j]); } \
    mbar_wait(s_bar + B_SEMPTY + 8 * (wg * 2 + ((q) & 1)), (((q) >> 1) & 1) ^ 1);                      \
    _Pragma("unroll") for (int j = 0; j < 4; j++)                                                      \
        stmatrix_x4((st_base ^ (j << 5)) + ((q) & 1) * 8192, pk[(q) * 16 + j * 4],                     \
                    pk[(q) * 16 + j * 4 + 1], pk[(q) * 16 + j * 4 + 2], pk[(q) * 16 + j * 4 + 3]);     \
    fence_proxy_async_smem();                                                                          \
    __syncwarp();                                                                                      \
    mbar_arrive_elect(s_bar + B_SFULL + 8 * (wg * 2 + ((q) & 1)), true);                              \
  }
#define G_STAGE(s) G_STAGE_Y(s, false, false, )
#define G_STAGE_X(s, ...) G_STAGE_Y(s, false, false, __VA_ARGS__)
#define G_STAGE_Y(s, first, last, ...)                                                                    \
  {                                                                                                       \
    mbar_wait_rest(s_bar + B_GFULL + 8 * (s), gphase, gok && (first));                                    \
    TR(9);                                                                                                \
    const uint32_t da = make_desc(DBASE + OFF_A + (((s) * 16384) ^ aswz) + wg * 8192, 16);                \
    const uint32_t db = make_desc(DBASE + ((s) ^ rot) * TILE32K, 8192);                                   \
    named_bar_sync_if(5 + wg, 256, !(first));                                                             \
    wgmma_fence();                                                                                        \
    _Pragma("unroll") for (int k = 0; k < 5; k++) {                                                       \
      __VA_ARGS__;                                                                                        \
      if (k == 0) wgmma_ss_n256_tbo<0, 0>(acc, da, db, !(first));                                         \
      if (k == 1) wgmma_ss_n256_tbo<2, 128>(acc, da, db, 1);                                              \
      if (k == 2) wgmma_ss_n256_tbo<4, 256>(acc, da, db, 1);                                              \
      if (k == 3) wgmma_ss_n256_tbo<6, 384>(acc, da, db, 1);                                              \
    }                                                                                                     \
    wgmma_commit();                                                                                       \
    named_bar_arrive_if(6 - wg, 256, !(wg ? (last) : (first)));                                           \
    if (!(first)) {                                                                                       \
      wgmma_wait<1>();                                                                                    \
      mbar_arrive_cluster_if(s_bar + B_GEMPTY + 8 * (((s) + 3) & 3), etgt, lane == 0 && (warp & 3) < 2);  \
    }                                                                                                     \
  }
        TL0(item);
        undef_regs(acc);
        {
          constexpr bool gok = false;
#ifdef TRE
          const uint32_t e0 = clock() - c_entry;
          mbar_wait(s_bar + B_GFULL, gphase);
          if (threadIdx.x == 0 && seg == 0) g_tr[16001 + 2 * blockIdx.x] = e0 | ((clock() - c_entry) << 16);
#endif
          G_STAGE_Y(0, true, false, )
        }
        if (seg == 0) CLUSTER_WAIT();
        undef_regs(pk);
        for (;;) {
          constexpr bool gok = false;
          const int nkb4 = prob_nkb4(item >> 8);
          const uint32_t next = p.g[cluster_id][gi++];
          G_STAGE(1)
          if (have) G_STORE_CHUNK(0)
          G_STAGE(2)
          G_STAGE(3)
          if (have) G_STORE_CHUNK(1)
          gphase ^= 1;
          G_STAGE(0)
          G_STAGE(1)
          if (have) G_STORE_CHUNK(2)
          G_STAGE(2)
          if (have) G_STORE_CHUNK(3)
          G_STAGE_Y(3, false, nkb4 == 2, )
          gphase ^= 1;
          int kb4 = 2;
          if (nkb4 == 16 && DO_LOCAL) {
            constexpr uint32_t aswz = 0, rot = 0;
            G_STAGE(0)
            G_STAGE(1)
            for (; kb4 < 10; kb4++) {
              float ls[36];
              TR(10);
              mbar_wait(s_bar + B_AFULL, kb4 & 1);
              TR(11);
              {
                const uint32_t dq = make_desc(DBASE + OFF_STG + wg * 64, 16);
                G_STAGE_X(2, if (k == 1) wgmma_ss_n72_init(ls, dq, dq + L_K / 16); if (k == 3) wgmma_ss_n72(ls, dq + 2, dq + L_K / 16 + 2, 1))
              }
              mbar_wait(s_bar + B_AFULL + 8, kb4 & 1);
              const int tid = opaque_tid();
              uint32_t vw[16];
              uint4 pw[8];
              {
                const uint32_t va = sbase + OFF_STG + L_V + ((tid >> 4) & 7) * 1024 + wg * 64 + (tid & 15) * 4;
#pragma unroll
                for (int j = 1; j < 16; j++) vw[j] = lds32((va ^ ((j & 7) << 4)) + j * 128);
              }
              G_STAGE(3)
              gphase ^= 1;
              fence_regs(ls);
              mbar_arrive_if(s_bar + B_AEMPTY, (threadIdx.x & 127) == 0);
              {
                const int d = (tid & 3) * 2 - ((tid >> 2) & 7);
                const bool p0 = d > 0, p1 = d >= 0;
                const int w = warp & 3;
                float x0, x1, y0, y1;
#define L_PICK(w_)                                   \
  {                                                  \
    x0 = p0 ? ls[8 * (w_)] : ls[8 * (w_) + 4];       \
    x1 = p1 ? ls[8 * (w_) + 1] : ls[8 * (w_) + 5];   \
    y0 = p0 ? ls[8 * (w_) + 6] : ls[8 * (w_) + 10];  \
    y1 = p1 ? ls[8 * (w_) + 7] : ls[8 * (w_) + 11];  \
  }
                if (w == 0) {
                  if (kb4 == 2 && blockIdx.x < 32) ls[0] = ls[1] = -INFINITY;
                  L_PICK(0)
                } else if (w == 1) L_PICK(1)
                else if (w == 2) L_PICK(2)
                else L_PICK(3)
                constexpr float C = 0.17677669529663687f * 1.4426950408889634f;
                float mx = fmaxf(x0, x1), my = fmaxf(y0, y1);
                mx = fmaxf(mx, __shfl_xor_sync(0xffffffffu, mx, 1));
                my = fmaxf(my, __shfl_xor_sync(0xffffffffu, my, 1));
                mx = -C * fmaxf(mx, __shfl_xor_sync(0xffffffffu, mx, 2));
                my = -C * fmaxf(my, __shfl_xor_sync(0xffffffffu, my, 2));
                x0 = ex2(fmaf(x0, C, mx));
                x1 = ex2(fmaf(x1, C, mx));
                y0 = ex2(fmaf(y0, C, my));
                y1 = ex2(fmaf(y1, C, my));
                float sx = x0 + x1, sy = y0 + y1;
                sx += __shfl_xor_sync(0xffffffffu, sx, 1);
                sy += __shfl_xor_sync(0xffffffffu, sy, 1);
                sx += __shfl_xor_sync(0xffffffffu, sx, 2);
                sy += __shfl_xor_sync(0xffffffffu, sy, 2);
                sx = rcp(sx);
                sy = rcp(sy);
                const uint32_t pa = sbase + OFF_STG + L_P + (tid >> 5) * 512 + (tid & 31) * 8;
                sts64(pa, x0 * sx, x1 * sx);
                sts64(pa + 256, y0 * sy, y1 * sy);
                __syncwarp();
              }
              const uint32_t pr = sbase + OFF_STG + L_P + (tid >> 4) * 256;
              uint32_t* dst = reinterpret_cast<uint32_t*>(p.ob) + (blockIdx.x & 15) * (SEQ * 32) + wg * 16 + (tid & 15) +
                              (((blockIdx.x >> 5) * 512 + (kb4 - 2) * 64 + ((tid >> 4) & 7) * 8) * 2 + ((blockIdx.x >> 4) & 1)) * 32;
#define L_PV(g0)                                                                                       \
  _Pragma("unroll") for (int g = (g0); g < (g0) + 4; g++) {                                            \
    const uint4 a = pw[2 * (g & 3)], b = pw[2 * (g & 3) + 1];                                          \
    const uint32_t w[8] = {a.x, a.y, a.z, a.w, b.x, b.y, b.z, b.w};                                    \
    float o0 = 0.f, o1 = 0.f;                                                                          \
    _Pragma("unroll") for (int c = 0; c < 8; c++) {                                                    \
      const uint32_t u = vw[c > g ? c : c + 8];                                                        \
      o0 = fmaf(__uint_as_float(w[c]), __uint_as_float(u << 16), o0);                                  \
      o1 = fmaf(__uint_as_float(w[c]), __uint_as_float(u & 0xFFFF0000u), o1);                          \
    }                                                                                                  \
    dst[g * 64] = pack_bf16(o0, o1);                                                                   \
  }
#pragma unroll
              for (int j = 0; j < 8; j++) pw[j] = lds128(pr + j * 16);
              mbar_arrive_elect(s_bar + B_AEMPTY + 8, true);
              G_STAGE(0)
              L_PV(0)
#pragma unroll
              for (int j = 0; j < 8; j++) pw[j] = lds128(pr + 128 + j * 16);
              G_STAGE(1)
              L_PV(4)
              __syncwarp();
              mbar_arrive_elect(s_bar + B_OFULL, true);
            }
            G_STAGE(2)
            G_STAGE(3)
            gphase ^= 1;
            kb4++;
          }
          const bool fin = next >= 0x600u;
          for (; kb4 < nkb4 - fin; kb4++) {
            G_STAGE(0)
            G_STAGE(1)
            G_STAGE(2)
            G_STAGE_Y(3, false, kb4 + 1 == nkb4, )
            gphase ^= 1;
          }
          if (fin) break;
          wgmma_wait<0>();
          mbar_arrive_cluster_if(s_bar + B_GEMPTY + 8 * 3, etgt, lane == 0 && (warp & 3) < 2);
          {
            const bool gok = mbar_test(s_bar + B_GFULL, gphase);
            fence_regs(acc);
#pragma unroll
            for (int j = 0; j < 64; j++) pk[j] = pack_bf16(acc[2 * j], acc[2 * j + 1]);
            have = item < 0x100u ? 2 : 1;
            item = next;
            TL0(item);
            G_STAGE_Y(0, true, false, )
          }
        }
        {
          constexpr bool gok = false;
          G_STAGE(0)
#if FS == 2
          G_STAGE(1)
#endif
          wgmma_wait<0>();
          mbar_arrive_cluster_if(s_bar + B_GEMPTY + 8 * (FS - 1), etgt, lane == 0 && (warp & 3) < 2);
          fence_regs(acc);
          float lo[64], hi[64];
#pragma unroll
          for (int j = 0; j < 64; j++) {
            asm volatile("mov.b32 %0, %1;" : "=f"(lo[j]) : "f"(acc[j]));
            asm volatile("mov.b32 %0, %1;" : "=f"(hi[j]) : "f"(acc[64 + j]));
          }
#pragma unroll
          for (int s = FS; s < 4; s++) {
            mbar_wait(s_bar + B_GFULL + 8 * s, gphase);
            const uint32_t da = make_desc(DBASE + OFF_A + ((s * 16384) ^ aswz) + wg * 8192, 16);
            const uint32_t db = make_desc(DBASE + (s ^ rot) * TILE32K, 8192);
            if (s == FS) named_bar_sync(5 + wg, 256);
            wgmma_fence();
            wgmma_ss_n128_tb<0, 0>(lo, da, db, 1);
            wgmma_ss_n128_tb<2, 128>(lo, da, db, 1);
            wgmma_ss_n128_tb<4, 256>(lo, da, db, 1);
            wgmma_ss_n128_tb<6, 384>(lo, da, db, 1);
            wgmma_commit();
          }
          wgmma_fence();
#pragma unroll
          for (int s = FS; s < 4; s++) {
            const uint32_t da = make_desc(DBASE + OFF_A + ((s * 16384) ^ aswz) + wg * 8192, 16);
            const uint32_t db = make_desc(DBASE + (s ^ rot) * TILE32K, 8192);
            wgmma_ss_n128_tb<0, 1024>(hi, da, db, 1);
            wgmma_ss_n128_tb<2, 1152>(hi, da, db, 1);
            wgmma_ss_n128_tb<4, 1280>(hi, da, db, 1);
            wgmma_ss_n128_tb<6, 1408>(hi, da, db, 1);
          }
          wgmma_commit();
          named_bar_arrive_if(6, 256, wg == 0);
          gphase ^= 1;
          const uint32_t so = sbase + stg_off(opaque_tid());
          mbar_wait(s_bar + B_STGFREE, stgpar);
          mbar_wait(s_bar + B_SEMPTY + 16 * wg, 1);
          mbar_wait(s_bar + B_SEMPTY + 16 * wg + 8, 1);
#define FIN_HALF(x, base, stride, bar)                                                                                \
  fence_regs(x);                                                                                                      \
  _Pragma("unroll") for (int j = 0; j < 8; j++)                                                                       \
      stmatrix_x4(((base) ^ ((j & 3) << 5)) + (j >> 2) * (stride), pack_bf16(x[8 * j], x[8 * j + 1]),                 \
                  pack_bf16(x[8 * j + 2], x[8 * j + 3]), pack_bf16(x[8 * j + 4], x[8 * j + 5]), pack_bf16(x[8 * j + 6], x[8 * j + 7])); \
  fence_proxy_async_smem();                                                                                           \
  __syncwarp();                                                                                                       \
  mbar_arrive_elect(s_bar + (bar) + 16 * wg, true);                                                                   \
  mbar_arrive_elect(s_bar + (bar) + 16 * wg + 8, true);
          wgmma_wait<1>();
          FIN_HALF(lo, so + OFF_STG + wg * 8192, 8192, B_SFULL)
          wgmma_wait<0>();
          TRI(12, 8);
#pragma unroll
          for (int s = FS; s < 4; s++) mbar_arrive_cluster_if(s_bar + B_GEMPTY + 8 * s, etgt, lane == 0 && (warp & 3) < 2);
          FIN_HALF(hi, so + OFF_A + (32768 ^ aswz), 16384, B_SFULL2)
          TRI(12, 10);
        }
      }
#ifdef ATT_ONLY
      if (seg == 0) CLUSTER_WAIT();
#endif
      if (seg == 0 && isB && DO_ATT) {
        float o[64], s[64];
        uint32_t pa[32], pb[32];
        undef_regs(o);
        undef_regs(s);
        undef_regs(pa);
        undef_regs(pb);
        uint32_t phase = 0;
        const bool sig = (threadIdx.x & 127) == 0, sig2 = (threadIdx.x & 95) == 0;
        if (wg == 1) named_bar_arrive(1, 256);

#define ISSUE_PV(pr, slot_)                                                             \
  {                                                                                     \
    const uint32_t dv = make_desc(DBASE + (slot_) * TILE32K, 16384);                    \
    if (!phalf) {                                                                       \
      wgmma_fence();                                                                    \
      _Pragma("unroll") for (int k = 0; k < 8; k++)                                     \
          wgmma_rs_n128_tb(o, pr[4 * k], pr[4 * k + 1], pr[4 * k + 2], pr[4 * k + 3], dv + k * 128, (k != 0) || !pfirst); \
      wgmma_commit();                                                                   \
    } else {                                                                            \
      wgmma_fence();                                                                    \
      _Pragma("unroll") for (int k = 0; k < 4; k++)                                     \
          wgmma_rs_n128_tb(o, pr[16 + 4 * k], pr[17 + 4 * k], pr[18 + 4 * k], pr[19 + 4 * k], dv + k * 128, (k != 0) || !pfirst); \
      wgmma_commit();                                                                   \
    }                                                                                   \
  }
#define EPILOGUE(on_)                                                                             \
  _Pragma("unroll") for (int j = 0; j < 8; j++) {                                                 \
    const int b = j * 8;                                                                          \
    stmatrix_x4_p((st_o ^ ((j & 3) << 5)) + (j >> 2) * 16384,                                     \
                  pack_bf16(o[b] * sc0, o[b + 1] * sc0), pack_bf16(o[b + 2] * sc1, o[b + 3] * sc1),   \
                  pack_bf16(o[b + 4] * sc0, o[b + 5] * sc0), pack_bf16(o[b + 6] * sc1, o[b + 7] * sc1), on_); \
  }
#define PUBLISH_O()                                  \
  {                                                  \
    fence_proxy_async_smem();                        \
    __syncwarp();                                    \
    mbar_arrive_elect(s_bar + B_OFULL, true);        \
  }
#define FINAL_SCALE()     \
  {                                                    \
    sc0 = t0 + __shfl_xor_sync(0xffffffffu, t0, 1);    \
    sc1 = t1 + __shfl_xor_sync(0xffffffffu, t1, 1);    \
    t0 = t1 = 0.f;                                     \
    sc0 += __shfl_xor_sync(0xffffffffu, sc0, 2);       \
    sc1 += __shfl_xor_sync(0xffffffffu, sc1, 2);       \
    sc0 = rcp(sc0);            \
    sc1 = rcp(sc1);                                    \
  }
        float l0 = 1.f, l1 = 1.f, t0 = 1.f, t1 = 1.f;
        float b0 = 0.f, b1 = 0.f, sc0 = 0.f, sc1 = 0.f;
        int gen = 0;
        int pfirst = 1;
        int phalf = 2;
        int fresh = 1;
        int diag = blockIdx.x & 1, dlast = !diag;
        int opub = 0;
        int last = 0;
        float rdy = -0.f;
        float x0 = 0.f, x1 = 0.f, x2 = 0.f, x3 = 0.f;
        bool rs = false;
        uint32_t code = p.order[cluster_id - NA_CL];
        int it = 0, nit = 0, rem = (code & 15) + dlast;
        TL0(0x1000 | code | rem);
        const float mrow = float((warp & 3) * 16 + (lane >> 2) - (lane & 3) * 2);
        const float lo0 = mrow < 0.f && wg == HW ? 0.f : SM_LO;
        const uint32_t st_o = sbase + OFF_STG + stg_off(opaque_tid() ^ (HW * 128));
#define MMA_PART(N_, acc_, PIN, PAR)                                                                       \
  {                                                                                                        \
    const uint32_t dq = make_desc(DBASE + OFF_A + (it & 1) * TILE32K + (wg ^ HW) * 8192, 16);              \
    const uint32_t dk = make_desc(DBASE + (PAR) * TILE32K, 16);                                            \
    TRI(0, fresh ? 7 : 0);                                                                                 \
    named_bar_sync(1 + wg, 256);                                                                           \
    TRI(1, fresh ? 6 : 1);                                                                                 \
    wgmma_fence();                                                                                         \
    uint32_t cv;                                                                                           \
    bool rv;                                                                                               \
    _Pragma("unroll") for (int k = 0; k < 8; k++) {                                                        \
      wgmma_ss_n##N_(acc_, dq + (k >> 2) * 1024 + (k & 3) * 2, dk + (k >> 2) * 1024 + (k & 3) * 2, k != 0); \
      if (k == 1) cv = lds32(s_bar + S_CODE + 4 * ((it + 1) & 7));        \
      if (k == 3) rv = mbar_test(s_bar + B_AFULL + 8 * (3 - (PAR)), phase ^ (1 - (PAR)));                  \
    }                                                                                                      \
    wgmma_commit();                                                                                        \
    code = __reduce_or_sync(0xffffffffu, cv);                                                              \
    if (opub) PUBLISH_O();                                                                                 \
    if (N_ == 128 && fresh) FINAL_SCALE();                                                                 \
    last = rem == 0 && (code & 0x8000u);                                                                   \
    nit = it + (rem == 0 && !last);                                                                        \
    mbar_wait_rest(s_bar + B_AFULL + 8 * (3 - (PAR)), phase ^ (1 - (PAR)), rv);                            \
    ISSUE_PV(PIN, 3 - (PAR));                                                                              \
    named_bar_arrive(2 - wg, 256);                                                                         \
    TR(2);                                                                                                 \
    wgmma_wait<1>();                                                                                       \
    fence_regs(acc_);                                                                                      \
    TR(3);                                                                                                 \
    mbar_arrive_cluster_if(s_bar + B_AEMPTY + 8 * (PAR), etgt, sig2);                                      \
    mbar_arrive_if(s_bar + B_QEMPTY + 8 * (it & 1), sig && rem == 0);                                      \
    rs = mbar_test(s_bar + B_STGFREE, ~it & 1) | (it == 0);                                                \
    if (N_ == 64 && fresh) FINAL_SCALE();                                                                  \
    l0 = t0;                                                                                               \
    l1 = t1;                                                                                               \
  }
#define LOW_SUM() ((t0 < lo0) | (t1 < SM_LO))
#define SECOND_HALF(POUT, PAR, FRESH, ...)                                                                 \
  wgmma_wait<0>();                                                                                         \
  fence_regs(o);                                                                                           \
  mbar_arrive_cluster_if(s_bar + B_AEMPTY + 8 * (3 - (PAR)), etgt, sig2 && ((PAR) || !(FRESH) || it > 0)); \
  rdy = mbar_test2(s_bar + B_AFULL + 8 * (1 - (PAR)), phase ^ (PAR), s_bar + B_QFULL + 8 * (nit & 1), (nit >> 1) & 1); \
  TR(8);                                                                                                   \
  __VA_ARGS__;                                                                                             \
  t0 += x0 + x1;                                                                                           \
  t1 += x2 + x3;                                                                                           \
  POUT[16] = pack_bf16(x0, x1);                                                                            \
  POUT[17] = pack_bf16(x2, x3);                                                                            \
  softmax_exp<9, TPOS, false>(s, 0.f, 0.f, POUT, t0, t1);                                                  \
  t0 = addv(t0, rdy);                                                                                      \
  softmax_exp<TPOS, 16, false>(s, 0.f, 0.f, POUT, t0, t1);                                                 \
                                                                                \
  phalf = diag && wg == HW;                                                                                \
  opub = (FRESH) && it > 0;                                                                                \
  pfirst = FRESH;                                                                                          \
  fresh = rem == 0;                                                                                        \
  it = nit;                                                                                                \
  rem = fresh ? (code & 15) + ((blockIdx.x ^ ~it) & 1) : rem - 1;                                          \
  dlast = !((blockIdx.x | it) & 1);                                                                        \
  diag = dlast ? rem == 0 : fresh;                                                                         \
  if (fresh && !last) { TL0(0x1000 | code | rem); }                                                        \
  if (PAR) phase ^= 1;                                                                                     \
                                                      \
  const float lim = __uint_as_float(__float_as_uint(last ? -1.f : SM_HI) | __float_as_uint(rdy));   \
  TR(4);
#ifndef TPOS
#define TPOS 14
#endif
#define SHIFT_S(j0_)                                                                                       \
  if (gen) { _Pragma("unroll") for (int j = (j0_); j < 64; j++) s[j] += (j & 2) ? b1 : b0; }
#define NEXT_STEP(NEXT, LOW)                                                                               \
  if (!__any_sync(0xffffffffu, !(t0 + t1 <= (diag && wg == HW ? -1.f : lim)) | (LOW))) goto plain##NEXT;   \
  if (!__any_sync(0xffffffffu, !(t0 + t1 <= lim) | (LOW))) goto half##NEXT;
#define STEP_END(POUT, PAR, NEXT, ...)                                                                     \
  if (fresh) {                                                                                             \
    __VA_ARGS__;                                                                                           \
    mbar_wait_rest(s_bar + B_STGFREE, ~it & 1, rs);                                                        \
    SECOND_HALF(POUT, PAR, 1, EPILOGUE(it > 0))                                                            \
    if (phalf && opub) {                                                     \
      PUBLISH_O();                                                                                         \
      opub = 0;                                                                                            \
    }                                                                                                      \
    NEXT_STEP(NEXT, LOW_SUM())                                                                             \
  } else {                                                                                                 \
    SECOND_HALF(POUT, PAR, 0, )                                                                            \
    NEXT_STEP(NEXT, false)                                                                                 \
  }
#define STEP_BEGIN(PIN, POUT, PAR, ...)                                                                    \
  {                                                                                                        \
    if (__any_sync(0xffffffffu, !(t0 + t1 <= SM_HI) | (LOW_SUM() & (pfirst != 0)))) {                           \
              \
      if (phalf) { _Pragma("unroll") for (int j = 0; j < 32; j++) asm volatile("mov.b32 %0, 0xff800000;" : "=f"(s[j])); } \
      float d0, d1;                                                                                        \
      softmax_max(s, d0, d1);                                                                              \
      if (!pfirst) {                                                                                       \
        d0 = fmaxf(d0, 0.f);                                                                               \
        d1 = fmaxf(d1, 0.f);                                                                               \
      }                                                                                                    \
      const float r0 = pfirst ? 1.f : ex2(-d0), r1 = pfirst ? 1.f : ex2(-d1);                              \
      t0 = l0 * r0;                                                                                        \
      t1 = l1 * r1;                                                                                        \
      softmax_exp<0, 16, true>(s, -d0, -d1, PIN, t0, t1);                                                  \
      b0 -= d0;                                                                                            \
      b1 -= d1;                                                                                            \
      gen = 1;                                                                                             \
      _Pragma("unroll") for (int j = 0; j < 16; j++) {                                                     \
        o[4 * j] *= r0;                                                                                    \
        o[4 * j + 1] *= r0;                                                                                \
        o[4 * j + 2] *= r1;                                                                                \
        o[4 * j + 3] *= r1;                                                                                \
      }                                                                                                    \
    }                                                                                                      \
    if (last) {                                                                                            \
      __VA_ARGS__;                                                                                         \
      break;                                                                                               \
    }                                                                                                      \
    mbar_wait_rest(s_bar + B_AFULL + 8 * (PAR), phase, __float_as_uint(rdy) == 0);                         \
    mbar_wait_rest(s_bar + B_QFULL + 8 * (it & 1), (it >> 1) & 1, __float_as_uint(rdy) == 0);              \
  }                                                                                                        \
  if (diag && wg == HW) {                                                                                  \
  half##PAR:                                                                                               \
                                                     \
    float sl[32];                                                                                          \
    undef_regs(sl);                                                                                        \
    MMA_PART(64, sl, PIN, PAR)                                                                             \
    _Pragma("unroll") for (int j = 0; j < 32; j++) asm volatile("mov.b32 %0, %1;" : "=f"(s[32 + j]) : "f"(sl[j])); \
    SHIFT_S(32)                                                                                            \
    _Pragma("unroll") for (int j = 0; j < 8; j++) {                                                        \
      if (float(8 * j) > mrow) s[32 + 4 * j] = -3e38f;                                                     \
      if (float(8 * j + 1) > mrow) s[33 + 4 * j] = -3e38f;                                                 \
      if (float(8 * j - 8) > mrow) s[34 + 4 * j] = -3e38f;                                                 \
      if (float(8 * j - 7) > mrow) s[35 + 4 * j] = -3e38f;                                                 \
    }                                                                                                      \
    x0 = ex2v(s[32]), x1 = ex2v(s[33]), x2 = ex2v(s[34]), x3 = ex2v(s[35]);                                \
  } else {                                                                                                 \
  plain##PAR:                                                                                              \
    MMA_PART(128, s, PIN, PAR)                                                                             \
    if (diag || gen) {                                                                                     \
      SHIFT_S(0)                                                                                           \
                                     \
      const float rowf = diag ? mrow : 64.f;                                                               \
      _Pragma("unroll") for (int j = 0; j < 8; j++) {                                                      \
        s[32 + 4 * j] = fmaf(__saturatef(float(8 * j) - rowf), -3e38f, s[32 + 4 * j]);                     \
        s[33 + 4 * j] = fmaf(__saturatef(float(8 * j + 1) - rowf), -3e38f, s[33 + 4 * j]);                 \
        s[34 + 4 * j] = fmaf(__saturatef(float(8 * j - 8) - rowf), -3e38f, s[34 + 4 * j]);                 \
        s[35 + 4 * j] = fmaf(__saturatef(float(8 * j - 7) - rowf), -3e38f, s[35 + 4 * j]);                 \
      }                                                                                                    \
      softmax_exp<0, 8, false>(s, 0.f, 0.f, POUT, t0, t1);                                                 \
      x0 = ex2v(s[32]), x1 = ex2v(s[33]), x2 = ex2v(s[34]), x3 = ex2v(s[35]);                              \
    } else {                                                                                               \
      softmax_exp<0, 8, false>(s, 0.f, 0.f, POUT, t0, t1);                                                 \
      x0 = ex2v(s[32]), x1 = ex2v(s[33]), x2 = ex2v(s[34]), x3 = ex2v(s[35]);                              \
    }                                                                                                      \
  }
        for (;;) {
          STEP_END(pa, 1, 0, if (phalf == 2) { wgmma_wait<0>(); goto begin0; })
        begin0:
          STEP_BEGIN(pa, pb, 0, rot = 0; phase ^= 1)
          STEP_END(pb, 0, 1, )
          STEP_BEGIN(pb, pa, 1, rot = 1; _Pragma("unroll") for (int j = 0; j < 32; j++) asm volatile("mov.b32 %0, %1;" : "=r"(pa[j]) : "r"(pb[j])))
        }
        {
          mbar_wait(s_bar + B_AFULL + 8 * (3 - rot), phase);
          TRI(12, 2);
          ISSUE_PV(pa, 3 - rot);
          if (opub) PUBLISH_O();
          FINAL_SCALE();
          mbar_wait(s_bar + B_STGFREE, it & 1);
          wgmma_wait<0>();
          fence_regs(o);
          TRI(12, 4);
          mbar_arrive_cluster_if(s_bar + B_AEMPTY + 8 * (3 - rot), etgt, sig2);
          EPILOGUE(true);
          PUBLISH_O();
          TRI(12, 5);
          stgpar = ~it & 1;
          tail = tail_item(code);
          aswz = (~it & 1) * TILE32K;
          rot ^= blockIdx.x & ~it & 1;
        }
      }
    }
    TL0(0xFFFF);
    TRI(15, 15);
  }
}

typedef CUresult (*EncodeFn)(CUtensorMap*, CUtensorMapDataType, cuuint32_t, void*, const cuuint64_t*,
                             const cuuint64_t*, const cuuint32_t*, const cuuint32_t*, CUtensorMapInterleave,
                             CUtensorMapSwizzle, CUtensorMapL2promotion, CUtensorMapFloatOOBfill);

EncodeFn get_encode() {
  static EncodeFn fn = nullptr;
  if (!fn) {
    void* p = nullptr;
    cudaDriverEntryPointQueryResult st;
    cudaGetDriverEntryPoint("cuTensorMapEncodeTiled", &p, cudaEnableDefault, &st);
    fn = (EncodeFn)p;
  }
  return fn;
}

void make_map(CUtensorMap* m, const void* ptr, int rows, int cols, int box_rows, int box_groups, bool blocked = false) {
  cuuint64_t dims[3] = {64, (cuuint64_t)rows, (cuuint64_t)(cols / 64)};
  cuuint64_t strides[2] = {(cuuint64_t)(blocked ? 128 : cols * 2), (cuuint64_t)(blocked ? rows * 128 : 128)};
  cuuint32_t box[3] = {64, (cuuint32_t)box_rows, (cuuint32_t)box_groups};
  cuuint32_t es[3] = {1, 1, 1};
  CUtensorMapL2promotion prom = blocked || box_groups == 1 ? CU_TENSOR_MAP_L2_PROMOTION_NONE : CU_TENSOR_MAP_L2_PROMOTION_L2_256B;
  get_encode()(m, CU_TENSOR_MAP_DATA_TYPE_BFLOAT16, 3, const_cast<void*>(ptr), dims, strides, box, es,
               CU_TENSOR_MAP_INTERLEAVE_NONE, CU_TENSOR_MAP_SWIZZLE_128B, prom,
               CU_TENSOR_MAP_FLOAT_OOB_FILL_NONE);
}

void make_store_map(CUtensorMap* m, const void* ptr, int cols, uint64_t s_par, uint64_t s_pair, uint64_t s_grp) {
  cuuint64_t dims[4] = {64, 2, SEQ / 2, (cuuint64_t)(cols / 64)};
  cuuint64_t strides[3] = {s_par, s_pair, s_grp};
  cuuint32_t box[4] = {64, 2, 32, 1};
  cuuint32_t es[4] = {1, 1, 1, 1};
  get_encode()(m, CU_TENSOR_MAP_DATA_TYPE_BFLOAT16, 4, const_cast<void*>(ptr), dims, strides, box, es,
               CU_TENSOR_MAP_INTERLEAVE_NONE, CU_TENSOR_MAP_SWIZZLE_128B, CU_TENSOR_MAP_L2_PROMOTION_NONE,
               CU_TENSOR_MAP_FLOAT_OOB_FILL_NONE);
}

#ifdef SCHED_PRINT
static int envi(const char* n, int d) { const char* e = getenv(n); return e ? (int)strtol(e, 0, 0) : d; }
#define PARAM(name, val) const int name = envi(#name, val)
#else
#define PARAM(name, val) const int name = val
#endif
void build_schedule(Params& p) {
  PARAM(C_KB, 1028);
  PARAM(C_TILE, 10);
  PARAM(C_QX, 0);
  PARAM(C_START, 4500);
  PARAM(C_STEP, 2052);
  PARAM(C_ITEM, 300);
  PARAM(C_LAG, 8000);
  PARAM(C_SP, 5200);
  PARAM(C_TAIL, 22000);
  PARAM(C_SHORT, 0);
  PARAM(C_AT, 72);
  PARAM(C_LATE, 0);
  PARAM(C_LMASK, 0xAA0);
  PARAM(C_AM, 100);
  PARAM(C_ODD, 1300);
  PARAM(C_READY, 10000);
  auto gemm_cost = [&](int prob) {
    static const int nkb[NPROB] = {16, 8, 8, 16, 64, 16};
    return nkb[prob] * C_KB + C_TILE + (prob == 0 ? C_QX : 0);
  };
  memset(p.g, 0xFF, sizeof(p.g));
  int n1[NCLUSTER];
  long t1[NCLUSTER];
  long ready[16];
  for (int c = 0; c < NCLUSTER; c++) { n1[c] = 0; t1[c] = C_START; }
  for (int i = 0; i < 16; i++) ready[i] = 0;
  auto add = [&](int c, int prob, int mp, int nt) {
    p.g[c][n1[c]++] = (uint16_t)((prob << 8) | (mp << 4) | nt);
    t1[c] += gemm_cost(prob);
    if (prob < 3) {
      const long r = t1[c] + C_READY;
      if (r > ready[nt]) ready[nt] = r;
    }
  };
#ifdef GEMM_ONLY
  for (int c = 0; c < NCLUSTER; c++) {
    for (int i = 0; i < 13; i++) add(c, 0, c & 7, (i + (c >> 3) * 2) & 15);
    p.g[c][n1[c]++] = 0x600;
  }
  return;
#endif
#ifdef ATT_ONLY
  for (int c = 0; c < NCLUSTER; c++) { p.g[c][0] = 0x600; p.g[c][1] = 0x500; }
  for (int i = 0; i < 256; i++) p.order[i] = (uint16_t)(((i & 31) << 4) | (14 - 2 * (i >> 5)));
  return;
#endif
  for (int r = 0; r < 8; r++)
    for (int c = 0; c < NA_CL; c++) {
      const int mp = c & 7, nt = 2 * r + ((c >> 3) & 1);
      for (int j = 0; j < (c < 16 ? 1 : 2); j++) {
        add(c, c < 16 ? 0 : 1 + j, mp, nt);
      }
    }
  long tA = 0;
  for (int c = 0; c < NA_CL; c++) {
    if (t1[c] > tA) tA = t1[c];
    add(c, 4, c & 7, c >> 3);
  }
  for (int r = 0; r < 3; r++)
    for (int j = 0; j < 34; j++) {
      if (j >= 32) { if (r < 2) add(NA_CL + j, 3, j & 7, 4 + r); }
      else if (r < 2 || j >= 16 || (j & 7) >= 2) add(NA_CL + j, 3, j & 7, (j >> 3) + (r == 0 ? 0 : r == 1 ? 8 : 4));
    }
  for (int c = NA_CL; c < NCLUSTER; c++) {
    p.g[c][n1[c]++] = 0x600;
    p.g[c][n1[c]++] = 0x500;
  }
  static const uint16_t order[256] = {
    14, 30, 10, 44, 26, 78, 60, 94, 12, 46, 8, 42, 24, 76, 58, 110, 92, 6, 126, 40, 22, 74, 56, 108,
    90, 4, 124, 38, 20, 72, 54, 106, 28, 62, 142, 158, 88, 2, 140, 122, 36, 18, 174, 156, 70, 52, 190, 104,
    86, 0, 138, 120, 34, 16, 172, 154, 68, 50, 206, 188, 102, 84, 222, 136, 118, 32, 170, 152, 66, 48, 204, 186,
    100, 82, 238, 220, 134, 116, 254, 168, 150, 64, 202, 184, 98, 80, 236, 218, 132, 114, 270, 252, 166, 148, 286, 200,
    182, 96, 234, 216, 130, 112, 268, 250, 164, 146, 302, 284, 198, 180, 318, 232, 214, 128, 266, 248, 162, 144, 300, 282,
    196, 178, 334, 316, 230, 212, 350, 264, 246, 160, 310, 328, 382, 194, 314, 360, 192, 340, 278, 298, 274, 208, 342, 366,
    210, 260, 290, 312, 336, 378, 306, 292, 240, 330, 364, 224, 228, 346, 380, 434, 376, 244, 362, 226, 344, 348, 408, 272,
    304, 176, 320, 368, 280, 412, 390, 332, 262, 288, 258, 256, 242, 402, 294, 388, 422, 296, 406, 398, 384, 374, 326, 352,
    400, 414, 394, 276, 322, 418, 392, 396, 370, 356, 324, 410, 386, 430, 462, 494, 446, 510, 478, 484, 482, 354, 498, 404,
    308, 416, 428, 492, 508, 460, 476, 444, 452, 358, 426, 372, 490, 506, 458, 442, 474, 338, 424, 472, 456, 440, 488, 454,
    450, 438, 470, 486, 420, 436, 468, 500, 504, 466, 502, 448, 496, 432, 480, 464,
  };
  memcpy(p.order, order, sizeof(order));
#ifdef SCHED_PRINT
  uint16_t fixed[256];
  memcpy(fixed, p.order, sizeof(fixed));
  long tf[NB_CL];
  bool done[512], started[NB_CL];
  long fin[16];
  int cnt[NB_CL] = {};
  for (int c = 0; c < NB_CL; c++) { tf[c] = t1[NA_CL + c] + 2000; started[c] = false; }
  for (int i = 0; i < 512; i++) done[i] = i & 1;
  for (int i = 0; i < 16; i++) fin[i] = 0;
  auto alen = [&](int qt) { return (long)(2 * qt + 3) * C_STEP / 2 + C_ITEM + (qt < 2 ? C_SHORT : 0); };
  int nq = NB_CL;
  for (int n = 0; n < 256; n++) {
    int cb = 0;
    for (int c = 1; c < NB_CL; c++)
      if (tf[c] < tf[cb]) cb = c;
    int best = -1;
    long bkey = 0;
    for (int i = 0; i < 512; i++) {
      if (done[i]) continue;
      const int hp = i >> 5;
      long dl = -(long)(16 - hp) * C_SP - C_LAG + ((i >> 4) & 1) * C_ODD;
      if (dl > -C_TAIL) dl = -C_TAIL;
      long key = dl - alen(i & 15) * (dl == -C_TAIL ? C_AT : C_AM) / 100;
      if ((i >> 4) == 31 && (C_LMASK >> (i & 15) & 1)) key += C_LATE;
      if (ready[hp] > tf[cb]) key += (1L << 40) + (ready[hp] - tf[cb]) * 1024;
      if (best < 0 || key < bkey) { best = i; bkey = key; }
    }
    done[best] = true;
    if (!started[cb]) { p.order[cb] = (uint16_t)best; started[cb] = true; }
    else p.order[nq++] = (uint16_t)best;
    if (ready[best >> 5] > tf[cb]) tf[cb] = ready[best >> 5];
    tf[cb] += alen(best & 15) + (cnt[cb]++ & 1 ? -C_STEP / 2 : C_STEP / 2);
    if (tf[cb] + C_LAG > fin[best >> 5]) fin[best >> 5] = tf[cb] + C_LAG;
  }
  if (!getenv("HEUR")) memcpy(p.order, fixed, sizeof(fixed));
#endif
#ifdef SCHED_PRINT
  ord_hook(p.order);
  long t = tA, tmin = tf[0], tmax = tf[0];
  printf("sched: outA start %ld, fin:", t);
  for (int hp = 0; hp < 16; hp++) {
    printf(" %ld", fin[hp] - t);
    if (fin[hp] > t) t = fin[hp];
    t += 4 * C_KB;
  }
  for (int c = 0; c < NB_CL; c++) { if (tf[c] < tmin) tmin = tf[c]; if (tf[c] > tmax) tmax = tf[c]; }
  printf("\nA end %ld, attention end %ld..%ld (+%d), ready[15] %ld nq %d\n", t, tmin, tmax, gemm_cost(5), ready[15], nq);
#endif
}

}

extern "C" void kernel_launch(void* const* d_in, const int* in_sizes, int n_in, void* d_out, int out_size) {
  const bf16* A_x = (const bf16*)d_in[0];
  const bf16* A_c = (const bf16*)d_in[1];
  const bf16* A_wq = (const bf16*)d_in[2];
  const bf16* A_wuk = (const bf16*)d_in[3];
  const bf16* A_wuv = (const bf16*)d_in[4];
  const bf16* A_wo = (const bf16*)d_in[5];
  const bf16* B_x = (const bf16*)d_in[6];
  const bf16* B_wqkv = (const bf16*)d_in[7];
  const bf16* B_wo = (const bf16*)d_in[8];
  bf16* out = (bf16*)d_out;

  static Params p;
  static bf16 *q, *k, *v, *ctx, *qkvb, *ob;
  static bool init = false;
  if (!init) {
    cudaGetSymbolAddress((void**)&q, g_q);
    cudaGetSymbolAddress((void**)&k, g_k);
    cudaGetSymbolAddress((void**)&v, g_v);
    cudaGetSymbolAddress((void**)&qkvb, g_qkvb);
    cudaGetSymbolAddress((void**)&ob, g_ob);
    cudaFuncSetAttribute(mega_kernel, cudaFuncAttributeMaxDynamicSharedMemorySize, SMEM_BYTES);
    build_schedule(p);
    ctx = q;
    init = true;
  }
  make_map(&p.ta[0], A_x, SEQ, DM, 128, 1);
  make_map(&p.tb[0], A_wq, DM, HHD, 64, 2);
  make_store_map(&p.tc[0], q, HHD, 128, 256, SEQ * 128);
  make_map(&p.ta[1], A_c, SEQ, DC, 128, 1);
  make_map(&p.tb[1], A_wuk, DC, HHD, 64, 2);
  make_store_map(&p.tc[1], k, HHD, 128, 256, SEQ * 128);
  make_map(&p.ta[2], A_c, SEQ, DC, 128, 1);
  make_map(&p.tb[2], A_wuv, DC, HHD, 64, 2);
  make_store_map(&p.tc[2], v, HHD, 128, 256, SEQ * 128);
  make_map(&p.ta[3], B_x, SEQ, DM, 128, 1);
  make_map(&p.tb[3], B_wqkv, DM, 3 * DM, 64, 2);
  make_store_map(&p.tc[3], qkvb, 3 * DM, SEQ * 64, 128, SEQ * 128);
  make_map(&p.ta[4], ctx, SEQ, HHD, 128, 1, true);
  make_map(&p.tb[4], A_wo, HHD, DM, 64, 2);
  make_store_map(&p.tc[4], out, 2 * DM, 4 * DM, 8 * DM, 128);
  make_map(&p.ta[5], ob, SEQ, DM, 128, 1, true);
  make_map(&p.tb[5], B_wo, DM, DM, 64, 2);
  make_store_map(&p.tc[5], out, 2 * DM, 4 * DM, 8 * DM, 128);
  make_map(&p.tq, q, SEQ, HHD, 128, 2, true);
  make_map(&p.tk, k, SEQ, HHD, 128, 1, true);
  make_map(&p.tv, v, SEQ, HHD, 128, 1, true);
  make_map(&p.tl, qkvb, SEQ / 2, 6 * DM, 64, 1, true);
  make_map(&p.th, qkvb, SEQ / 2, 6 * DM, 72, 1, true);
  make_map(&p.to, ctx, SEQ, HHD, 128, 2, true);
  p.ob = ob;
  mega_kernel<<<NCTA, 384, SMEM_BYTES, cudaStreamPerThread>>>(p);
}
```

```cpp
#include <cuda_runtime.h>
#include <cuda_bf16.h>
#include <cuda.h>
#include <stdint.h>
#include <string.h>

namespace {

typedef __nv_bfloat16 bf16;

constexpr int SEQ = 2048;
constexpr int NHEAD = 32;
constexpr int HD = 128;
constexpr int DM = 1024;
constexpr int DC = 512;
constexpr int HHD = NHEAD * HD;

__device__ __align__(1024) bf16 g_q[SEQ * HHD];
__device__ __align__(1024) bf16 g_k[SEQ * HHD];
__device__ __align__(1024) bf16 g_v[SEQ * HHD];
__device__ __align__(1024) bf16 g_qkvb[SEQ * 3 * DM];
__device__ __align__(1024) bf16 g_ob[SEQ * DM];
constexpr int CNT_QKV = 0, CNT_CTX = 16, CNT_QKVB = 32, CNT_DONE = 33, CNT_QUEUE = 34, CNT_OB = 35, CNT_N = 39;
__device__ uint32_t g_cnt[CNT_N * 8];
#ifdef TIMELINE
__device__ __align__(16) unsigned long long g_tl[132 * 4 * 64];
#endif


__device__ __forceinline__ uint32_t smem_u32(const void* p) {
  return static_cast<uint32_t>(__cvta_generic_to_shared(p));
}
__device__ __forceinline__ void mbar_init(uint32_t bar, uint32_t count) {
  asm volatile("mbarrier.init.shared::cta.b64 [%0], %1;" ::"r"(bar), "r"(count) : "memory");
}
__device__ __forceinline__ void mbar_expect_tx(uint32_t bar, uint32_t bytes) {
  asm volatile("mbarrier.arrive.expect_tx.shared::cta.b64 _, [%0], %1;" ::"r"(bar), "r"(bytes) : "memory");
}
__device__ __forceinline__ void mbar_arrive(uint32_t bar) {
  asm volatile("mbarrier.arrive.shared::cta.b64 _, [%0];" ::"r"(bar) : "memory");
}
__device__ __forceinline__ void mbar_arrive_if(uint32_t bar, bool on) {
  asm volatile("{\n.reg .pred p;\nsetp.ne.b32 p, %1, 0;\n@p mbarrier.arrive.shared::cta.b64 _, [%0];\n}" ::"r"(bar),
               "r"((int)on)
               : "memory");
}
__device__ __forceinline__ void mbar_arrive_cluster_if(uint32_t bar, uint32_t cta, bool on) {
  asm volatile(
      "{\n.reg .b32 ra;\n.reg .pred p;\nsetp.ne.b32 p, %2, 0;\nmapa.shared::cluster.u32 ra, %0, %1;\n"
      "@p mbarrier.arrive.shared::cluster.b64 _, [ra];\n}" ::"r"(bar),
      "r"(cta), "r"((int)on)
      : "memory");
}
__device__ __forceinline__ bool mbar_try_wait(uint32_t bar, uint32_t parity) {
  uint32_t ok;
  asm volatile(
      "{\n.reg .pred p;\nmbarrier.try_wait.parity.shared::cta.b64 p, [%1], %2;\nselp.u32 %0, 1, 0, p;\n}"
      : "=r"(ok)
      : "r"(bar), "r"(parity)
      : "memory");
  return ok != 0;
}
__device__ __forceinline__ bool mbar_test(uint32_t bar, uint32_t parity) {
  uint32_t ok;
  asm volatile(
      "{\n.reg .pred p;\nmbarrier.test_wait.parity.shared::cta.b64 p, [%1], %2;\nselp.u32 %0, 1, 0, p;\n}"
      : "=r"(ok)
      : "r"(bar), "r"(parity)
      : "memory");
  return ok != 0;
}
#ifdef DBGW
__device__ uint32_t* g_dbg;
__device__ __forceinline__ void mbar_wait_l(uint32_t bar, uint32_t parity, int line) {
  uint32_t t0 = clock();
  bool rec = false;
  while (!mbar_try_wait(bar, parity)) {
    uint32_t d = clock() - t0;
    if (d > (1u << 26) && !rec) { rec = true; g_dbg[blockIdx.x * 16 + (threadIdx.x >> 5)] = (bar & 1023) | (parity << 12) | (line << 16); __threadfence_system(); }
    if (d > (1u << 28)) __trap();
  }
}
#define mbar_wait(b, p) mbar_wait_l(b, p, __LINE__)
#define DBG(i, v) *(volatile uint32_t*)(g_dbg + blockIdx.x * 16 + (i)) = (v)
__device__ __forceinline__ void mbar_wait_unused(uint32_t bar, uint32_t parity) {
#else
#define DBG(i, v)
__device__ __forceinline__ void mbar_wait(uint32_t bar, uint32_t parity) {
#endif
  asm volatile(
      "{\n.reg .pred p;\n.reg .u32 t;\n"
      "mbarrier.try_wait.parity.shared::cta.b64 p, [%0], %1;\n"
      "@p bra DONE;\n"
      "mov.u32 t, 0x100000;\n"
      "LAB_WAIT:\n"
      "mbarrier.try_wait.parity.shared::cta.b64 p, [%0], %1;\n"
      "@p bra DONE;\n"
      "sub.u32 t, t, 1;\n"
      "setp.ne.u32 p, t, 0;\n"
      "@p bra LAB_WAIT;\n"
      "trap;\n"
      "DONE:\n}" ::"r"(bar),
      "r"(parity)
      : "memory");
}
constexpr uint64_t EV_NORMAL = 0x1000000000000000ull;
__device__ __forceinline__ uint64_t policy_first() {
  uint64_t p;
  asm("createpolicy.fractional.L2::evict_first.b64 %0, 1.0;" : "=l"(p));
  return p;
}
#define EV_FIRST policy_first()
__device__ __forceinline__ void tma_load_3d(uint32_t dst, const CUtensorMap* map, int c0, int c1, int c2,
                                            uint32_t bar, uint64_t hint) {
  asm volatile(
      "cp.async.bulk.tensor.3d.shared::cluster.global.mbarrier::complete_tx::bytes.L2::cache_hint [%0], [%1, {%3, %4, %5}], [%2], %6;" ::"r"(dst),
      "l"(map), "r"(bar), "r"(c0), "r"(c1), "r"(c2), "l"(hint)
      : "memory");
}
__device__ __forceinline__ void tma_load_3d_mc(uint32_t dst, const CUtensorMap* map, int c0, int c1, int c2,
                                               uint32_t bar, uint16_t mask, uint64_t hint) {
  asm volatile(
      "cp.async.bulk.tensor.3d.shared::cluster.global.mbarrier::complete_tx::bytes.multicast::cluster.L2::cache_hint [%0], [%1, {%3, %4, %5}], [%2], %6, %7;" ::"r"(dst),
      "l"(map), "r"(bar), "r"(c0), "r"(c1), "r"(c2), "h"(mask), "l"(hint)
      : "memory");
}
__device__ __forceinline__ void tma_store_3d(const CUtensorMap* map, uint32_t src, int c0, int c1, int c2, uint64_t hint) {
  asm volatile("cp.async.bulk.tensor.3d.global.shared::cta.bulk_group.L2::cache_hint [%0, {%2, %3, %4}], [%1], %5;" ::"l"(map),
               "r"(src), "r"(c0), "r"(c1), "r"(c2), "l"(hint)
               : "memory");
}
__device__ __forceinline__ void tma_store_4d(const CUtensorMap* map, uint32_t src, int c2, int c3, uint64_t hint) {
  asm volatile("cp.async.bulk.tensor.4d.global.shared::cta.bulk_group.L2::cache_hint [%0, {%2, %2, %3, %4}], [%1], %5;" ::"l"(map),
               "r"(src), "r"(0), "r"(c2), "r"(c3), "l"(hint)
               : "memory");
}
__device__ __forceinline__ void bulk_commit() { asm volatile("cp.async.bulk.commit_group;" ::: "memory"); }
template <int N>
__device__ __forceinline__ void bulk_wait_read() {
  asm volatile("cp.async.bulk.wait_group.read %0;" ::"n"(N) : "memory");
}
template <int N>
__device__ __forceinline__ void bulk_wait() {
  asm volatile("cp.async.bulk.wait_group %0;" ::"n"(N) : "memory");
}
__device__ __forceinline__ void fence_proxy_async_smem() {
  asm volatile("fence.proxy.async.shared::cta;" ::: "memory");
}
__device__ __forceinline__ bool elect_one() {
  uint32_t pred;
  asm volatile("{\n.reg .pred P;\nelect.sync _|P, 0xffffffff;\nselp.b32 %0, 1, 0, P;\n}" : "=r"(pred));
  return pred != 0;
}
__device__ __forceinline__ void named_bar_sync(int id, int n) {
  asm volatile("bar.sync %0, %1;" ::"r"(id), "r"(n) : "memory");
}
__device__ __forceinline__ void named_bar_arrive(int id, int n) {
  asm volatile("bar.arrive %0, %1;" ::"r"(id), "r"(n) : "memory");
}
__device__ __forceinline__ void named_bar_sync_if(int id, int n, bool on) {
  asm volatile("{\n.reg .pred p;\nsetp.ne.b32 p, %2, 0;\n@p bar.sync %0, %1;\n}" ::"r"(id), "r"(n), "r"((int)on) : "memory");
}
__device__ __forceinline__ void named_bar_arrive_if(int id, int n, bool on) {
  asm volatile("{\n.reg .pred p;\nsetp.ne.b32 p, %2, 0;\n@p bar.arrive %0, %1;\n}" ::"r"(id), "r"(n), "r"((int)on) : "memory");
}
template <int N>
__device__ __forceinline__ void reg_alloc() {
  asm volatile("setmaxnreg.inc.sync.aligned.u32 %0;" ::"n"(N));
}
template <int N>
__device__ __forceinline__ void reg_dealloc() {
  asm volatile("setmaxnreg.dec.sync.aligned.u32 %0;" ::"n"(N));
}
__device__ __forceinline__ void wgmma_fence() { asm volatile("wgmma.fence.sync.aligned;" ::: "memory"); }
__device__ __forceinline__ void wgmma_commit() { asm volatile("wgmma.commit_group.sync.aligned;" ::: "memory"); }
template <int N>
__device__ __forceinline__ void wgmma_wait() {
  asm volatile("wgmma.wait_group.sync.aligned %0;" ::"n"(N) : "memory");
}
template <int N>
__device__ __forceinline__ void fence_regs(float (&d)[N]) {
#pragma unroll
  for (int i = 0; i < N; i++) asm volatile("" : "+f"(d[i])::"memory");
}
__device__ __forceinline__ void fence_regs(uint32_t (&d)[32]) {
#pragma unroll
  for (int i = 0; i < 16; i++) asm volatile("" : "+r"(d[i])::"memory");
}
template <int N>
__device__ __forceinline__ void undef_regs(float (&d)[N]) {
#pragma unroll
  for (int i = 0; i < N; i++) d[i] = 0.f;
}
template <int N>
__device__ __forceinline__ void undef_regs(uint32_t (&d)[N]) {
#pragma unroll
  for (int i = 0; i < N; i++) d[i] = 0u;
}
__device__ __forceinline__ uint32_t pack_bf16(float lo, float hi) {
  uint32_t r;
  asm("cvt.rn.bf16x2.f32 %0, %1, %2;" : "=r"(r) : "f"(hi), "f"(lo));
  return r;
}
__device__ __forceinline__ void stmatrix_x4(uint32_t addr, uint32_t r0, uint32_t r1, uint32_t r2, uint32_t r3) {
  asm volatile("stmatrix.sync.aligned.m8n8.x4.shared.b16 [%0], {%1, %2, %3, %4};" ::"r"(addr), "r"(r0), "r"(r1),
               "r"(r2), "r"(r3)
               : "memory");
}
__device__ __forceinline__ void stmatrix_x4_p(uint32_t addr, uint32_t r0, uint32_t r1, uint32_t r2, uint32_t r3,
                                              bool on) {
  asm volatile("{\n.reg .pred p;\nsetp.ne.b32 p, %5, 0;\n@p stmatrix.sync.aligned.m8n8.x4.shared.b16 [%0], {%1, %2, %3, %4};\n}" ::"r"(addr),
               "r"(r0), "r"(r1), "r"(r2), "r"(r3), "r"((int)on)
               : "memory");
}
__device__ __forceinline__ float ex2(float x) {
  float y;
  asm("ex2.approx.ftz.f32 %0, %1;" : "=f"(y) : "f"(x));
  return y;
}
__device__ __forceinline__ float rcp(float x) {
  float y;
  asm("rcp.approx.ftz.f32 %0, %1;" : "=f"(y) : "f"(x));
  return y;
}
__device__ __forceinline__ float ex2v(float x) {
  float y;
  asm volatile("ex2.approx.ftz.f32 %0, %1;" : "=f"(y) : "f"(x));
  return y;
}
__device__ __forceinline__ float addv(float a, float b) {
  float y;
  asm volatile("add.f32 %0, %1, %2;" : "=f"(y) : "f"(a), "f"(b));
  return y;
}
__device__ __forceinline__ void mbar_arrive_elect(uint32_t bar, bool on) {
  asm volatile("{\n.reg .pred p, q;\nelect.sync _|q, 0xffffffff;\nsetp.ne.and.b32 p, %1, 0, q;\n@p mbarrier.arrive.shared::cta.b64 _, [%0];\n}" ::"r"(bar),
               "r"((int)on)
               : "memory");
}
__device__ __forceinline__ float mbar_test2(uint32_t bar0, uint32_t par0, uint32_t bar1, uint32_t par1) {
  float f;
  asm volatile(
      "{\n.reg .pred p, q;\nmbarrier.test_wait.parity.shared::cta.b64 p, [%1], %2;\n"
      "mbarrier.test_wait.parity.shared::cta.b64 q, [%3], %4;\nand.pred p, p, q;\nselp.f32 %0, 0f00000000, 0f80000000, p;\n}"
      : "=f"(f)
      : "r"(bar0), "r"(par0), "r"(bar1), "r"(par1)
      : "memory");
  return f;
}
__device__ __forceinline__ void mbar_wait_rest(uint32_t bar, uint32_t parity, bool ok) {
  asm volatile(
      "{\n.reg .pred p;\n.reg .u32 t;\n"
      "setp.ne.b32 p, %2, 0;\n"
      "@p bra DONE;\n"
      "mov.u32 t, 0x100000;\n"
      "LAB_WAIT:\n"
      "mbarrier.try_wait.parity.shared::cta.b64 p, [%0], %1;\n"
      "@p bra DONE;\n"
      "sub.u32 t, t, 1;\n"
      "setp.ne.u32 p, t, 0;\n"
      "@p bra LAB_WAIT;\n"
      "trap;\n"
      "DONE:\n}" ::"r"(bar),
      "r"(parity), "r"((int)ok)
      : "memory");
}
__device__ __forceinline__ void send_peer(uint32_t addr, uint32_t bar, uint32_t v) {
  asm volatile(
      "{\n.reg .b32 ra, rb;\nmapa.shared::cluster.u32 ra, %0, 1;\nmapa.shared::cluster.u32 rb, %1, 1;\n"
      "st.async.weak.shared::cluster.mbarrier::complete_tx::bytes.b32 [ra], %2, [rb];\n}" ::"r"(addr),
      "r"(bar), "r"(v)
      : "memory");
}
__device__ __forceinline__ void cnt_signal(int idx, uint32_t inc = 1) {
  asm volatile("red.release.gpu.global.add.u32 [%0], %1;" ::"l"(g_cnt + idx * 8), "r"(inc) : "memory");
}
__device__ __forceinline__ void cnt_signal_done(int idx, uint32_t inc = 1) {
  asm volatile("fence.proxy.async.global;" ::: "memory");
  cnt_signal(idx, inc);
}
__device__ __forceinline__ uint32_t cnt_next(int idx) {
  uint32_t v;
  asm volatile("atom.relaxed.gpu.global.add.u32 %0, [%1], 1;" : "=r"(v) : "l"(g_cnt + idx * 8) : "memory");
  return v;
}
__device__ __forceinline__ uint32_t cnt_peek(int idx) {
  uint32_t v;
  asm volatile("ld.acquire.gpu.global.u32 %0, [%1];" : "=r"(v) : "l"(g_cnt + idx * 8) : "memory");
  return v;
}
__device__ __forceinline__ void cnt_wait(int idx, uint32_t target) {
  asm volatile(
      "{\n.reg .pred p;\n.reg .u32 v, t0, t1;\n"
      "ld.acquire.gpu.global.u32 v, [%0];\n"
      "setp.ge.u32 p, v, %1;\n"
      "@p bra DONE;\n"
      "mov.u32 t0, %%clock;\n"
      "LAB_WAIT:\n"
      "nanosleep.u32 100;\n"
      "ld.acquire.gpu.global.u32 v, [%0];\n"
      "setp.ge.u32 p, v, %1;\n"
      "@p bra DONE;\n"
      "mov.u32 t1, %%clock;\n"
      "sub.u32 t1, t1, t0;\n"
      "setp.lt.u32 p, t1, 0x80000000;\n"
      "@p bra LAB_WAIT;\n"
      "trap;\n"
      "DONE:\n}" ::"l"(g_cnt + idx * 8),
      "r"(target)
      : "memory");
}
__device__ __forceinline__ void cnt_wait_bit(int idx, uint32_t bit, uint32_t& v) {
  asm volatile(
      "{\n.reg .pred p;\n.reg .u32 x, t0, t1;\n"
      "and.b32 x, %0, %2;\n"
      "setp.ne.u32 p, x, 0;\n"
      "@p bra DONE;\n"
      "mov.u32 t0, %%clock;\n"
      "LAB_WAIT:\n"
      "ld.acquire.gpu.global.u32 %0, [%1];\n"
      "and.b32 x, %0, %2;\n"
      "setp.ne.u32 p, x, 0;\n"
      "@p bra DONE;\n"
      "nanosleep.u32 64;\n"
      "mov.u32 t1, %%clock;\n"
      "sub.u32 t1, t1, t0;\n"
      "setp.lt.u32 p, t1, 0x80000000;\n"
      "@p bra LAB_WAIT;\n"
      "trap;\n"
      "DONE:\n}" : "+r"(v) : "l"(g_cnt + idx * 8),
      "r"(bit)
      : "memory");
}
__device__ __forceinline__ bool cnt_done(uint32_t total) {
  uint32_t old;
  asm volatile("atom.acq_rel.gpu.global.add.u32 %0, [%1], 1;" : "=r"(old) : "l"(g_cnt + CNT_DONE * 8) : "memory");
  return old == total - 1;
}
__device__ __forceinline__ void cnt_rearm() {
#pragma unroll
  for (int i = 0; i < CNT_N; i++) g_cnt[i * 8] = 0;
}
__device__ __forceinline__ void fence_proxy_async_global() { asm volatile("fence.proxy.async.global;" ::: "memory"); }
#ifdef TIMELINE
__device__ __forceinline__ void tl_rec(int role, int& n, uint32_t code) {
  unsigned long long t;
  asm volatile("mov.u64 %0, %%globaltimer;" : "=l"(t));
  uint32_t c;
  asm volatile("mov.u32 %0, %%clock;" : "=r"(c));
  if (n < 32) {
    g_tl[(blockIdx.x * 4 + role) * 64 + 2 * n] = t;
    g_tl[(blockIdx.x * 4 + role) * 64 + 2 * n + 1] = ((unsigned long long)code << 32) | c;
  }
  n++;
}
#define TL(role, code) tl_rec(role, tln, code)
__device__ __forceinline__ void tl_rec_p(int role, int& n, uint32_t code, bool on) {
  unsigned long long t;
  asm volatile("mov.u64 %0, %%globaltimer;" : "=l"(t));
  uint32_t c;
  asm volatile("mov.u32 %0, %%clock;" : "=r"(c));
  asm volatile("{\n.reg .pred p;\nsetp.ne.b32 p, %3, 0;\n@p st.global.v2.u64 [%0], {%1, %2};\n}" ::"l"(g_tl + (blockIdx.x * 4 + role) * 64 + 2 * n),
               "l"(t), "l"(((unsigned long long)code << 32) | c), "r"((int)(on && n < 32)) : "memory");
  n++;
}
#define TL0(code) tl_rec_p(0, tln, code, threadIdx.x == 0)
#define TL_DECL int tln = 0
#ifdef TLWAIT
#define TW_DECL uint32_t w0 = 0, w1 = 0, w2 = 0, w3 = 0; int tln3 = 0
#define TW(w, stmt) { uint32_t c0_ = clock(); stmt; w += clock() - c0_; }
#define TW_FLUSH() { tl_rec_p(3, tln3, (min(w0, 65534u) << 16) | min(w1, 65534u), threadIdx.x == TLWAIT); tl_rec_p(3, tln3, (min(w2, 65534u) << 16) | min(w3, 65534u), threadIdx.x == TLWAIT); w0 = w1 = w2 = w3 = 0; }
#define TW_END() tl_rec_p(3, tln3, 0xFFFF, threadIdx.x == TLWAIT)
#endif
#else
#define TL(role, code)
#define TL0(code)
#define TL_DECL
#endif
#ifdef TRACE
__device__ uint32_t g_tr[2 * 2 * 4096];
#define TR_DECL int trn = 0; const bool tron = (blockIdx.x == TRACE || blockIdx.x == TRACE2) && (threadIdx.x & 127) == TRW * 32; uint32_t* trp = g_tr + ((blockIdx.x == TRACE ? 0 : 2) + (threadIdx.x >> 7)) * 4096
#ifndef TRW
#define TRW 0
#endif
#ifndef TRM
#define TRM 0xFFFF
#endif
#define TRI(id, code) if ((TRM >> (id)) & 1) { asm volatile("{\n.reg .pred p;\nsetp.ne.b32 p, %2, 0;\n@p st.global.u32 [%0], %1;\n}" ::"l"(trp + trn), "r"(((uint32_t)clock() << 4) | (code)), "r"((int)(tron && trn < 4095)) : "memory"); trn++; }
#define TR(code) TRI(code, code)
#else
#define TR_DECL
#define TR(code)
#define TRI(id, code)
#endif
#ifndef TLWAIT
#define TW_DECL
#define TW(w, stmt) stmt
#define TW_FLUSH()
#define TW_END()
#endif

__device__ __forceinline__ uint32_t make_desc(uint32_t addr, uint32_t lbo_bytes) {
  return (addr >> 4) + ((lbo_bytes >> 4) << 16);
}

__device__ __forceinline__ void wgmma_ss_n128(float (&d)[64], uint32_t da, uint32_t db, int scale_d) {
  asm volatile("{\n.reg .pred p;\n.reg .b64 a, b;\nsetp.ne.b32 p, %66, 0;\nmov.b64 a, {%64, 0x40000040};\nmov.b64 b, {%65, 0x40000040};\n"
    "wgmma.mma_async.sync.aligned.m64n128k16.f32.bf16.bf16 {%0, %1, %2, %3, %4, %5, %6, %7, %8, %9, %10, %11, %12, %13, %14, %15, %16, %17, %18, %19, %20, %21, %22, %23, %24, %25, %26, %27, %28, %29, %30, %31, %32, %33, %34, %35, %36, %37, %38, %39, %40, %41, %42, %43, %44, %45, %46, %47, %48, %49, %50, %51, %52, %53, %54, %55, %56, %57, %58, %59, %60, %61, %62, %63}, a, b, p, 1, 1, 0, 0;\n}\n"
    : "+f"(d[0]), "+f"(d[1]), "+f"(d[2]), "+f"(d[3]), "+f"(d[4]), "+f"(d[5]), "+f"(d[6]), "+f"(d[7]), "+f"(d[8]), "+f"(d[9]), "+f"(d[10]), "+f"(d[11]), "+f"(d[12]), "+f"(d[13]), "+f"(d[14]), "+f"(d[15]), "+f"(d[16]), "+f"(d[17]), "+f"(d[18]), "+f"(d[19]), "+f"(d[20]), "+f"(d[21]), "+f"(d[22]), "+f"(d[23]), "+f"(d[24]), "+f"(d[25]), "+f"(d[26]), "+f"(d[27]), "+f"(d[28]), "+f"(d[29]), "+f"(d[30]), "+f"(d[31]), "+f"(d[32]), "+f"(d[33]), "+f"(d[34]), "+f"(d[35]), "+f"(d[36]), "+f"(d[37]), "+f"(d[38]), "+f"(d[39]), "+f"(d[40]), "+f"(d[41]), "+f"(d[42]), "+f"(d[43]), "+f"(d[44]), "+f"(d[45]), "+f"(d[46]), "+f"(d[47]), "+f"(d[48]), "+f"(d[49]), "+f"(d[50]), "+f"(d[51]), "+f"(d[52]), "+f"(d[53]), "+f"(d[54]), "+f"(d[55]), "+f"(d[56]), "+f"(d[57]), "+f"(d[58]), "+f"(d[59]), "+f"(d[60]), "+f"(d[61]), "+f"(d[62]), "+f"(d[63])
    : "r"(da), "r"(db), "r"(scale_d));
}
__device__ __forceinline__ void wgmma_ss_n64(float (&d)[32], uint32_t da, uint32_t db, int scale_d) {
  asm volatile("{\n.reg .pred p;\n.reg .b64 a, b;\nsetp.ne.b32 p, %34, 0;\nmov.b64 a, {%32, 0x40000040};\nmov.b64 b, {%33, 0x40000040};\n"
    "wgmma.mma_async.sync.aligned.m64n64k16.f32.bf16.bf16 {%0, %1, %2, %3, %4, %5, %6, %7, %8, %9, %10, %11, %12, %13, %14, %15, %16, %17, %18, %19, %20, %21, %22, %23, %24, %25, %26, %27, %28, %29, %30, %31}, a, b, p, 1, 1, 0, 0;\n}\n"
    : "+f"(d[0]), "+f"(d[1]), "+f"(d[2]), "+f"(d[3]), "+f"(d[4]), "+f"(d[5]), "+f"(d[6]), "+f"(d[7]), "+f"(d[8]), "+f"(d[9]), "+f"(d[10]), "+f"(d[11]), "+f"(d[12]), "+f"(d[13]), "+f"(d[14]), "+f"(d[15]), "+f"(d[16]), "+f"(d[17]), "+f"(d[18]), "+f"(d[19]), "+f"(d[20]), "+f"(d[21]), "+f"(d[22]), "+f"(d[23]), "+f"(d[24]), "+f"(d[25]), "+f"(d[26]), "+f"(d[27]), "+f"(d[28]), "+f"(d[29]), "+f"(d[30]), "+f"(d[31])
    : "r"(da), "r"(db), "r"(scale_d));
}
__device__ __forceinline__ void wgmma_rs_n128_tb(float (&d)[64], uint32_t a0, uint32_t a1, uint32_t a2, uint32_t a3, uint32_t db, int scale_d) {
  asm volatile("{\n.reg .pred p;\n.reg .b64 b;\nsetp.ne.b32 p, %69, 0;\nmov.b64 b, {%68, 0x40000040};\n"
    "wgmma.mma_async.sync.aligned.m64n128k16.f32.bf16.bf16 {%0, %1, %2, %3, %4, %5, %6, %7, %8, %9, %10, %11, %12, %13, %14, %15, %16, %17, %18, %19, %20, %21, %22, %23, %24, %25, %26, %27, %28, %29, %30, %31, %32, %33, %34, %35, %36, %37, %38, %39, %40, %41, %42, %43, %44, %45, %46, %47, %48, %49, %50, %51, %52, %53, %54, %55, %56, %57, %58, %59, %60, %61, %62, %63}, {%64, %65, %66, %67}, b, p, 1, 1, 1;\n}\n"
    : "+f"(d[0]), "+f"(d[1]), "+f"(d[2]), "+f"(d[3]), "+f"(d[4]), "+f"(d[5]), "+f"(d[6]), "+f"(d[7]), "+f"(d[8]), "+f"(d[9]), "+f"(d[10]), "+f"(d[11]), "+f"(d[12]), "+f"(d[13]), "+f"(d[14]), "+f"(d[15]), "+f"(d[16]), "+f"(d[17]), "+f"(d[18]), "+f"(d[19]), "+f"(d[20]), "+f"(d[21]), "+f"(d[22]), "+f"(d[23]), "+f"(d[24]), "+f"(d[25]), "+f"(d[26]), "+f"(d[27]), "+f"(d[28]), "+f"(d[29]), "+f"(d[30]), "+f"(d[31]), "+f"(d[32]), "+f"(d[33]), "+f"(d[34]), "+f"(d[35]), "+f"(d[36]), "+f"(d[37]), "+f"(d[38]), "+f"(d[39]), "+f"(d[40]), "+f"(d[41]), "+f"(d[42]), "+f"(d[43]), "+f"(d[44]), "+f"(d[45]), "+f"(d[46]), "+f"(d[47]), "+f"(d[48]), "+f"(d[49]), "+f"(d[50]), "+f"(d[51]), "+f"(d[52]), "+f"(d[53]), "+f"(d[54]), "+f"(d[55]), "+f"(d[56]), "+f"(d[57]), "+f"(d[58]), "+f"(d[59]), "+f"(d[60]), "+f"(d[61]), "+f"(d[62]), "+f"(d[63])
    : "r"(a0), "r"(a1), "r"(a2), "r"(a3), "r"(db), "r"(scale_d));
}
__device__ __forceinline__ void wgmma_ss_n72_init(float (&d)[36], uint32_t da, uint32_t db) {
  asm volatile("{\n.reg .pred p;\n.reg .b64 a, b;\nsetp.ne.b32 p, 0, 0;\nmov.b64 a, {%36, 0x40000040};\nmov.b64 b, {%37, 0x40000040};\n"
    "wgmma.mma_async.sync.aligned.m64n72k16.f32.bf16.bf16 {%0, %1, %2, %3, %4, %5, %6, %7, %8, %9, %10, %11, %12, %13, %14, %15, %16, %17, %18, %19, %20, %21, %22, %23, %24, %25, %26, %27, %28, %29, %30, %31, %32, %33, %34, %35}, a, b, p, 1, 1, 0, 0;\n}\n"
    : "=f"(d[0]), "=f"(d[1]), "=f"(d[2]), "=f"(d[3]), "=f"(d[4]), "=f"(d[5]), "=f"(d[6]), "=f"(d[7]), "=f"(d[8]), "=f"(d[9]), "=f"(d[10]), "=f"(d[11]), "=f"(d[12]), "=f"(d[13]), "=f"(d[14]), "=f"(d[15]), "=f"(d[16]), "=f"(d[17]), "=f"(d[18]), "=f"(d[19]), "=f"(d[20]), "=f"(d[21]), "=f"(d[22]), "=f"(d[23]), "=f"(d[24]), "=f"(d[25]), "=f"(d[26]), "=f"(d[27]), "=f"(d[28]), "=f"(d[29]), "=f"(d[30]), "=f"(d[31]), "=f"(d[32]), "=f"(d[33]), "=f"(d[34]), "=f"(d[35])
    : "r"(da), "r"(db));
}
__device__ __forceinline__ void wgmma_ss_n72(float (&d)[36], uint32_t da, uint32_t db, int scale_d) {
  asm volatile("{\n.reg .pred p;\n.reg .b64 a, b;\nsetp.ne.b32 p, %38, 0;\nmov.b64 a, {%36, 0x40000040};\nmov.b64 b, {%37, 0x40000040};\n"
    "wgmma.mma_async.sync.aligned.m64n72k16.f32.bf16.bf16 {%0, %1, %2, %3, %4, %5, %6, %7, %8, %9, %10, %11, %12, %13, %14, %15, %16, %17, %18, %19, %20, %21, %22, %23, %24, %25, %26, %27, %28, %29, %30, %31, %32, %33, %34, %35}, a, b, p, 1, 1, 0, 0;\n}\n"
    : "+f"(d[0]), "+f"(d[1]), "+f"(d[2]), "+f"(d[3]), "+f"(d[4]), "+f"(d[5]), "+f"(d[6]), "+f"(d[7]), "+f"(d[8]), "+f"(d[9]), "+f"(d[10]), "+f"(d[11]), "+f"(d[12]), "+f"(d[13]), "+f"(d[14]), "+f"(d[15]), "+f"(d[16]), "+f"(d[17]), "+f"(d[18]), "+f"(d[19]), "+f"(d[20]), "+f"(d[21]), "+f"(d[22]), "+f"(d[23]), "+f"(d[24]), "+f"(d[25]), "+f"(d[26]), "+f"(d[27]), "+f"(d[28]), "+f"(d[29]), "+f"(d[30]), "+f"(d[31]), "+f"(d[32]), "+f"(d[33]), "+f"(d[34]), "+f"(d[35])
    : "r"(da), "r"(db), "r"(scale_d));
}
template <int OA, int OB>
__device__ __forceinline__ void wgmma_ss_n128_tb(float (&d)[64], uint32_t da, uint32_t db, int scale_d) {
  asm volatile("{\n.reg .pred p;\n.reg .b64 a, b;\n.reg .b32 x, y;\nsetp.ne.b32 p, %66, 0;\nadd.u32 x, %64, %67;\nadd.u32 y, %65, %68;\nmov.b64 a, {x, 0x40000040};\nmov.b64 b, {y, 0x40000040};\n"
    "wgmma.mma_async.sync.aligned.m64n128k16.f32.bf16.bf16 {%0, %1, %2, %3, %4, %5, %6, %7, %8, %9, %10, %11, %12, %13, %14, %15, %16, %17, %18, %19, %20, %21, %22, %23, %24, %25, %26, %27, %28, %29, %30, %31, %32, %33, %34, %35, %36, %37, %38, %39, %40, %41, %42, %43, %44, %45, %46, %47, %48, %49, %50, %51, %52, %53, %54, %55, %56, %57, %58, %59, %60, %61, %62, %63}, a, b, p, 1, 1, 0, 1;\n}\n"
    : "+f"(d[0]), "+f"(d[1]), "+f"(d[2]), "+f"(d[3]), "+f"(d[4]), "+f"(d[5]), "+f"(d[6]), "+f"(d[7]), "+f"(d[8]), "+f"(d[9]), "+f"(d[10]), "+f"(d[11]), "+f"(d[12]), "+f"(d[13]), "+f"(d[14]), "+f"(d[15]), "+f"(d[16]), "+f"(d[17]), "+f"(d[18]), "+f"(d[19]), "+f"(d[20]), "+f"(d[21]), "+f"(d[22]), "+f"(d[23]), "+f"(d[24]), "+f"(d[25]), "+f"(d[26]), "+f"(d[27]), "+f"(d[28]), "+f"(d[29]), "+f"(d[30]), "+f"(d[31]), "+f"(d[32]), "+f"(d[33]), "+f"(d[34]), "+f"(d[35]), "+f"(d[36]), "+f"(d[37]), "+f"(d[38]), "+f"(d[39]), "+f"(d[40]), "+f"(d[41]), "+f"(d[42]), "+f"(d[43]), "+f"(d[44]), "+f"(d[45]), "+f"(d[46]), "+f"(d[47]), "+f"(d[48]), "+f"(d[49]), "+f"(d[50]), "+f"(d[51]), "+f"(d[52]), "+f"(d[53]), "+f"(d[54]), "+f"(d[55]), "+f"(d[56]), "+f"(d[57]), "+f"(d[58]), "+f"(d[59]), "+f"(d[60]), "+f"(d[61]), "+f"(d[62]), "+f"(d[63])
    : "r"(da), "r"(db), "r"(scale_d), "n"(OA), "n"(OB));
}
template <int OA, int OB>
__device__ __forceinline__ void wgmma_ss_n256_tbo(float (&d)[128], uint32_t da, uint32_t db, int scale_d) {
  asm volatile("{\n.reg .pred p;\n.reg .b64 a, b;\n.reg .b32 x, y;\nsetp.ne.b32 p, %130, 0;\nadd.u32 x, %128, %131;\nadd.u32 y, %129, %132;\nmov.b64 a, {x, 0x40000040};\nmov.b64 b, {y, 0x40000040};\n"
    "wgmma.mma_async.sync.aligned.m64n256k16.f32.bf16.bf16 {%0, %1, %2, %3, %4, %5, %6, %7, %8, %9, %10, %11, %12, %13, %14, %15, %16, %17, %18, %19, %20, %21, %22, %23, %24, %25, %26, %27, %28, %29, %30, %31, %32, %33, %34, %35, %36, %37, %38, %39, %40, %41, %42, %43, %44, %45, %46, %47, %48, %49, %50, %51, %52, %53, %54, %55, %56, %57, %58, %59, %60, %61, %62, %63, %64, %65, %66, %67, %68, %69, %70, %71, %72, %73, %74, %75, %76, %77, %78, %79, %80, %81, %82, %83, %84, %85, %86, %87, %88, %89, %90, %91, %92, %93, %94, %95, %96, %97, %98, %99, %100, %101, %102, %103, %104, %105, %106, %107, %108, %109, %110, %111, %112, %113, %114, %115, %116, %117, %118, %119, %120, %121, %122, %123, %124, %125, %126, %127}, a, b, p, 1, 1, 0, 1;\n}\n"
    : "+f"(d[0]), "+f"(d[1]), "+f"(d[2]), "+f"(d[3]), "+f"(d[4]), "+f"(d[5]), "+f"(d[6]), "+f"(d[7]), "+f"(d[8]), "+f"(d[9]), "+f"(d[10]), "+f"(d[11]), "+f"(d[12]), "+f"(d[13]), "+f"(d[14]), "+f"(d[15]), "+f"(d[16]), "+f"(d[17]), "+f"(d[18]), "+f"(d[19]), "+f"(d[20]), "+f"(d[21]), "+f"(d[22]), "+f"(d[23]), "+f"(d[24]), "+f"(d[25]), "+f"(d[26]), "+f"(d[27]), "+f"(d[28]), "+f"(d[29]), "+f"(d[30]), "+f"(d[31]), "+f"(d[32]), "+f"(d[33]), "+f"(d[34]), "+f"(d[35]), "+f"(d[36]), "+f"(d[37]), "+f"(d[38]), "+f"(d[39]), "+f"(d[40]), "+f"(d[41]), "+f"(d[42]), "+f"(d[43]), "+f"(d[44]), "+f"(d[45]), "+f"(d[46]), "+f"(d[47]), "+f"(d[48]), "+f"(d[49]), "+f"(d[50]), "+f"(d[51]), "+f"(d[52]), "+f"(d[53]), "+f"(d[54]), "+f"(d[55]), "+f"(d[56]), "+f"(d[57]), "+f"(d[58]), "+f"(d[59]), "+f"(d[60]), "+f"(d[61]), "+f"(d[62]), "+f"(d[63]), "+f"(d[64]), "+f"(d[65]), "+f"(d[66]), "+f"(d[67]), "+f"(d[68]), "+f"(d[69]), "+f"(d[70]), "+f"(d[71]), "+f"(d[72]), "+f"(d[73]), "+f"(d[74]), "+f"(d[75]), "+f"(d[76]), "+f"(d[77]), "+f"(d[78]), "+f"(d[79]), "+f"(d[80]), "+f"(d[81]), "+f"(d[82]), "+f"(d[83]), "+f"(d[84]), "+f"(d[85]), "+f"(d[86]), "+f"(d[87]), "+f"(d[88]), "+f"(d[89]), "+f"(d[90]), "+f"(d[91]), "+f"(d[92]), "+f"(d[93]), "+f"(d[94]), "+f"(d[95]), "+f"(d[96]), "+f"(d[97]), "+f"(d[98]), "+f"(d[99]), "+f"(d[100]), "+f"(d[101]), "+f"(d[102]), "+f"(d[103]), "+f"(d[104]), "+f"(d[105]), "+f"(d[106]), "+f"(d[107]), "+f"(d[108]), "+f"(d[109]), "+f"(d[110]), "+f"(d[111]), "+f"(d[112]), "+f"(d[113]), "+f"(d[114]), "+f"(d[115]), "+f"(d[116]), "+f"(d[117]), "+f"(d[118]), "+f"(d[119]), "+f"(d[120]), "+f"(d[121]), "+f"(d[122]), "+f"(d[123]), "+f"(d[124]), "+f"(d[125]), "+f"(d[126]), "+f"(d[127])
    : "r"(da), "r"(db), "r"(scale_d), "n"(OA), "n"(OB));
}

constexpr int NCTA = 132;
constexpr int NCLUSTER = 66;
constexpr int NPROB = 6;
#ifdef GEMM_ONLY
#define DO_LOCAL false
#define DO_ATT false
#else
#define DO_LOCAL true
#define DO_ATT true
#endif
#ifdef ATT_ONLY
#define NA_CL_ 0
#define NITEMS 768
#else
#define NA_CL_ 32
#define NITEMS 256
#endif
constexpr int G1_MAX = 24, NA_CL = NA_CL_, NB_CL = NCLUSTER - NA_CL;
constexpr int TILE32K = 32768;
constexpr uint32_t DBASE = 1024;
constexpr int OFF_STG = 4 * TILE32K;
constexpr int OFF_A = 5 * TILE32K;
constexpr int OFF_BAR = 7 * TILE32K;
constexpr int L_K = 8192, L_V = L_K + 9216, L_P = L_V + 9216;
constexpr int SMEM_BYTES = OFF_BAR + 1024;
constexpr int B_GFULL = 0, B_GEMPTY = 32, B_AFULL = 64, B_AEMPTY = 104, B_QFULL = 144, B_QEMPTY = 160,
              B_SFULL = 176, B_SEMPTY = 208, B_OFULL = 240, B_STGFREE = 256, S_CODE = 272, B_SFULL2 = 304,
              B_MAIL = 336, S_MAIL = 368;
#ifndef FS
#define FS 2
#endif
#ifndef HW
#define HW 1
#endif
#ifndef PACE
#define PACE 900u
#endif
#ifndef REG_C
#define REG_C 232
#define REG_P 40
#endif

struct Params {
  CUtensorMap ta[NPROB];
  CUtensorMap tb[NPROB];
  CUtensorMap tc[NPROB];
  CUtensorMap tq, tk, tv, to, tl, th;
  bf16* ob;
  uint16_t g[NCLUSTER][G1_MAX];
  uint16_t order[256];
};
__device__ __forceinline__ uint32_t tail_item(uint32_t code) {
  return (code & 0x7FFF) < 32 ? (5u << 8) | ((code & 4) << 4) | ((code & 0x18) << 1) | (code & 3) : 0xFFFFu;
}
#ifndef HM
#define HM 0x39383F00
#endif
#define HINT(b) ((HM >> (b) & 1) ? EV_FIRST : EV_NORMAL)
__device__ __forceinline__ uint32_t lds32(uint32_t a) {
  uint32_t v;
  asm volatile("ld.shared.u32 %0, [%1];" : "=r"(v) : "r"(a) : "memory");
  return v;
}
__device__ __forceinline__ uint4 lds128(uint32_t a) {
  uint4 v;
  asm volatile("ld.shared.v4.u32 {%0, %1, %2, %3}, [%4];" : "=r"(v.x), "=r"(v.y), "=r"(v.z), "=r"(v.w) : "r"(a) : "memory");
  return v;
}
__device__ __forceinline__ void sts64(uint32_t a, float x, float y) {
  asm volatile("st.shared.v2.f32 [%0], {%1, %2};" ::"r"(a), "f"(x), "f"(y) : "memory");
}
__device__ __forceinline__ void sts32(uint32_t a, uint32_t v) {
  asm volatile("st.shared.u32 [%0], %1;" ::"r"(a), "r"(v) : "memory");
}
__device__ __forceinline__ uint32_t opaque_tid() {
  uint32_t t;
  asm volatile("mov.u32 %0, %%tid.x;" : "=r"(t));
  return t;
}
__device__ __forceinline__ uint32_t stg_off(uint32_t tid) {
  return (tid >> 5) * 2048 + (tid & 15) * 128 + ((((tid >> 4) & 1) ^ (tid & 7)) << 4);
}
__device__ __forceinline__ int prob_nkb4(int prob) { return (0x4F4224 >> (prob * 4) & 15) + (prob == 4); }

constexpr float SM_C = 0.08838834764831845f * 1.4426950408889634f;
constexpr float SM_HI = 1099511627776.0f;
constexpr float SM_LO = 8.673617379884035e-19f;
__device__ __forceinline__ void softmax_max(const float (&s)[64], float& a0, float& a1) {
  a0 = fmaxf(s[0], s[1]);
  a1 = fmaxf(s[2], s[3]);
#pragma unroll
  for (int j = 1; j < 16; j++) {
    a0 = fmaxf(a0, fmaxf(s[4 * j], s[4 * j + 1]));
    a1 = fmaxf(a1, fmaxf(s[4 * j + 2], s[4 * j + 3]));
  }
  a0 = fmaxf(a0, __shfl_xor_sync(0xffffffffu, a0, 1));
  a1 = fmaxf(a1, __shfl_xor_sync(0xffffffffu, a1, 1));
  a0 = fmaxf(a0, __shfl_xor_sync(0xffffffffu, a0, 2));
  a1 = fmaxf(a1, __shfl_xor_sync(0xffffffffu, a1, 2));
}
template <int J0, int J1, bool OFS, int N>
__device__ __forceinline__ void softmax_exp(const float (&s)[64], float b0, float b1, uint32_t (&out)[N], float& t0,
                                            float& t1) {
#pragma unroll
  for (int j = J0; j < J1; j++) {
    const float e0 = ex2(OFS ? s[4 * j] + b0 : s[4 * j]);
    const float e1 = ex2(OFS ? s[4 * j + 1] + b0 : s[4 * j + 1]);
    const float e2 = ex2(OFS ? s[4 * j + 2] + b1 : s[4 * j + 2]);
    const float e3 = ex2(OFS ? s[4 * j + 3] + b1 : s[4 * j + 3]);
    t0 += e0 + e1;
    t1 += e2 + e3;
    out[2 * j] = pack_bf16(e0, e1);
    out[2 * j + 1] = pack_bf16(e2, e3);
  }
}

__device__ __forceinline__ uint32_t scale_q(uint32_t x) {
  uint32_t t, y;
  asm("mul.rn.bf16x2 %0, %1, %2;" : "=r"(t) : "r"(x), "r"(0xb9d8b9d8u));
  asm("fma.rn.bf16x2 %0, %1, %2, %3;" : "=r"(y) : "r"(x), "r"(0x3e033e03u), "r"(t));
  return y;
}

__global__ void __cluster_dims__(2, 1, 1) __launch_bounds__(384, 1) mega_kernel(const __grid_constant__ Params p) {
  extern __shared__ __align__(1024) uint8_t smem_raw[];
#ifdef TRACE
  const uint32_t c_entry = clock();
#endif
  const uint32_t sbase = smem_u32(smem_raw);
  const uint32_t s_bar = sbase + OFF_BAR;
  const int cluster_id = blockIdx.x >> 1;
  const bool isB = cluster_id >= NA_CL;
#if !defined(ATT_ONLY) && !defined(GEMM_ONLY)
#define EARLY 1
#else
#define EARLY 0
#endif
  const int prob0 = isB ? 3 : cluster_id >> 4;
  const int ng0 = (isB ? (cluster_id - NA_CL) >> 3 : (cluster_id >> 3) & 1) * 4;
  const uint32_t t0 = clock();
  auto early = [&](int s) {
    const uint32_t full = s_bar + B_GFULL + 8 * s;
    mbar_expect_tx(full, 49152);
    tma_load_3d(sbase + OFF_A + s * 16384, &p.ta[prob0], 0, (blockIdx.x & 15) * 128, s, full, EV_NORMAL);
    tma_load_3d(sbase + s * TILE32K, &p.tb[prob0], 0, s * 64, ng0, full, EV_NORMAL);
    tma_load_3d(sbase + s * TILE32K + 16384, &p.tb[prob0], 0, s * 64, ng0 + 2, full, EV_NORMAL);
  };
  if ((threadIdx.x >> 5) == 8) {
    if (elect_one()) {
      mbar_init(s_bar + B_GFULL, 1);
      asm volatile("fence.mbarrier_init.release.cluster;" ::: "memory");
      if (EARLY) early(0);
      for (int s = 1; s < 4; s++) mbar_init(s_bar + B_GFULL + 8 * s, 1);
      asm volatile("fence.mbarrier_init.release.cluster;" ::: "memory");
    }
    __syncwarp();
    named_bar_arrive(7, 288);
  }
  const int warp0 = __shfl_sync(0xffffffffu, threadIdx.x >> 5, 0);
  if (warp0 >= 8) reg_dealloc<REG_P>();
#define CLUSTER_ARRIVE() asm volatile("barrier.cluster.arrive.relaxed.aligned;" ::: "memory")
#define CLUSTER_WAIT() asm volatile("barrier.cluster.wait.acquire.aligned;" ::: "memory")

  if (warp0 >= 8) {
    if (warp0 == 10 && elect_one()) {
      if ((sbase & 0x3FFFFu) != DBASE) __trap();
      for (int s = 0; s < 4; s++) {
        mbar_init(s_bar + B_GEMPTY + 8 * s, 4);
        mbar_init(s_bar + B_SFULL + 8 * s, 4);
        mbar_init(s_bar + B_SFULL2 + 8 * s, 4);
        mbar_init(s_bar + B_SEMPTY + 8 * s, 1);
        mbar_init(s_bar + B_AFULL + 8 * s, 1);
        mbar_init(s_bar + B_AEMPTY + 8 * s, isB ? 4 : s ? 8 : 2);
        mbar_init(s_bar + B_MAIL + 8 * s, 1);
      }
      for (int s = 0; s < 2; s++) {
        mbar_init(s_bar + B_QFULL + 8 * s, 1);
        mbar_init(s_bar + B_QEMPTY + 8 * s, 2);
      }
      mbar_init(s_bar + B_OFULL, 8);
      mbar_init(s_bar + B_STGFREE, 1);
      asm volatile("fence.mbarrier_init.release.cluster;" ::: "memory");
    }
    __syncwarp();
    CLUSTER_ARRIVE();
    if (EARLY && warp0 == 8 && elect_one()) {
#pragma unroll 1
      for (int s = 1; s < 4; s++) {
        while ((uint32_t)clock() - t0 < s * PACE) {}
        early(s);
      }
    }
    __syncwarp();
    CLUSTER_WAIT();
    const uint32_t rank = blockIdx.x & 1;
    if (warp0 == 8) {
      if (elect_one()) {
        TL_DECL;
        uint32_t gphase = 1 - EARLY;
        uint32_t tail = 0;
        int gi = 0;
        uint32_t aswz = 0, lastq = 0, n = 0;
        uint32_t aprev = ~0u;
        for (int seg = 0; seg < 2; seg++) {
          for (;;) {
            uint32_t item = p.g[cluster_id][gi++];
            if (item == 0x500u) item = tail;
            if (item >= 0x600u) break;
            const int prob = item >> 8;
            const int rt = ((item >> 4) & 15) * 2 + rank;
            const int ngrp0 = (item & 15) * 4;
            const int nkb4 = prob_nkb4(prob);
            const CUtensorMap* ta = &p.ta[prob];
            const CUtensorMap* tb = &p.tb[prob];
            const uint64_t ahint = p.g[cluster_id][gi] >= 0x400u ? EV_FIRST : EV_NORMAL;
            const int rot4 = prob < 4 ? 1 - gi : 0;
            const uint32_t akey = (item + 0x100u) & 0x6F0u;
            const bool keep = akey == aprev;
            aprev = akey;
            TL(1, item);
            uint32_t seen = 0;
            if (prob == 5) {
              cnt_wait_bit(CNT_OB + (rt >> 2), 32u << (rt & 3) * 8, seen);
              fence_proxy_async_global();
            }
            for (int kb4 = EARLY && gi == 1; kb4 < nkb4; kb4++) {
#pragma unroll 1
              for (int s = 0; s < 4; s++) {
                const int bs = s ^ (n & 1);
                if (prob == 4 && !(s & 1)) {
                  cnt_wait_bit(CNT_CTX + rt, 1u << (kb4 * 2 + (s >> 1)), seen);
                  fence_proxy_async_global();
                }
                if (prob == 5 && kb4 == 0) {
                  mbar_wait(s_bar + B_AEMPTY + 8 * bs, (~(n + (s & 1)) >> 1) & 1);
                  if (s == 2) mbar_wait(s_bar + B_QEMPTY + (aswz ? 0 : 8), lastq);
                }
                mbar_wait(s_bar + B_GEMPTY + 8 * s, gphase);
                const uint32_t full = s_bar + B_GFULL + 8 * s;
                const int kb = ((kb4 + rot4) & (nkb4 - 1)) * 4 + s;
                if (keep && kb4 == 0) {
                  mbar_expect_tx(full, 32768);
                } else {
                  mbar_expect_tx(full, 49152);
                  tma_load_3d(sbase + OFF_A + ((s * 16384) ^ aswz), ta, 0, rt * 128, kb, full, ahint);
                }
                tma_load_3d_mc(sbase + bs * TILE32K + rank * 16384, tb, 0, kb * 64, ngrp0 + rank * 2, full,
                               (uint16_t)3, HINT(8 + prob));
              }
              gphase ^= 1;
            }
          }
          if (seg == 0 && isB && DO_ATT) {
            int pv_row = 0, pv_col = 0;
            uint64_t pv_hint = 0;
            bool pv_own = false;
#define ACQ_SLOT(slot, n)                                                              \
  {                                                                                    \
    if ((n) < 2) mbar_wait(s_bar + B_GEMPTY + 8 * (slot), gphase);                     \
    mbar_wait(s_bar + B_AEMPTY + 8 * (slot), (~(n) >> 1) & 1);                         \
  }
#define LOAD_KV(map, slot, row, col, own, hint)                                        \
  {                                                                                    \
    const uint32_t full = s_bar + B_AFULL + 8 * (slot);                                \
    mbar_expect_tx(full, TILE32K);                                                     \
    if (own) {                                                                         \
      tma_load_3d(sbase + (slot) * TILE32K, map, 0, row, col, full, hint);             \
      tma_load_3d(sbase + (slot) * TILE32K + 16384, map, 0, row, (col) + 1, full, hint); \
    } else {                                                                           \
      tma_load_3d_mc(sbase + (slot) * TILE32K + rank * 16384, map, 0, row, (col) + rank, full, (uint16_t)3, hint); \
    }                                                                                  \
  }
#define LOAD_V()                                                                       \
  {                                                                                    \
    const uint32_t vs = 3 - (n & 1);                                                   \
    ACQ_SLOT(vs, n - 1);                                                               \
    LOAD_KV(&p.tv, vs, pv_row, pv_col, pv_own, pv_hint)                                \
  }
#ifdef ATT_ONLY
#define NEXT_CODE() (nxt < NITEMS ? p.order[nxt & 255] : 0x8000u + 64)
#else
#define NEXT_CODE() (nxt < 256 ? p.order[nxt] : nxt + (0x8000u - 256))
#endif
            uint32_t code = p.order[cluster_id - NA_CL];
            int it = 0;
            uint32_t seen = 0;
            for (;; it++) {
              if (it == 1) mbar_wait(s_bar + B_STGFREE, 0);
              if (code & 0x8000u) break;
              const int head = code >> 4;
              const int q0 = code & 15, up = rank == (it & 1);
              uint32_t nxt = 0;
              TL(1, 0x1000 | code | up);
#ifndef ATT_ONLY
              if (seen < 48) cnt_wait(CNT_QKV + (head >> 1), 48);
#endif
              fence_proxy_async_global();
              {
                const int b = it & 1;
                if (it < 2) {
                  mbar_wait(s_bar + B_GEMPTY + 16 * b, gphase);
                  mbar_wait(s_bar + B_GEMPTY + 16 * b + 8, gphase);
                }
                mbar_wait(s_bar + B_QEMPTY + 8 * b, ((it >> 1) & 1) ^ 1);
                mbar_expect_tx(s_bar + B_QFULL + 8 * b, TILE32K);
                tma_load_3d(sbase + OFF_A + b * TILE32K, &p.tq, 0, (q0 + up) * 128, head * 2, s_bar + B_QFULL + 8 * b, HINT(24));
              }
#pragma unroll 1
              for (int i = q0 + (up & it); i >= -(up & ~it); i--) {
                const int t = i < 0 ? q0 + 1 : i;
                if (rank == 0 && i == min(q0, 1)) nxt = cnt_next(CNT_QUEUE) + NB_CL;
                if (i == 0) {
                  if (rank == 0) {
                    code = NEXT_CODE();
                    send_peer(s_bar + S_MAIL + 4 * (it & 3), s_bar + B_MAIL + 8 * (it & 3), code);
                  } else {
                    mbar_expect_tx(s_bar + B_MAIL + 8 * (it & 3), 4);
                    mbar_wait(s_bar + B_MAIL + 8 * (it & 3), (it >> 2) & 1);
                    code = lds32(s_bar + S_MAIL + 4 * (it & 3));
                  }
                  sts32(s_bar + S_CODE + 4 * ((it + 1) & 7), code);
                  seen = cnt_peek(CNT_QKV + ((code >> 5) & 15));
                }
                ACQ_SLOT(n & 1, n);
                LOAD_KV(&p.tk, n & 1, t * 128, head * 2, t > q0, HINT(t >= q0 ? 29 : 25))
                if (n) LOAD_V();
                n++;
                pv_row = t * 128;
                pv_col = head * 2;
                pv_own = t > q0;
                pv_hint = HINT(t >= q0 ? 29 : 26);
              }
            }
            ACQ_SLOT(n & 1, n);
            mbar_arrive(s_bar + B_AFULL + 8 * (n & 1));
            LOAD_V();
            if (rank & it) {
              ACQ_SLOT(2 + (n & 1), n);
#pragma unroll 1
              for (int i = 0; i < 8; i++) mbar_arrive_cluster_if(s_bar + B_AEMPTY + 8 * ((n & 1) + (i & 2)), i & 1, true);
              n++;
            }
            tail = tail_item(code);
            aswz = (it & 1) * TILE32K;
            mbar_wait(s_bar + B_QEMPTY + 8 * (it & 1), ((it >> 1) & 1) ^ 1);
            lastq = ((it - 1) >> 1) & 1;
            if (tail == 0xFFFFu) {
#pragma unroll 1
              for (int s = 0; s < 4; s++) mbar_wait(s_bar + B_AEMPTY + 8 * (s ^ (n & 1)), (~(n + (s & 1)) >> 1) & 1);
            }
          }
        }
        if (cnt_done(NCTA * 2)) cnt_rearm();
#pragma unroll 1
        for (int s = 0; s < 4; s++) mbar_wait(s_bar + B_GEMPTY + 8 * s, gphase);
        TL(1, 0xFFFF);
      }
    } else if (warp0 == 9) {
      if (elect_one()) {
        TL_DECL;
        uint32_t tail = 0;
        int gi = 0;
        uint32_t aswz = 0;
        bool rearm = false;
        for (int seg = 0; seg < 2; seg++) {
          for (;;) {
            uint32_t item = p.g[cluster_id][gi++];
            if (item == 0x500u) item = tail;
            if (item >= 0x600u) break;
            const int prob = item >> 8;
            const int rt = ((item >> 4) & 15) * 2 + rank;
            const int cg = (item & 15) * 4 + (prob == 5 ? 16 : 0);
            const CUtensorMap* tc = &p.tc[prob];
            const int nl = (p.g[cluster_id][gi] >> 8) == 4 && DO_LOCAL ? 8 : 1;
            const int grp = (blockIdx.x & 15) * 2 + ((blockIdx.x >> 4) & 1), r0 = (blockIdx.x >> 5) * 512;
            if (nl > 1) {
              cnt_wait(CNT_QKVB, 192);
              fence_proxy_async_global();
            }
            if (prob >= 4) rearm = cnt_done(NCTA * 2);
            const bool lastt = p.g[cluster_id][gi] >= 0x600u;
#pragma unroll 1
            for (int c = 0; c < 8; c++) {
              const int q = lastt ? c & 3 : c >> 1, w = lastt ? c >> 2 : c & 1;
              const int idx = w * 2 + (q & 1);
              const bool alt = lastt && q >= 2;
              mbar_wait(s_bar + (alt ? B_SFULL2 : B_SFULL) + 8 * idx, lastt ? seg : q >> 1);
              tma_store_4d(tc, sbase + (alt ? OFF_A + ((q * 16384) ^ aswz) + w * 8192 : OFF_STG + idx * 8192),
                           rt * 64 + w * 32, cg + q, HINT(16 + prob));
              bulk_commit();
              if (c > 0 && !lastt) {
                bulk_wait_read<1>();
                mbar_arrive(s_bar + B_SEMPTY + 8 * ((w ^ 1) * 2 + (((c - 1) >> 1) & 1)));
              }
            }
            bulk_wait_read<0>();
            mbar_arrive(s_bar + (lastt ? B_STGFREE : B_SEMPTY + 8 * 3));
#pragma unroll 1
            for (int c = 0; c < nl; c++) {
              if (nl > 1) {
                mbar_wait(s_bar + B_AEMPTY, (c & 1) ^ 1);
                mbar_expect_tx(s_bar + B_AFULL, L_V);
                tma_load_3d(sbase + OFF_STG, &p.tl, 0, r0 + c * 64, grp, s_bar + B_AFULL, HINT(28));
                tma_load_3d(sbase + OFF_STG + L_K, &p.th, 0, r0 + c * 64 - 8, 32 + grp, s_bar + B_AFULL, HINT(28));
                mbar_wait(s_bar + B_AEMPTY + 8, (c & 1) ^ 1);
                mbar_expect_tx(s_bar + B_AFULL + 8, 9216);
                tma_load_3d(sbase + OFF_STG + L_V, &p.th, 0, r0 + c * 64 - 8, 64 + grp, s_bar + B_AFULL + 8, HINT(28));
              }
              if (c) {
                mbar_wait(s_bar + B_OFULL, ~c & 1);
                cnt_signal(CNT_OB + (blockIdx.x >> 5) * 2 + ((c - 1) >> 2), 1u << ((c - 1) & 3) * 8);
              } else if (prob < 4) {
                bulk_wait<0>();
                cnt_signal_done(prob == 3 ? CNT_QKVB : CNT_QKV + (item & 15));
                TL(2, item);
              }
            }
            if (nl > 1) {
              mbar_wait(s_bar + B_OFULL, 1);
              cnt_signal(CNT_OB + (blockIdx.x >> 5) * 2 + 1, 1u << 24);
              TL(2, 0x600);
            }
          }
          if (seg == 0 && isB && DO_ATT) {
#ifdef ATT_ONLY
            mbar_arrive(s_bar + B_STGFREE);
#endif
            uint32_t code = p.order[cluster_id - NA_CL];
            for (int it = 0; !(code & 0x8000u); it++) {
              code |= rank == (it & 1);
              aswz = (~it & 1) * TILE32K;
              mbar_wait(s_bar + B_OFULL, it & 1);
              tma_store_3d(&p.to, sbase + OFF_STG, 0, (code & 15) * 128, (code >> 4) * 2, HINT(27));
              bulk_commit();
              const uint32_t nxt = lds32(s_bar + S_CODE + 4 * ((it + 1) & 7));
              bulk_wait_read<0>();
              mbar_arrive(s_bar + B_STGFREE);
              bulk_wait<0>();
              cnt_signal_done(CNT_CTX + (code & 15), 1u << (code >> 4));
              TL(2, 0x1000 | code);
              code = nxt;
            }
            tail = tail_item(code);
            if (tail == 0xFFFFu) rearm = cnt_done(NCTA * 2);
          }
        }
        if (rearm) cnt_rearm();
        TL(2, 0xFFFF);
      }
    }
  } else {
    CLUSTER_ARRIVE();
    reg_alloc<REG_C>();
    named_bar_sync(7, 288);
    const int warp = __shfl_sync(0xffffffffu, opaque_tid() >> 5, 0);
    const int wg = warp >> 2;
    const int lane = threadIdx.x & 31;
    TL_DECL;
    TR_DECL;
#ifdef TRACE
    if (tron) trp[trn] = (c_entry << 4) | 12;
    trn++;
    TRI(9, 13);
#endif
    uint32_t gphase = 0;
    uint32_t tail = 0, aswz = 0, rot = 0, stgpar = 1;
    const uint32_t etgt = warp & 1;
    int gi = 0;
    for (int seg = 0; seg < 2; seg++) {
      uint32_t item = p.g[cluster_id][gi++];
      if (item == 0x500u) item = tail;
      if (item < 0x600u) {
        float acc[128];
        uint32_t pk[64];
        int have = 0;
#define G_STORE_CHUNK(q)                                                                               \
  {                                                                                                    \
    const uint32_t st_base = sbase + OFF_STG + wg * 8192 + stg_off(opaque_tid());                      \
    if (have == 2) { _Pragma("unroll") for (int j = 0; j < 16; j++) pk[(q) * 16 + j] = scale_q(pk[(q) * 16 + j]); } \
    mbar_wait(s_bar + B_SEMPTY + 8 * (wg * 2 + ((q) & 1)), (((q) >> 1) & 1) ^ 1);                      \
    _Pragma("unroll") for (int j = 0; j < 4; j++)                                                      \
        stmatrix_x4((st_base ^ (j << 5)) + ((q) & 1) * 8192, pk[(q) * 16 + j * 4],                     \
                    pk[(q) * 16 + j * 4 + 1], pk[(q) * 16 + j * 4 + 2], pk[(q) * 16 + j * 4 + 3]);     \
    fence_proxy_async_smem();                                                                          \
    __syncwarp();                                                                                      \
    mbar_arrive_elect(s_bar + B_SFULL + 8 * (wg * 2 + ((q) & 1)), true);                              \
  }
#define G_STAGE(s) G_STAGE_Y(s, false, false, )
#define G_STAGE_X(s, ...) G_STAGE_Y(s, false, false, __VA_ARGS__)
#define G_STAGE_Y(s, first, last, ...)                                                                    \
  {                                                                                                       \
    mbar_wait_rest(s_bar + B_GFULL + 8 * (s), gphase, gok && (first));                                    \
    TR(9);                                                                                                \
    const uint32_t da = make_desc(DBASE + OFF_A + (((s) * 16384) ^ aswz) + wg * 8192, 16);                \
    const uint32_t db = make_desc(DBASE + ((s) ^ rot) * TILE32K, 8192);                                   \
    named_bar_sync_if(5 + wg, 256, !(first));                                                             \
    wgmma_fence();                                                                                        \
    _Pragma("unroll") for (int k = 0; k < 5; k++) {                                                       \
      __VA_ARGS__;                                                                                        \
      if (k == 0) wgmma_ss_n256_tbo<0, 0>(acc, da, db, !(first));                                         \
      if (k == 1) wgmma_ss_n256_tbo<2, 128>(acc, da, db, 1);                                              \
      if (k == 2) wgmma_ss_n256_tbo<4, 256>(acc, da, db, 1);                                              \
      if (k == 3) wgmma_ss_n256_tbo<6, 384>(acc, da, db, 1);                                              \
    }                                                                                                     \
    wgmma_commit();                                                                                       \
    named_bar_arrive_if(6 - wg, 256, !(wg ? (last) : (first)));                                           \
    if (!(first)) {                                                                                       \
      wgmma_wait<1>();                                                                                    \
      mbar_arrive_cluster_if(s_bar + B_GEMPTY + 8 * (((s) + 3) & 3), etgt, lane == 0 && (warp & 3) < 2);  \
    }                                                                                                     \
  }
        TL0(item);
        undef_regs(acc);
        {
          constexpr bool gok = false;
#ifdef TRE
          const uint32_t e0 = clock() - c_entry;
          mbar_wait(s_bar + B_GFULL, gphase);
          if (threadIdx.x == 0 && seg == 0) g_tr[16001 + 2 * blockIdx.x] = e0 | ((clock() - c_entry) << 16);
#endif
          G_STAGE_Y(0, true, false, )
        }
        if (seg == 0) CLUSTER_WAIT();
        undef_regs(pk);
        for (;;) {
          constexpr bool gok = false;
          const int nkb4 = prob_nkb4(item >> 8);
          const uint32_t next = p.g[cluster_id][gi++];
          G_STAGE(1)
          if (have) G_STORE_CHUNK(0)
          G_STAGE(2)
          G_STAGE(3)
          if (have) G_STORE_CHUNK(1)
          gphase ^= 1;
          G_STAGE(0)
          G_STAGE(1)
          if (have) G_STORE_CHUNK(2)
          G_STAGE(2)
          if (have) G_STORE_CHUNK(3)
          G_STAGE_Y(3, false, nkb4 == 2, )
          gphase ^= 1;
          int kb4 = 2;
          if (nkb4 == 16 && DO_LOCAL) {
            constexpr uint32_t aswz = 0, rot = 0;
            G_STAGE(0)
            G_STAGE(1)
            for (; kb4 < 10; kb4++) {
              float ls[36];
              TR(10);
              mbar_wait(s_bar + B_AFULL, kb4 & 1);
              TR(11);
              {
                const uint32_t dq = make_desc(DBASE + OFF_STG + wg * 64, 16);
                G_STAGE_X(2, if (k == 1) wgmma_ss_n72_init(ls, dq, dq + L_K / 16); if (k == 3) wgmma_ss_n72(ls, dq + 2, dq + L_K / 16 + 2, 1))
              }
              mbar_wait(s_bar + B_AFULL + 8, kb4 & 1);
              const int tid = opaque_tid();
              uint32_t vw[16];
              uint4 pw[8];
              {
                const uint32_t va = sbase + OFF_STG + L_V + ((tid >> 4) & 7) * 1024 + wg * 64 + (tid & 15) * 4;
#pragma unroll
                for (int j = 1; j < 16; j++) vw[j] = lds32((va ^ ((j & 7) << 4)) + j * 128);
              }
              G_STAGE(3)
              gphase ^= 1;
              fence_regs(ls);
              mbar_arrive_if(s_bar + B_AEMPTY, (threadIdx.x & 127) == 0);
              {
                const int d = (tid & 3) * 2 - ((tid >> 2) & 7);
                const bool p0 = d > 0, p1 = d >= 0;
                const int w = warp & 3;
                float x0, x1, y0, y1;
#define L_PICK(w_)                                   \
  {                                                  \
    x0 = p0 ? ls[8 * (w_)] : ls[8 * (w_) + 4];       \
    x1 = p1 ? ls[8 * (w_) + 1] : ls[8 * (w_) + 5];   \
    y0 = p0 ? ls[8 * (w_) + 6] : ls[8 * (w_) + 10];  \
    y1 = p1 ? ls[8 * (w_) + 7] : ls[8 * (w_) + 11];  \
  }
                if (w == 0) {
                  if (kb4 == 2 && blockIdx.x < 32) ls[0] = ls[1] = -INFINITY;
                  L_PICK(0)
                } else if (w == 1) L_PICK(1)
                else if (w == 2) L_PICK(2)
                else L_PICK(3)
                constexpr float C = 0.17677669529663687f * 1.4426950408889634f;
                float mx = fmaxf(x0, x1), my = fmaxf(y0, y1);
                mx = fmaxf(mx, __shfl_xor_sync(0xffffffffu, mx, 1));
                my = fmaxf(my, __shfl_xor_sync(0xffffffffu, my, 1));
                mx = -C * fmaxf(mx, __shfl_xor_sync(0xffffffffu, mx, 2));
                my = -C * fmaxf(my, __shfl_xor_sync(0xffffffffu, my, 2));
                x0 = ex2(fmaf(x0, C, mx));
                x1 = ex2(fmaf(x1, C, mx));
                y0 = ex2(fmaf(y0, C, my));
                y1 = ex2(fmaf(y1, C, my));
                float sx = x0 + x1, sy = y0 + y1;
                sx += __shfl_xor_sync(0xffffffffu, sx, 1);
                sy += __shfl_xor_sync(0xffffffffu, sy, 1);
                sx += __shfl_xor_sync(0xffffffffu, sx, 2);
                sy += __shfl_xor_sync(0xffffffffu, sy, 2);
                sx = rcp(sx);
                sy = rcp(sy);
                const uint32_t pa = sbase + OFF_STG + L_P + (tid >> 5) * 512 + (tid & 31) * 8;
                sts64(pa, x0 * sx, x1 * sx);
                sts64(pa + 256, y0 * sy, y1 * sy);
                __syncwarp();
              }
              const uint32_t pr = sbase + OFF_STG + L_P + (tid >> 4) * 256;
              uint32_t* dst = reinterpret_cast<uint32_t*>(p.ob) + (blockIdx.x & 15) * (SEQ * 32) + wg * 16 + (tid & 15) +
                              (((blockIdx.x >> 5) * 512 + (kb4 - 2) * 64 + ((tid >> 4) & 7) * 8) * 2 + ((blockIdx.x >> 4) & 1)) * 32;
#define L_PV(g0)                                                                                       \
  _Pragma("unroll") for (int g = (g0); g < (g0) + 4; g++) {                                            \
    const uint4 a = pw[2 * (g & 3)], b = pw[2 * (g & 3) + 1];                                          \
    const uint32_t w[8] = {a.x, a.y, a.z, a.w, b.x, b.y, b.z, b.w};                                    \
    float o0 = 0.f, o1 = 0.f;                                                                          \
    _Pragma("unroll") for (int c = 0; c < 8; c++) {                                                    \
      const uint32_t u = vw[c > g ? c : c + 8];                                                        \
      o0 = fmaf(__uint_as_float(w[c]), __uint_as_float(u << 16), o0);                                  \
      o1 = fmaf(__uint_as_float(w[c]), __uint_as_float(u & 0xFFFF0000u), o1);                          \
    }                                                                                                  \
    dst[g * 64] = pack_bf16(o0, o1);                                                                   \
  }
#pragma unroll
              for (int j = 0; j < 8; j++) pw[j] = lds128(pr + j * 16);
              mbar_arrive_elect(s_bar + B_AEMPTY + 8, true);
              G_STAGE(0)
              L_PV(0)
#pragma unroll
              for (int j = 0; j < 8; j++) pw[j] = lds128(pr + 128 + j * 16);
              G_STAGE(1)
              L_PV(4)
              __syncwarp();
              mbar_arrive_elect(s_bar + B_OFULL, true);
            }
            G_STAGE(2)
            G_STAGE(3)
            gphase ^= 1;
            kb4++;
          }
          const bool fin = next >= 0x600u;
          for (; kb4 < nkb4 - fin; kb4++) {
            G_STAGE(0)
            G_STAGE(1)
            G_STAGE(2)
            G_STAGE_Y(3, false, kb4 + 1 == nkb4, )
            gphase ^= 1;
          }
          if (fin) break;
          wgmma_wait<0>();
          mbar_arrive_cluster_if(s_bar + B_GEMPTY + 8 * 3, etgt, lane == 0 && (warp & 3) < 2);
          {
            const bool gok = mbar_test(s_bar + B_GFULL, gphase);
            fence_regs(acc);
#pragma unroll
            for (int j = 0; j < 64; j++) pk[j] = pack_bf16(acc[2 * j], acc[2 * j + 1]);
            have = item < 0x100u ? 2 : 1;
            item = next;
            TL0(item);
            G_STAGE_Y(0, true, false, )
          }
        }
        {
          constexpr bool gok = false;
          G_STAGE(0)
#if FS == 2
          G_STAGE(1)
#endif
          wgmma_wait<0>();
          mbar_arrive_cluster_if(s_bar + B_GEMPTY + 8 * (FS - 1), etgt, lane == 0 && (warp & 3) < 2);
          fence_regs(acc);
          float lo[64], hi[64];
#pragma unroll
          for (int j = 0; j < 64; j++) {
            asm volatile("mov.b32 %0, %1;" : "=f"(lo[j]) : "f"(acc[j]));
            asm volatile("mov.b32 %0, %1;" : "=f"(hi[j]) : "f"(acc[64 + j]));
          }
#pragma unroll
          for (int s = FS; s < 4; s++) {
            mbar_wait(s_bar + B_GFULL + 8 * s, gphase);
            const uint32_t da = make_desc(DBASE + OFF_A + ((s * 16384) ^ aswz) + wg * 8192, 16);
            const uint32_t db = make_desc(DBASE + (s ^ rot) * TILE32K, 8192);
            if (s == FS) named_bar_sync(5 + wg, 256);
            wgmma_fence();
            wgmma_ss_n128_tb<0, 0>(lo, da, db, 1);
            wgmma_ss_n128_tb<2, 128>(lo, da, db, 1);
            wgmma_ss_n128_tb<4, 256>(lo, da, db, 1);
            wgmma_ss_n128_tb<6, 384>(lo, da, db, 1);
            wgmma_commit();
          }
          wgmma_fence();
#pragma unroll
          for (int s = FS; s < 4; s++) {
            const uint32_t da = make_desc(DBASE + OFF_A + ((s * 16384) ^ aswz) + wg * 8192, 16);
            const uint32_t db = make_desc(DBASE + (s ^ rot) * TILE32K, 8192);
            wgmma_ss_n128_tb<0, 1024>(hi, da, db, 1);
            wgmma_ss_n128_tb<2, 1152>(hi, da, db, 1);
            wgmma_ss_n128_tb<4, 1280>(hi, da, db, 1);
            wgmma_ss_n128_tb<6, 1408>(hi, da, db, 1);
          }
          wgmma_commit();
          named_bar_arrive_if(6, 256, wg == 0);
          gphase ^= 1;
          const uint32_t so = sbase + stg_off(opaque_tid());
          mbar_wait(s_bar + B_STGFREE, stgpar);
          mbar_wait(s_bar + B_SEMPTY + 16 * wg, 1);
          mbar_wait(s_bar + B_SEMPTY + 16 * wg + 8, 1);
#define FIN_HALF(x, base, stride, bar)                                                                                \
  fence_regs(x);                                                                                                      \
  _Pragma("unroll") for (int j = 0; j < 8; j++)                                                                       \
      stmatrix_x4(((base) ^ ((j & 3) << 5)) + (j >> 2) * (stride), pack_bf16(x[8 * j], x[8 * j + 1]),                 \
                  pack_bf16(x[8 * j + 2], x[8 * j + 3]), pack_bf16(x[8 * j + 4], x[8 * j + 5]), pack_bf16(x[8 * j + 6], x[8 * j + 7])); \
  fence_proxy_async_smem();                                                                                           \
  __syncwarp();                                                                                                       \
  mbar_arrive_elect(s_bar + (bar) + 16 * wg, true);                                                                   \
  mbar_arrive_elect(s_bar + (bar) + 16 * wg + 8, true);
          wgmma_wait<1>();
          FIN_HALF(lo, so + OFF_STG + wg * 8192, 8192, B_SFULL)
          wgmma_wait<0>();
          TRI(12, 8);
#pragma unroll
          for (int s = FS; s < 4; s++) mbar_arrive_cluster_if(s_bar + B_GEMPTY + 8 * s, etgt, lane == 0 && (warp & 3) < 2);
          FIN_HALF(hi, so + OFF_A + (32768 ^ aswz), 16384, B_SFULL2)
          TRI(12, 10);
        }
      }
#ifdef ATT_ONLY
      if (seg == 0) CLUSTER_WAIT();
#endif
      if (seg == 0 && isB && DO_ATT) {
        float o[64], s[64];
        uint32_t pa[32], pb[32];
        undef_regs(o);
        undef_regs(s);
        undef_regs(pa);
        undef_regs(pb);
        uint32_t phase = 0;
        const bool sig = (threadIdx.x & 127) == 0, sig2 = (threadIdx.x & 95) == 0;
        if (wg == 1) named_bar_arrive(1, 256);

#define ISSUE_PV(pr, slot_)                                                             \
  {                                                                                     \
    const uint32_t dv = make_desc(DBASE + (slot_) * TILE32K, 16384);                    \
    if (!phalf) {                                                                       \
      wgmma_fence();                                                                    \
      _Pragma("unroll") for (int k = 0; k < 8; k++)                                     \
          wgmma_rs_n128_tb(o, pr[4 * k], pr[4 * k + 1], pr[4 * k + 2], pr[4 * k + 3], dv + k * 128, (k != 0) || !pfirst); \
      wgmma_commit();                                                                   \
    } else {                                                                            \
      wgmma_fence();                                                                    \
      _Pragma("unroll") for (int k = 0; k < 4; k++)                                     \
          wgmma_rs_n128_tb(o, pr[16 + 4 * k], pr[17 + 4 * k], pr[18 + 4 * k], pr[19 + 4 * k], dv + k * 128, (k != 0) || !pfirst); \
      wgmma_commit();                                                                   \
    }                                                                                   \
  }
#define EPILOGUE(on_)                                                                             \
  _Pragma("unroll") for (int j = 0; j < 8; j++) {                                                 \
    const int b = j * 8;                                                                          \
    stmatrix_x4_p((st_o ^ ((j & 3) << 5)) + (j >> 2) * 16384,                                     \
                  pack_bf16(o[b] * sc0, o[b + 1] * sc0), pack_bf16(o[b + 2] * sc1, o[b + 3] * sc1),   \
                  pack_bf16(o[b + 4] * sc0, o[b + 5] * sc0), pack_bf16(o[b + 6] * sc1, o[b + 7] * sc1), on_); \
  }
#define PUBLISH_O()                                  \
  {                                                  \
    fence_proxy_async_smem();                        \
    __syncwarp();                                    \
    mbar_arrive_elect(s_bar + B_OFULL, true);        \
  }
#define FINAL_SCALE()     \
  {                                                    \
    sc0 = t0 + __shfl_xor_sync(0xffffffffu, t0, 1);    \
    sc1 = t1 + __shfl_xor_sync(0xffffffffu, t1, 1);    \
    t0 = t1 = 0.f;                                     \
    sc0 += __shfl_xor_sync(0xffffffffu, sc0, 2);       \
    sc1 += __shfl_xor_sync(0xffffffffu, sc1, 2);       \
    sc0 = rcp(sc0);            \
    sc1 = rcp(sc1);                                    \
  }
        float l0 = 1.f, l1 = 1.f, t0 = 1.f, t1 = 1.f;
        float b0 = 0.f, b1 = 0.f, sc0 = 0.f, sc1 = 0.f;
        int gen = 0;
        int pfirst = 1;
        int phalf = 2;
        int fresh = 1;
        int diag = blockIdx.x & 1, dlast = !diag;
        int opub = 0;
        int last = 0;
        float rdy;
        float x0 = 0.f, x1 = 0.f, x2 = 0.f, x3 = 0.f;
        bool rs = false;
        uint32_t code = p.order[cluster_id - NA_CL];
        int it = 0, nit = 0, rem = (code & 15) + dlast;
        TL0(0x1000 | code | rem);
        const float mrow = float((warp & 3) * 16 + (lane >> 2) - (lane & 3) * 2);
        const float lo0 = mrow < 0.f && wg == HW ? 0.f : SM_LO;
        const uint32_t st_o = sbase + OFF_STG + stg_off(opaque_tid() ^ (HW * 128));
#define MMA_PART(N_, acc_, PIN, PAR)                                                                       \
  {                                                                                                        \
    const uint32_t dq = make_desc(DBASE + OFF_A + (it & 1) * TILE32K + (wg ^ HW) * 8192, 16);              \
    const uint32_t dk = make_desc(DBASE + (PAR) * TILE32K, 16);                                            \
    TRI(0, fresh ? 7 : 0);                                                                                 \
    named_bar_sync(1 + wg, 256);                                                                           \
    TRI(1, fresh ? 6 : 1);                                                                                 \
    wgmma_fence();                                                                                         \
    uint32_t cv;                                                                                           \
    bool rv;                                                                                               \
    _Pragma("unroll") for (int k = 0; k < 8; k++) {                                                        \
      wgmma_ss_n##N_(acc_, dq + (k >> 2) * 1024 + (k & 3) * 2, dk + (k >> 2) * 1024 + (k & 3) * 2, k != 0); \
      if (k == 1) cv = lds32(s_bar + S_CODE + 4 * ((it + 1) & 7));        \
      if (k == 3) rv = mbar_test(s_bar + B_AFULL + 8 * (3 - (PAR)), phase ^ (1 - (PAR)));                  \
    }                                                                                                      \
    wgmma_commit();                                                                                        \
    code = __reduce_or_sync(0xffffffffu, cv);                                                              \
    if (opub) PUBLISH_O();                                                                                 \
    if (N_ == 128 && fresh) FINAL_SCALE();                                                                 \
    last = rem == 0 && (code & 0x8000u);                                                                   \
    nit = it + (rem == 0 && !last);                                                                        \
    mbar_wait_rest(s_bar + B_AFULL + 8 * (3 - (PAR)), phase ^ (1 - (PAR)), rv);                            \
    ISSUE_PV(PIN, 3 - (PAR));                                                                              \
    named_bar_arrive(2 - wg, 256);                                                                         \
    TR(2);                                                                                                 \
    wgmma_wait<1>();                                                                                       \
    fence_regs(acc_);                                                                                      \
    TR(3);                                                                                                 \
    mbar_arrive_cluster_if(s_bar + B_AEMPTY + 8 * (PAR), etgt, sig2);                                      \
    mbar_arrive_if(s_bar + B_QEMPTY + 8 * (it & 1), sig && rem == 0);                                      \
    rs = mbar_test(s_bar + B_STGFREE, ~it & 1) | (it == 0);                                                \
    if (N_ == 64 && fresh) FINAL_SCALE();                                                                  \
    l0 = t0;                                                                                               \
    l1 = t1;                                                                                               \
  }
#define LOW_SUM() ((t0 < lo0) | (t1 < SM_LO))
#define SECOND_HALF(POUT, PAR, FRESH, ...)                                                                 \
  wgmma_wait<0>();                                                                                         \
  fence_regs(o);                                                                                           \
  mbar_arrive_cluster_if(s_bar + B_AEMPTY + 8 * (3 - (PAR)), etgt, sig2 && ((PAR) || !(FRESH) || it > 0)); \
  TR(8);                                                                                                   \
  __VA_ARGS__;                                                                                             \
  t0 += x0 + x1;                                                                                           \
  t1 += x2 + x3;                                                                                           \
  POUT[16] = pack_bf16(x0, x1);                                                                            \
  POUT[17] = pack_bf16(x2, x3);                                                                            \
  softmax_exp<9, ZPOS, false>(s, 0.f, 0.f, POUT, t0, t1);                                                  \
  {                                                                                                        \
           \
    const uint32_t z = (__float_as_uint(t0) | __float_as_uint(t1)) >> 31;                                  \
    rdy = mbar_test2(s_bar + B_AFULL + 8 * (1 - (PAR)), (phase ^ (PAR)) + z, s_bar + B_QFULL + 8 * (nit & 1), ((nit >> 1) & 1) + z); \
  }                                                                                                        \
  softmax_exp<ZPOS, TPOS, false>(s, 0.f, 0.f, POUT, t0, t1);                                               \
  t0 = addv(t0, rdy);                                                                                      \
  softmax_exp<TPOS, 16, false>(s, 0.f, 0.f, POUT, t0, t1);                                                 \
                                                                                \
  phalf = diag && wg == HW;                                                                                \
  opub = (FRESH) && it > 0;                                                                                \
  pfirst = FRESH;                                                                                          \
  fresh = rem == 0;                                                                                        \
  it = nit;                                                                                                \
  rem = fresh ? (code & 15) + ((blockIdx.x ^ ~it) & 1) : rem - 1;                                          \
  dlast = !((blockIdx.x | it) & 1);                                                                        \
  diag = dlast ? rem == 0 : fresh;                                                                         \
  if (fresh && !last) { TL0(0x1000 | code | rem); }                                                        \
  if (PAR) phase ^= 1;                                                                                     \
                                                      \
  const float lim = __uint_as_float(__float_as_uint(last ? -1.f : SM_HI) | __float_as_uint(rdy));   \
  TR(4);
#ifndef TPOS
#define TPOS 15
#define ZPOS 13
#endif
#define SHIFT_S(j0_)                                                                                       \
  if (gen) { _Pragma("unroll") for (int j = (j0_); j < 64; j++) s[j] += (j & 2) ? b1 : b0; }
#define NEXT_STEP(NEXT, LOW)                                                                               \
  if (!__any_sync(0xffffffffu, !(t0 + t1 <= (diag && wg == HW ? -1.f : lim)) | (LOW))) goto plain##NEXT;   \
  if (!__any_sync(0xffffffffu, !(t0 + t1 <= lim) | (LOW))) goto half##NEXT;
#define STEP_END(POUT, PAR, NEXT, ...)                                                                     \
  if (fresh) {                                                                                             \
    __VA_ARGS__;                                                                                           \
    mbar_wait_rest(s_bar + B_STGFREE, ~it & 1, rs);                                                        \
    SECOND_HALF(POUT, PAR, 1, EPILOGUE(it > 0))                                                            \
    if (phalf && opub) {                                                     \
      PUBLISH_O();                                                                                         \
      opub = 0;                                                                                            \
    }                                                                                                      \
    NEXT_STEP(NEXT, LOW_SUM())                                                                             \
  } else {                                                                                                 \
    SECOND_HALF(POUT, PAR, 0, )                                                                            \
    NEXT_STEP(NEXT, false)                                                                                 \
  }
#define STEP_BEGIN(PIN, POUT, PAR, ...)                                                                    \
  {                                                                                                        \
    if (__any_sync(0xffffffffu, !(t0 + t1 <= SM_HI) | (LOW_SUM() & (pfirst != 0)))) {                           \
              \
      if (phalf) { _Pragma("unroll") for (int j = 0; j < 32; j++) asm volatile("mov.b32 %0, 0xff800000;" : "=f"(s[j])); } \
      float d0, d1;                                                                                        \
      softmax_max(s, d0, d1);                                                                              \
      if (!pfirst) {                                                                                       \
        d0 = fmaxf(d0, 0.f);                                                                               \
        d1 = fmaxf(d1, 0.f);                                                                               \
      }                                                                                                    \
      const float r0 = pfirst ? 1.f : ex2(-d0), r1 = pfirst ? 1.f : ex2(-d1);                              \
      t0 = l0 * r0;                                                                                        \
      t1 = l1 * r1;                                                                                        \
      softmax_exp<0, 16, true>(s, -d0, -d1, PIN, t0, t1);                                                  \
      b0 -= d0;                                                                                            \
      b1 -= d1;                                                                                            \
      gen = 1;                                                                                             \
      _Pragma("unroll") for (int j = 0; j < 16; j++) {                                                     \
        o[4 * j] *= r0;                                                                                    \
        o[4 * j + 1] *= r0;                                                                                \
        o[4 * j + 2] *= r1;                                                                                \
        o[4 * j + 3] *= r1;                                                                                \
      }                                                                                                    \
    }                                                                                                      \
    if (last) {                                                                                            \
      __VA_ARGS__;                                                                                         \
      break;                                                                                               \
    }                                                                                                      \
    const bool rq = mbar_test(s_bar + B_QFULL + 8 * (it & 1), (it >> 1) & 1);                              \
    mbar_wait(s_bar + B_AFULL + 8 * (PAR), phase);                                                         \
    mbar_wait_rest(s_bar + B_QFULL + 8 * (it & 1), (it >> 1) & 1, rq);                                     \
  }                                                                                                        \
  if (diag && wg == HW) {                                                                                  \
  half##PAR:                                                                                               \
                                                     \
    float sl[32];                                                                                          \
    undef_regs(sl);                                                                                        \
    MMA_PART(64, sl, PIN, PAR)                                                                             \
    _Pragma("unroll") for (int j = 0; j < 32; j++) asm volatile("mov.b32 %0, %1;" : "=f"(s[32 + j]) : "f"(sl[j])); \
    SHIFT_S(32)                                                                                            \
    _Pragma("unroll") for (int j = 0; j < 8; j++) {                                                        \
      if (float(8 * j) > mrow) s[32 + 4 * j] = -3e38f;                                                     \
      if (float(8 * j + 1) > mrow) s[33 + 4 * j] = -3e38f;                                                 \
      if (float(8 * j - 8) > mrow) s[34 + 4 * j] = -3e38f;                                                 \
      if (float(8 * j - 7) > mrow) s[35 + 4 * j] = -3e38f;                                                 \
    }                                                                                                      \
    x0 = ex2v(s[32]), x1 = ex2v(s[33]), x2 = ex2v(s[34]), x3 = ex2v(s[35]);                                \
  } else {                                                                                                 \
  plain##PAR:                                                                                              \
    MMA_PART(128, s, PIN, PAR)                                                                             \
    if (diag || gen) {                                                                                     \
      SHIFT_S(0)                                                                                           \
                                     \
      const float rowf = diag ? mrow : 64.f;                                                               \
      _Pragma("unroll") for (int j = 0; j < 8; j++) {                                                      \
        s[32 + 4 * j] = fmaf(__saturatef(float(8 * j) - rowf), -3e38f, s[32 + 4 * j]);                     \
        s[33 + 4 * j] = fmaf(__saturatef(float(8 * j + 1) - rowf), -3e38f, s[33 + 4 * j]);                 \
        s[34 + 4 * j] = fmaf(__saturatef(float(8 * j - 8) - rowf), -3e38f, s[34 + 4 * j]);                 \
        s[35 + 4 * j] = fmaf(__saturatef(float(8 * j - 7) - rowf), -3e38f, s[35 + 4 * j]);                 \
      }                                                                                                    \
      softmax_exp<0, 8, false>(s, 0.f, 0.f, POUT, t0, t1);                                                 \
      x0 = ex2v(s[32]), x1 = ex2v(s[33]), x2 = ex2v(s[34]), x3 = ex2v(s[35]);                              \
    } else {                                                                                               \
      softmax_exp<0, 8, false>(s, 0.f, 0.f, POUT, t0, t1);                                                 \
      x0 = ex2v(s[32]), x1 = ex2v(s[33]), x2 = ex2v(s[34]), x3 = ex2v(s[35]);                              \
    }                                                                                                      \
  }
        for (;;) {
          STEP_END(pa, 1, 0, if (phalf == 2) { wgmma_wait<0>(); goto begin0; })
        begin0:
          STEP_BEGIN(pa, pb, 0, rot = 0; phase ^= 1)
          STEP_END(pb, 0, 1, )
          STEP_BEGIN(pb, pa, 1, rot = 1; _Pragma("unroll") for (int j = 0; j < 32; j++) asm volatile("mov.b32 %0, %1;" : "=r"(pa[j]) : "r"(pb[j])))
        }
        {
          mbar_wait(s_bar + B_AFULL + 8 * (3 - rot), phase);
          TRI(12, 2);
          ISSUE_PV(pa, 3 - rot);
          if (opub) PUBLISH_O();
          FINAL_SCALE();
          mbar_wait(s_bar + B_STGFREE, it & 1);
          wgmma_wait<0>();
          fence_regs(o);
          TRI(12, 4);
          mbar_arrive_cluster_if(s_bar + B_AEMPTY + 8 * (3 - rot), etgt, sig2);
          EPILOGUE(true);
          PUBLISH_O();
          TRI(12, 5);
          stgpar = ~it & 1;
          tail = tail_item(code);
          aswz = (~it & 1) * TILE32K;
          rot ^= blockIdx.x & ~it & 1;
        }
      }
    }
    TL0(0xFFFF);
    TRI(15, 15);
  }
}

typedef CUresult (*EncodeFn)(CUtensorMap*, CUtensorMapDataType, cuuint32_t, void*, const cuuint64_t*,
                             const cuuint64_t*, const cuuint32_t*, const cuuint32_t*, CUtensorMapInterleave,
                             CUtensorMapSwizzle, CUtensorMapL2promotion, CUtensorMapFloatOOBfill);

EncodeFn get_encode() {
  static EncodeFn fn = nullptr;
  if (!fn) {
    void* p = nullptr;
    cudaDriverEntryPointQueryResult st;
    cudaGetDriverEntryPoint("cuTensorMapEncodeTiled", &p, cudaEnableDefault, &st);
    fn = (EncodeFn)p;
  }
  return fn;
}

void make_map(CUtensorMap* m, const void* ptr, int rows, int cols, int box_rows, int box_groups, bool blocked = false) {
  cuuint64_t dims[3] = {64, (cuuint64_t)rows, (cuuint64_t)(cols / 64)};
  cuuint64_t strides[2] = {(cuuint64_t)(blocked ? 128 : cols * 2), (cuuint64_t)(blocked ? rows * 128 : 128)};
  cuuint32_t box[3] = {64, (cuuint32_t)box_rows, (cuuint32_t)box_groups};
  cuuint32_t es[3] = {1, 1, 1};
  CUtensorMapL2promotion prom = blocked || box_groups == 1 ? CU_TENSOR_MAP_L2_PROMOTION_NONE : CU_TENSOR_MAP_L2_PROMOTION_L2_256B;
  get_encode()(m, CU_TENSOR_MAP_DATA_TYPE_BFLOAT16, 3, const_cast<void*>(ptr), dims, strides, box, es,
               CU_TENSOR_MAP_INTERLEAVE_NONE, CU_TENSOR_MAP_SWIZZLE_128B, prom,
               CU_TENSOR_MAP_FLOAT_OOB_FILL_NONE);
}

void make_store_map(CUtensorMap* m, const void* ptr, int cols, uint64_t s_par, uint64_t s_pair, uint64_t s_grp) {
  cuuint64_t dims[4] = {64, 2, SEQ / 2, (cuuint64_t)(cols / 64)};
  cuuint64_t strides[3] = {s_par, s_pair, s_grp};
  cuuint32_t box[4] = {64, 2, 32, 1};
  cuuint32_t es[4] = {1, 1, 1, 1};
  get_encode()(m, CU_TENSOR_MAP_DATA_TYPE_BFLOAT16, 4, const_cast<void*>(ptr), dims, strides, box, es,
               CU_TENSOR_MAP_INTERLEAVE_NONE, CU_TENSOR_MAP_SWIZZLE_128B, CU_TENSOR_MAP_L2_PROMOTION_NONE,
               CU_TENSOR_MAP_FLOAT_OOB_FILL_NONE);
}

#ifdef SCHED_PRINT
static int envi(const char* n, int d) { const char* e = getenv(n); return e ? (int)strtol(e, 0, 0) : d; }
#define PARAM(name, val) const int name = envi(#name, val)
#else
#define PARAM(name, val) const int name = val
#endif
void build_schedule(Params& p) {
  PARAM(C_KB, 1028);
  PARAM(C_TILE, 10);
  PARAM(C_QX, 0);
  PARAM(C_START, 4500);
  PARAM(C_STEP, 2052);
  PARAM(C_ITEM, 300);
  PARAM(C_LAG, 8000);
  PARAM(C_SP, 5200);
  PARAM(C_TAIL, 22000);
  PARAM(C_SHORT, 0);
  PARAM(C_AT, 72);
  PARAM(C_LATE, 0);
  PARAM(C_LMASK, 0xAA0);
  PARAM(C_AM, 100);
  PARAM(C_ODD, 1300);
  PARAM(C_READY, 10000);
  auto gemm_cost = [&](int prob) {
    static const int nkb[NPROB] = {16, 8, 8, 16, 64, 16};
    return nkb[prob] * C_KB + C_TILE + (prob == 0 ? C_QX : 0);
  };
  memset(p.g, 0xFF, sizeof(p.g));
  int n1[NCLUSTER];
  long t1[NCLUSTER];
  long ready[16];
  for (int c = 0; c < NCLUSTER; c++) { n1[c] = 0; t1[c] = C_START; }
  for (int i = 0; i < 16; i++) ready[i] = 0;
  auto add = [&](int c, int prob, int mp, int nt) {
    p.g[c][n1[c]++] = (uint16_t)((prob << 8) | (mp << 4) | nt);
    t1[c] += gemm_cost(prob);
    if (prob < 3) {
      const long r = t1[c] + C_READY;
      if (r > ready[nt]) ready[nt] = r;
    }
  };
#ifdef GEMM_ONLY
  for (int c = 0; c < NCLUSTER; c++) {
    for (int i = 0; i < 13; i++) add(c, 0, c & 7, (i + (c >> 3) * 2) & 15);
    p.g[c][n1[c]++] = 0x600;
  }
  return;
#endif
#ifdef ATT_ONLY
  for (int c = 0; c < NCLUSTER; c++) { p.g[c][0] = 0x600; p.g[c][1] = 0x500; }
  for (int i = 0; i < 256; i++) p.order[i] = (uint16_t)(((i & 31) << 4) | (14 - 2 * (i >> 5)));
  return;
#endif
  for (int r = 0; r < 8; r++)
    for (int c = 0; c < NA_CL; c++) {
      const int mp = c & 7, nt = 2 * r + ((c >> 3) & 1);
      for (int j = 0; j < (c < 16 ? 1 : 2); j++) {
        add(c, c < 16 ? 0 : 1 + j, mp, nt);
      }
    }
  long tA = 0;
  for (int c = 0; c < NA_CL; c++) {
    if (t1[c] > tA) tA = t1[c];
    add(c, 4, c & 7, c >> 3);
  }
  for (int r = 0; r < 3; r++)
    for (int j = 0; j < 34; j++) {
      if (j >= 32) { if (r < 2) add(NA_CL + j, 3, j & 7, 4 + r); }
      else if (r < 2 || j >= 16 || (j & 7) >= 2) add(NA_CL + j, 3, j & 7, (j >> 3) + (r == 0 ? 0 : r == 1 ? 8 : 4));
    }
  for (int c = NA_CL; c < NCLUSTER; c++) {
    p.g[c][n1[c]++] = 0x600;
    p.g[c][n1[c]++] = 0x500;
  }
  static const uint16_t order[256] = {
    14, 30, 10, 44, 26, 78, 60, 94, 12, 46, 8, 42, 24, 76, 58, 110, 92, 6, 126, 40, 22, 74, 56, 108,
    90, 4, 124, 38, 20, 72, 54, 106, 28, 62, 142, 158, 88, 2, 140, 122, 36, 18, 174, 156, 70, 52, 190, 104,
    86, 0, 138, 120, 34, 16, 172, 154, 68, 50, 206, 188, 102, 84, 222, 136, 118, 32, 170, 152, 66, 48, 204, 186,
    100, 82, 238, 220, 134, 116, 254, 168, 150, 64, 202, 184, 98, 80, 236, 218, 132, 114, 270, 252, 166, 148, 286, 200,
    182, 96, 234, 216, 130, 112, 268, 250, 164, 146, 302, 284, 198, 180, 318, 232, 214, 128, 266, 248, 162, 144, 300, 282,
    196, 178, 334, 316, 230, 212, 350, 264, 246, 160, 310, 328, 382, 194, 314, 360, 192, 340, 278, 298, 274, 208, 342, 366,
    210, 260, 290, 312, 336, 378, 306, 292, 240, 330, 364, 224, 228, 346, 380, 434, 376, 244, 362, 226, 344, 348, 408, 272,
    304, 176, 320, 368, 280, 412, 390, 332, 262, 288, 258, 256, 242, 402, 294, 388, 422, 296, 406, 398, 384, 374, 326, 352,
    400, 414, 394, 276, 322, 418, 392, 396, 370, 356, 324, 410, 386, 430, 462, 494, 446, 510, 478, 484, 482, 354, 498, 404,
    308, 416, 428, 492, 508, 460, 476, 444, 452, 358, 426, 372, 490, 506, 458, 442, 474, 338, 424, 472, 456, 440, 488, 454,
    450, 438, 470, 486, 420, 436, 468, 500, 504, 466, 502, 448, 496, 432, 480, 464,
  };
  memcpy(p.order, order, sizeof(order));
#ifdef SCHED_PRINT
  uint16_t fixed[256];
  memcpy(fixed, p.order, sizeof(fixed));
  long tf[NB_CL];
  bool done[512], started[NB_CL];
  long fin[16];
  int cnt[NB_CL] = {};
  for (int c = 0; c < NB_CL; c++) { tf[c] = t1[NA_CL + c] + 2000; started[c] = false; }
  for (int i = 0; i < 512; i++) done[i] = i & 1;
  for (int i = 0; i < 16; i++) fin[i] = 0;
  auto alen = [&](int qt) { return (long)(2 * qt + 3) * C_STEP / 2 + C_ITEM + (qt < 2 ? C_SHORT : 0); };
  int nq = NB_CL;
  for (int n = 0; n < 256; n++) {
    int cb = 0;
    for (int c = 1; c < NB_CL; c++)
      if (tf[c] < tf[cb]) cb = c;
    int best = -1;
    long bkey = 0;
    for (int i = 0; i < 512; i++) {
      if (done[i]) continue;
      const int hp = i >> 5;
      long dl = -(long)(16 - hp) * C_SP - C_LAG + ((i >> 4) & 1) * C_ODD;
      if (dl > -C_TAIL) dl = -C_TAIL;
      long key = dl - alen(i & 15) * (dl == -C_TAIL ? C_AT : C_AM) / 100;
      if ((i >> 4) == 31 && (C_LMASK >> (i & 15) & 1)) key += C_LATE;
      if (ready[hp] > tf[cb]) key += (1L << 40) + (ready[hp] - tf[cb]) * 1024;
      if (best < 0 || key < bkey) { best = i; bkey = key; }
    }
    done[best] = true;
    if (!started[cb]) { p.order[cb] = (uint16_t)best; started[cb] = true; }
    else p.order[nq++] = (uint16_t)best;
    if (ready[best >> 5] > tf[cb]) tf[cb] = ready[best >> 5];
    tf[cb] += alen(best & 15) + (cnt[cb]++ & 1 ? -C_STEP / 2 : C_STEP / 2);
    if (tf[cb] + C_LAG > fin[best >> 5]) fin[best >> 5] = tf[cb] + C_LAG;
  }
  if (!getenv("HEUR")) memcpy(p.order, fixed, sizeof(fixed));
#endif
#ifdef SCHED_PRINT
  ord_hook(p.order);
  long t = tA, tmin = tf[0], tmax = tf[0];
  printf("sched: outA start %ld, fin:", t);
  for (int hp = 0; hp < 16; hp++) {
    printf(" %ld", fin[hp] - t);
    if (fin[hp] > t) t = fin[hp];
    t += 4 * C_KB;
  }
  for (int c = 0; c < NB_CL; c++) { if (tf[c] < tmin) tmin = tf[c]; if (tf[c] > tmax) tmax = tf[c]; }
  printf("\nA end %ld, attention end %ld..%ld (+%d), ready[15] %ld nq %d\n", t, tmin, tmax, gemm_cost(5), ready[15], nq);
#endif
}

}

extern "C" void kernel_launch(void* const* d_in, const int* in_sizes, int n_in, void* d_out, int out_size) {
  const bf16* A_x = (const bf16*)d_in[0];
  const bf16* A_c = (const bf16*)d_in[1];
  const bf16* A_wq = (const bf16*)d_in[2];
  const bf16* A_wuk = (const bf16*)d_in[3];
  const bf16* A_wuv = (const bf16*)d_in[4];
  const bf16* A_wo = (const bf16*)d_in[5];
  const bf16* B_x = (const bf16*)d_in[6];
  const bf16* B_wqkv = (const bf16*)d_in[7];
  const bf16* B_wo = (const bf16*)d_in[8];
  bf16* out = (bf16*)d_out;

  static Params p;
  static bf16 *q, *k, *v, *ctx, *qkvb, *ob;
  static bool init = false;
  if (!init) {
    cudaGetSymbolAddress((void**)&q, g_q);
    cudaGetSymbolAddress((void**)&k, g_k);
    cudaGetSymbolAddress((void**)&v, g_v);
    cudaGetSymbolAddress((void**)&qkvb, g_qkvb);
    cudaGetSymbolAddress((void**)&ob, g_ob);
    cudaFuncSetAttribute(mega_kernel, cudaFuncAttributeMaxDynamicSharedMemorySize, SMEM_BYTES);
    build_schedule(p);
    ctx = q;
    init = true;
  }
  make_map(&p.ta[0], A_x, SEQ, DM, 128, 1);
  make_map(&p.tb[0], A_wq, DM, HHD, 64, 2);
  make_store_map(&p.tc[0], q, HHD, 128, 256, SEQ * 128);
  make_map(&p.ta[1], A_c, SEQ, DC, 128, 1);
  make_map(&p.tb[1], A_wuk, DC, HHD, 64, 2);
  make_store_map(&p.tc[1], k, HHD, 128, 256, SEQ * 128);
  make_map(&p.ta[2], A_c, SEQ, DC, 128, 1);
  make_map(&p.tb[2], A_wuv, DC, HHD, 64, 2);
  make_store_map(&p.tc[2], v, HHD, 128, 256, SEQ * 128);
  make_map(&p.ta[3], B_x, SEQ, DM, 128, 1);
  make_map(&p.tb[3], B_wqkv, DM, 3 * DM, 64, 2);
  make_store_map(&p.tc[3], qkvb, 3 * DM, SEQ * 64, 128, SEQ * 128);
  make_map(&p.ta[4], ctx, SEQ, HHD, 128, 1, true);
  make_map(&p.tb[4], A_wo, HHD, DM, 64, 2);
  make_store_map(&p.tc[4], out, 2 * DM, 4 * DM, 8 * DM, 128);
  make_map(&p.ta[5], ob, SEQ, DM, 128, 1, true);
  make_map(&p.tb[5], B_wo, DM, DM, 64, 2);
  make_store_map(&p.tc[5], out, 2 * DM, 4 * DM, 8 * DM, 128);
  make_map(&p.tq, q, SEQ, HHD, 128, 2, true);
  make_map(&p.tk, k, SEQ, HHD, 128, 1, true);
  make_map(&p.tv, v, SEQ, HHD, 128, 1, true);
  make_map(&p.tl, qkvb, SEQ / 2, 6 * DM, 64, 1, true);
  make_map(&p.th, qkvb, SEQ / 2, 6 * DM, 72, 1, true);
  make_map(&p.to, ctx, SEQ, HHD, 128, 2, true);
  p.ob = ob;
  mega_kernel<<<NCTA, 384, SMEM_BYTES, cudaStreamPerThread>>>(p);
}
```

```cpp
#include <cuda_runtime.h>
#include <cuda_bf16.h>
#include <cuda.h>
#include <stdint.h>
#include <string.h>

namespace {

typedef __nv_bfloat16 bf16;

constexpr int SEQ = 2048;
constexpr int NHEAD = 32;
constexpr int HD = 128;
constexpr int DM = 1024;
constexpr int DC = 512;
constexpr int HHD = NHEAD * HD;

__device__ __align__(1024) bf16 g_q[SEQ * HHD];
__device__ __align__(1024) bf16 g_k[SEQ * HHD];
__device__ __align__(1024) bf16 g_v[SEQ * HHD];
__device__ __align__(1024) bf16 g_qkvb[SEQ * 3 * DM];
__device__ __align__(1024) bf16 g_ob[SEQ * DM];
constexpr int CNT_QKV = 0, CNT_CTX = 16, CNT_QKVB = 32, CNT_DONE = 33, CNT_QUEUE = 34, CNT_OB = 35, CNT_N = 39;
__device__ uint32_t g_cnt[CNT_N * 8];
#ifdef TIMELINE
__device__ __align__(16) unsigned long long g_tl[132 * 4 * 64];
#endif


__device__ __forceinline__ uint32_t smem_u32(const void* p) {
  return static_cast<uint32_t>(__cvta_generic_to_shared(p));
}
__device__ __forceinline__ void mbar_init(uint32_t bar, uint32_t count) {
  asm volatile("mbarrier.init.shared::cta.b64 [%0], %1;" ::"r"(bar), "r"(count) : "memory");
}
__device__ __forceinline__ void mbar_expect_tx(uint32_t bar, uint32_t bytes) {
  asm volatile("mbarrier.arrive.expect_tx.shared::cta.b64 _, [%0], %1;" ::"r"(bar), "r"(bytes) : "memory");
}
__device__ __forceinline__ void mbar_arrive(uint32_t bar) {
  asm volatile("mbarrier.arrive.shared::cta.b64 _, [%0];" ::"r"(bar) : "memory");
}
__device__ __forceinline__ void mbar_arrive_if(uint32_t bar, bool on) {
  asm volatile("{\n.reg .pred p;\nsetp.ne.b32 p, %1, 0;\n@p mbarrier.arrive.shared::cta.b64 _, [%0];\n}" ::"r"(bar),
               "r"((int)on)
               : "memory");
}
__device__ __forceinline__ void mbar_arrive_cluster_if(uint32_t bar, uint32_t cta, bool on) {
  asm volatile(
      "{\n.reg .b32 ra;\n.reg .pred p;\nsetp.ne.b32 p, %2, 0;\nmapa.shared::cluster.u32 ra, %0, %1;\n"
      "@p mbarrier.arrive.shared::cluster.b64 _, [ra];\n}" ::"r"(bar),
      "r"(cta), "r"((int)on)
      : "memory");
}
__device__ __forceinline__ bool mbar_try_wait(uint32_t bar, uint32_t parity) {
  uint32_t ok;
  asm volatile(
      "{\n.reg .pred p;\nmbarrier.try_wait.parity.shared::cta.b64 p, [%1], %2;\nselp.u32 %0, 1, 0, p;\n}"
      : "=r"(ok)
      : "r"(bar), "r"(parity)
      : "memory");
  return ok != 0;
}
__device__ __forceinline__ bool mbar_test(uint32_t bar, uint32_t parity) {
  uint32_t ok;
  asm volatile(
      "{\n.reg .pred p;\nmbarrier.test_wait.parity.shared::cta.b64 p, [%1], %2;\nselp.u32 %0, 1, 0, p;\n}"
      : "=r"(ok)
      : "r"(bar), "r"(parity)
      : "memory");
  return ok != 0;
}
#ifdef DBGW
__device__ uint32_t* g_dbg;
__device__ __forceinline__ void mbar_wait_l(uint32_t bar, uint32_t parity, int line) {
  uint32_t t0 = clock();
  bool rec = false;
  while (!mbar_try_wait(bar, parity)) {
    uint32_t d = clock() - t0;
    if (d > (1u << 26) && !rec) { rec = true; g_dbg[blockIdx.x * 16 + (threadIdx.x >> 5)] = (bar & 1023) | (parity << 12) | (line << 16); __threadfence_system(); }
    if (d > (1u << 28)) __trap();
  }
}
#define mbar_wait(b, p) mbar_wait_l(b, p, __LINE__)
#define DBG(i, v) *(volatile uint32_t*)(g_dbg + blockIdx.x * 16 + (i)) = (v)
__device__ __forceinline__ void mbar_wait_unused(uint32_t bar, uint32_t parity) {
#else
#define DBG(i, v)
__device__ __forceinline__ void mbar_wait(uint32_t bar, uint32_t parity) {
#endif
  asm volatile(
      "{\n.reg .pred p;\n.reg .u32 t;\n"
      "mbarrier.try_wait.parity.shared::cta.b64 p, [%0], %1;\n"
      "@p bra DONE;\n"
      "mov.u32 t, 0x100000;\n"
      "LAB_WAIT:\n"
      "mbarrier.try_wait.parity.shared::cta.b64 p, [%0], %1;\n"
      "@p bra DONE;\n"
      "sub.u32 t, t, 1;\n"
      "setp.ne.u32 p, t, 0;\n"
      "@p bra LAB_WAIT;\n"
      "trap;\n"
      "DONE:\n}" ::"r"(bar),
      "r"(parity)
      : "memory");
}
constexpr uint64_t EV_NORMAL = 0x1000000000000000ull;
__device__ __forceinline__ uint64_t policy_first() {
  uint64_t p;
  asm("createpolicy.fractional.L2::evict_first.b64 %0, 1.0;" : "=l"(p));
  return p;
}
#define EV_FIRST policy_first()
__device__ __forceinline__ void tma_load_3d(uint32_t dst, const CUtensorMap* map, int c0, int c1, int c2,
                                            uint32_t bar, uint64_t hint) {
  asm volatile(
      "cp.async.bulk.tensor.3d.shared::cluster.global.mbarrier::complete_tx::bytes.L2::cache_hint [%0], [%1, {%3, %4, %5}], [%2], %6;" ::"r"(dst),
      "l"(map), "r"(bar), "r"(c0), "r"(c1), "r"(c2), "l"(hint)
      : "memory");
}
__device__ __forceinline__ void tma_load_3d_mc(uint32_t dst, const CUtensorMap* map, int c0, int c1, int c2,
                                               uint32_t bar, uint16_t mask, uint64_t hint) {
  asm volatile(
      "cp.async.bulk.tensor.3d.shared::cluster.global.mbarrier::complete_tx::bytes.multicast::cluster.L2::cache_hint [%0], [%1, {%3, %4, %5}], [%2], %6, %7;" ::"r"(dst),
      "l"(map), "r"(bar), "r"(c0), "r"(c1), "r"(c2), "h"(mask), "l"(hint)
      : "memory");
}
__device__ __forceinline__ void tma_store_3d(const CUtensorMap* map, uint32_t src, int c0, int c1, int c2, uint64_t hint) {
  asm volatile("cp.async.bulk.tensor.3d.global.shared::cta.bulk_group.L2::cache_hint [%0, {%2, %3, %4}], [%1], %5;" ::"l"(map),
               "r"(src), "r"(c0), "r"(c1), "r"(c2), "l"(hint)
               : "memory");
}
__device__ __forceinline__ void tma_store_4d(const CUtensorMap* map, uint32_t src, int c2, int c3, uint64_t hint) {
  asm volatile("cp.async.bulk.tensor.4d.global.shared::cta.bulk_group.L2::cache_hint [%0, {%2, %2, %3, %4}], [%1], %5;" ::"l"(map),
               "r"(src), "r"(0), "r"(c2), "r"(c3), "l"(hint)
               : "memory");
}
__device__ __forceinline__ void bulk_commit() { asm volatile("cp.async.bulk.commit_group;" ::: "memory"); }
template <int N>
__device__ __forceinline__ void bulk_wait_read() {
  asm volatile("cp.async.bulk.wait_group.read %0;" ::"n"(N) : "memory");
}
template <int N>
__device__ __forceinline__ void bulk_wait() {
  asm volatile("cp.async.bulk.wait_group %0;" ::"n"(N) : "memory");
}
__device__ __forceinline__ void fence_proxy_async_smem() {
  asm volatile("fence.proxy.async.shared::cta;" ::: "memory");
}
__device__ __forceinline__ bool elect_one() {
  uint32_t pred;
  asm volatile("{\n.reg .pred P;\nelect.sync _|P, 0xffffffff;\nselp.b32 %0, 1, 0, P;\n}" : "=r"(pred));
  return pred != 0;
}
__device__ __forceinline__ void named_bar_sync(int id, int n) {
  asm volatile("bar.sync %0, %1;" ::"r"(id), "r"(n) : "memory");
}
__device__ __forceinline__ void named_bar_arrive(int id, int n) {
  asm volatile("bar.arrive %0, %1;" ::"r"(id), "r"(n) : "memory");
}
__device__ __forceinline__ void named_bar_sync_if(int id, int n, bool on) {
  asm volatile("{\n.reg .pred p;\nsetp.ne.b32 p, %2, 0;\n@p bar.sync %0, %1;\n}" ::"r"(id), "r"(n), "r"((int)on) : "memory");
}
__device__ __forceinline__ void named_bar_arrive_if(int id, int n, bool on) {
  asm volatile("{\n.reg .pred p;\nsetp.ne.b32 p, %2, 0;\n@p bar.arrive %0, %1;\n}" ::"r"(id), "r"(n), "r"((int)on) : "memory");
}
template <int N>
__device__ __forceinline__ void reg_alloc() {
  asm volatile("setmaxnreg.inc.sync.aligned.u32 %0;" ::"n"(N));
}
template <int N>
__device__ __forceinline__ void reg_dealloc() {
  asm volatile("setmaxnreg.dec.sync.aligned.u32 %0;" ::"n"(N));
}
__device__ __forceinline__ void wgmma_fence() { asm volatile("wgmma.fence.sync.aligned;" ::: "memory"); }
__device__ __forceinline__ void wgmma_commit() { asm volatile("wgmma.commit_group.sync.aligned;" ::: "memory"); }
template <int N>
__device__ __forceinline__ void wgmma_wait() {
  asm volatile("wgmma.wait_group.sync.aligned %0;" ::"n"(N) : "memory");
}
template <int N>
__device__ __forceinline__ void fence_regs(float (&d)[N]) {
#pragma unroll
  for (int i = 0; i < N; i++) asm volatile("" : "+f"(d[i])::"memory");
}
__device__ __forceinline__ void fence_regs(uint32_t (&d)[32]) {
#pragma unroll
  for (int i = 0; i < 16; i++) asm volatile("" : "+r"(d[i])::"memory");
}
template <int N>
__device__ __forceinline__ void undef_regs(float (&d)[N]) {
#pragma unroll
  for (int i = 0; i < N; i++) d[i] = 0.f;
}
template <int N>
__device__ __forceinline__ void undef_regs(uint32_t (&d)[N]) {
#pragma unroll
  for (int i = 0; i < N; i++) d[i] = 0u;
}
__device__ __forceinline__ uint32_t pack_bf16(float lo, float hi) {
  uint32_t r;
  asm("cvt.rn.bf16x2.f32 %0, %1, %2;" : "=r"(r) : "f"(hi), "f"(lo));
  return r;
}
__device__ __forceinline__ void stmatrix_x4(uint32_t addr, uint32_t r0, uint32_t r1, uint32_t r2, uint32_t r3) {
  asm volatile("stmatrix.sync.aligned.m8n8.x4.shared.b16 [%0], {%1, %2, %3, %4};" ::"r"(addr), "r"(r0), "r"(r1),
               "r"(r2), "r"(r3)
               : "memory");
}
__device__ __forceinline__ void stmatrix_x4_p(uint32_t addr, uint32_t r0, uint32_t r1, uint32_t r2, uint32_t r3,
                                              bool on) {
  asm volatile("{\n.reg .pred p;\nsetp.ne.b32 p, %5, 0;\n@p stmatrix.sync.aligned.m8n8.x4.shared.b16 [%0], {%1, %2, %3, %4};\n}" ::"r"(addr),
               "r"(r0), "r"(r1), "r"(r2), "r"(r3), "r"((int)on)
               : "memory");
}
__device__ __forceinline__ float ex2(float x) {
  float y;
  asm("ex2.approx.ftz.f32 %0, %1;" : "=f"(y) : "f"(x));
  return y;
}
__device__ __forceinline__ float rcp(float x) {
  float y;
  asm("rcp.approx.ftz.f32 %0, %1;" : "=f"(y) : "f"(x));
  return y;
}
__device__ __forceinline__ float ex2v(float x) {
  float y;
  asm volatile("ex2.approx.ftz.f32 %0, %1;" : "=f"(y) : "f"(x));
  return y;
}
__device__ __forceinline__ float addv(float a, float b) {
  float y;
  asm volatile("add.f32 %0, %1, %2;" : "=f"(y) : "f"(a), "f"(b));
  return y;
}
__device__ __forceinline__ void mbar_arrive_elect(uint32_t bar, bool on) {
  asm volatile("{\n.reg .pred p, q;\nelect.sync _|q, 0xffffffff;\nsetp.ne.and.b32 p, %1, 0, q;\n@p mbarrier.arrive.shared::cta.b64 _, [%0];\n}" ::"r"(bar),
               "r"((int)on)
               : "memory");
}
__device__ __forceinline__ float mbar_test2(uint32_t bar0, uint32_t par0, uint32_t bar1, uint32_t par1) {
  float f;
  asm volatile(
      "{\n.reg .pred p, q;\nmbarrier.test_wait.parity.shared::cta.b64 p, [%1], %2;\n"
      "mbarrier.test_wait.parity.shared::cta.b64 q, [%3], %4;\nand.pred p, p, q;\nselp.f32 %0, 0f00000000, 0f80000000, p;\n}"
      : "=f"(f)
      : "r"(bar0), "r"(par0), "r"(bar1), "r"(par1)
      : "memory");
  return f;
}
__device__ __forceinline__ void mbar_wait_rest(uint32_t bar, uint32_t parity, bool ok) {
  asm volatile(
      "{\n.reg .pred p;\n.reg .u32 t;\n"
      "setp.ne.b32 p, %2, 0;\n"
      "@p bra DONE;\n"
      "mov.u32 t, 0x100000;\n"
      "LAB_WAIT:\n"
      "mbarrier.try_wait.parity.shared::cta.b64 p, [%0], %1;\n"
      "@p bra DONE;\n"
      "sub.u32 t, t, 1;\n"
      "setp.ne.u32 p, t, 0;\n"
      "@p bra LAB_WAIT;\n"
      "trap;\n"
      "DONE:\n}" ::"r"(bar),
      "r"(parity), "r"((int)ok)
      : "memory");
}
__device__ __forceinline__ void send_peer(uint32_t addr, uint32_t bar, uint32_t v) {
  asm volatile(
      "{\n.reg .b32 ra, rb;\nmapa.shared::cluster.u32 ra, %0, 1;\nmapa.shared::cluster.u32 rb, %1, 1;\n"
      "st.async.weak.shared::cluster.mbarrier::complete_tx::bytes.b32 [ra], %2, [rb];\n}" ::"r"(addr),
      "r"(bar), "r"(v)
      : "memory");
}
__device__ __forceinline__ void cnt_signal(int idx, uint32_t inc = 1) {
  asm volatile("red.release.gpu.global.add.u32 [%0], %1;" ::"l"(g_cnt + idx * 8), "r"(inc) : "memory");
}
__device__ __forceinline__ void cnt_signal_done(int idx, uint32_t inc = 1) {
  asm volatile("fence.proxy.async.global;" ::: "memory");
  cnt_signal(idx, inc);
}
__device__ __forceinline__ uint32_t cnt_next(int idx) {
  uint32_t v;
  asm volatile("atom.relaxed.gpu.global.add.u32 %0, [%1], 1;" : "=r"(v) : "l"(g_cnt + idx * 8) : "memory");
  return v;
}
__device__ __forceinline__ uint32_t cnt_peek(int idx) {
  uint32_t v;
  asm volatile("ld.acquire.gpu.global.u32 %0, [%1];" : "=r"(v) : "l"(g_cnt + idx * 8) : "memory");
  return v;
}
__device__ __forceinline__ void cnt_wait(int idx, uint32_t target) {
  asm volatile(
      "{\n.reg .pred p;\n.reg .u32 v, t0, t1;\n"
      "ld.acquire.gpu.global.u32 v, [%0];\n"
      "setp.ge.u32 p, v, %1;\n"
      "@p bra DONE;\n"
      "mov.u32 t0, %%clock;\n"
      "LAB_WAIT:\n"
      "nanosleep.u32 100;\n"
      "ld.acquire.gpu.global.u32 v, [%0];\n"
      "setp.ge.u32 p, v, %1;\n"
      "@p bra DONE;\n"
      "mov.u32 t1, %%clock;\n"
      "sub.u32 t1, t1, t0;\n"
      "setp.lt.u32 p, t1, 0x80000000;\n"
      "@p bra LAB_WAIT;\n"
      "trap;\n"
      "DONE:\n}" ::"l"(g_cnt + idx * 8),
      "r"(target)
      : "memory");
}
__device__ __forceinline__ void cnt_wait_bit(int idx, uint32_t bit, uint32_t& v) {
  asm volatile(
      "{\n.reg .pred p;\n.reg .u32 x, t0, t1;\n"
      "and.b32 x, %0, %2;\n"
      "setp.ne.u32 p, x, 0;\n"
      "@p bra DONE;\n"
      "mov.u32 t0, %%clock;\n"
      "LAB_WAIT:\n"
      "ld.acquire.gpu.global.u32 %0, [%1];\n"
      "and.b32 x, %0, %2;\n"
      "setp.ne.u32 p, x, 0;\n"
      "@p bra DONE;\n"
      "nanosleep.u32 64;\n"
      "mov.u32 t1, %%clock;\n"
      "sub.u32 t1, t1, t0;\n"
      "setp.lt.u32 p, t1, 0x80000000;\n"
      "@p bra LAB_WAIT;\n"
      "trap;\n"
      "DONE:\n}" : "+r"(v) : "l"(g_cnt + idx * 8),
      "r"(bit)
      : "memory");
}
__device__ __forceinline__ bool cnt_done(uint32_t total) {
  uint32_t old;
  asm volatile("atom.acq_rel.gpu.global.add.u32 %0, [%1], 1;" : "=r"(old) : "l"(g_cnt + CNT_DONE * 8) : "memory");
  return old == total - 1;
}
__device__ __forceinline__ void cnt_rearm() {
#pragma unroll
  for (int i = 0; i < CNT_N; i++) g_cnt[i * 8] = 0;
}
__device__ __forceinline__ void fence_proxy_async_global() { asm volatile("fence.proxy.async.global;" ::: "memory"); }
#ifdef TIMELINE
__device__ __forceinline__ void tl_rec(int role, int& n, uint32_t code) {
  unsigned long long t;
  asm volatile("mov.u64 %0, %%globaltimer;" : "=l"(t));
  uint32_t c;
  asm volatile("mov.u32 %0, %%clock;" : "=r"(c));
  if (n < 32) {
    g_tl[(blockIdx.x * 4 + role) * 64 + 2 * n] = t;
    g_tl[(blockIdx.x * 4 + role) * 64 + 2 * n + 1] = ((unsigned long long)code << 32) | c;
  }
  n++;
}
#define TL(role, code) tl_rec(role, tln, code)
__device__ __forceinline__ void tl_rec_p(int role, int& n, uint32_t code, bool on) {
  unsigned long long t;
  asm volatile("mov.u64 %0, %%globaltimer;" : "=l"(t));
  uint32_t c;
  asm volatile("mov.u32 %0, %%clock;" : "=r"(c));
  asm volatile("{\n.reg .pred p;\nsetp.ne.b32 p, %3, 0;\n@p st.global.v2.u64 [%0], {%1, %2};\n}" ::"l"(g_tl + (blockIdx.x * 4 + role) * 64 + 2 * n),
               "l"(t), "l"(((unsigned long long)code << 32) | c), "r"((int)(on && n < 32)) : "memory");
  n++;
}
#define TL0(code) tl_rec_p(0, tln, code, threadIdx.x == 0)
#define TL_DECL int tln = 0
#ifdef TLWAIT
#define TW_DECL uint32_t w0 = 0, w1 = 0, w2 = 0, w3 = 0; int tln3 = 0
#define TW(w, stmt) { uint32_t c0_ = clock(); stmt; w += clock() - c0_; }
#define TW_FLUSH() { tl_rec_p(3, tln3, (min(w0, 65534u) << 16) | min(w1, 65534u), threadIdx.x == TLWAIT); tl_rec_p(3, tln3, (min(w2, 65534u) << 16) | min(w3, 65534u), threadIdx.x == TLWAIT); w0 = w1 = w2 = w3 = 0; }
#define TW_END() tl_rec_p(3, tln3, 0xFFFF, threadIdx.x == TLWAIT)
#endif
#else
#define TL(role, code)
#define TL0(code)
#define TL_DECL
#endif
#ifdef TRACE
__device__ uint32_t g_tr[2 * 2 * 4096];
#define TR_DECL int trn = 0; const bool tron = (blockIdx.x == TRACE || blockIdx.x == TRACE2) && (threadIdx.x & 127) == TRW * 32; uint32_t* trp = g_tr + ((blockIdx.x == TRACE ? 0 : 2) + (threadIdx.x >> 7)) * 4096
#ifndef TRW
#define TRW 0
#endif
#ifndef TRM
#define TRM 0xFFFF
#endif
#define TRI(id, code) if ((TRM >> (id)) & 1) { asm volatile("{\n.reg .pred p;\nsetp.ne.b32 p, %2, 0;\n@p st.global.u32 [%0], %1;\n}" ::"l"(trp + trn), "r"(((uint32_t)clock() << 4) | (code)), "r"((int)(tron && trn < 4095)) : "memory"); trn++; }
#define TR(code) TRI(code, code)
#else
#define TR_DECL
#define TR(code)
#define TRI(id, code)
#endif
#ifndef TLWAIT
#define TW_DECL
#define TW(w, stmt) stmt
#define TW_FLUSH()
#define TW_END()
#endif

__device__ __forceinline__ uint32_t make_desc(uint32_t addr, uint32_t lbo_bytes) {
  return (addr >> 4) + ((lbo_bytes >> 4) << 16);
}

__device__ __forceinline__ void wgmma_ss_n128(float (&d)[64], uint32_t da, uint32_t db, int scale_d) {
  asm volatile("{\n.reg .pred p;\n.reg .b64 a, b;\nsetp.ne.b32 p, %66, 0;\nmov.b64 a, {%64, 0x40000040};\nmov.b64 b, {%65, 0x40000040};\n"
    "wgmma.mma_async.sync.aligned.m64n128k16.f32.bf16.bf16 {%0, %1, %2, %3, %4, %5, %6, %7, %8, %9, %10, %11, %12, %13, %14, %15, %16, %17, %18, %19, %20, %21, %22, %23, %24, %25, %26, %27, %28, %29, %30, %31, %32, %33, %34, %35, %36, %37, %38, %39, %40, %41, %42, %43, %44, %45, %46, %47, %48, %49, %50, %51, %52, %53, %54, %55, %56, %57, %58, %59, %60, %61, %62, %63}, a, b, p, 1, 1, 0, 0;\n}\n"
    : "+f"(d[0]), "+f"(d[1]), "+f"(d[2]), "+f"(d[3]), "+f"(d[4]), "+f"(d[5]), "+f"(d[6]), "+f"(d[7]), "+f"(d[8]), "+f"(d[9]), "+f"(d[10]), "+f"(d[11]), "+f"(d[12]), "+f"(d[13]), "+f"(d[14]), "+f"(d[15]), "+f"(d[16]), "+f"(d[17]), "+f"(d[18]), "+f"(d[19]), "+f"(d[20]), "+f"(d[21]), "+f"(d[22]), "+f"(d[23]), "+f"(d[24]), "+f"(d[25]), "+f"(d[26]), "+f"(d[27]), "+f"(d[28]), "+f"(d[29]), "+f"(d[30]), "+f"(d[31]), "+f"(d[32]), "+f"(d[33]), "+f"(d[34]), "+f"(d[35]), "+f"(d[36]), "+f"(d[37]), "+f"(d[38]), "+f"(d[39]), "+f"(d[40]), "+f"(d[41]), "+f"(d[42]), "+f"(d[43]), "+f"(d[44]), "+f"(d[45]), "+f"(d[46]), "+f"(d[47]), "+f"(d[48]), "+f"(d[49]), "+f"(d[50]), "+f"(d[51]), "+f"(d[52]), "+f"(d[53]), "+f"(d[54]), "+f"(d[55]), "+f"(d[56]), "+f"(d[57]), "+f"(d[58]), "+f"(d[59]), "+f"(d[60]), "+f"(d[61]), "+f"(d[62]), "+f"(d[63])
    : "r"(da), "r"(db), "r"(scale_d));
}
__device__ __forceinline__ void wgmma_ss_n64(float (&d)[32], uint32_t da, uint32_t db, int scale_d) {
  asm volatile("{\n.reg .pred p;\n.reg .b64 a, b;\nsetp.ne.b32 p, %34, 0;\nmov.b64 a, {%32, 0x40000040};\nmov.b64 b, {%33, 0x40000040};\n"
    "wgmma.mma_async.sync.aligned.m64n64k16.f32.bf16.bf16 {%0, %1, %2, %3, %4, %5, %6, %7, %8, %9, %10, %11, %12, %13, %14, %15, %16, %17, %18, %19, %20, %21, %22, %23, %24, %25, %26, %27, %28, %29, %30, %31}, a, b, p, 1, 1, 0, 0;\n}\n"
    : "+f"(d[0]), "+f"(d[1]), "+f"(d[2]), "+f"(d[3]), "+f"(d[4]), "+f"(d[5]), "+f"(d[6]), "+f"(d[7]), "+f"(d[8]), "+f"(d[9]), "+f"(d[10]), "+f"(d[11]), "+f"(d[12]), "+f"(d[13]), "+f"(d[14]), "+f"(d[15]), "+f"(d[16]), "+f"(d[17]), "+f"(d[18]), "+f"(d[19]), "+f"(d[20]), "+f"(d[21]), "+f"(d[22]), "+f"(d[23]), "+f"(d[24]), "+f"(d[25]), "+f"(d[26]), "+f"(d[27]), "+f"(d[28]), "+f"(d[29]), "+f"(d[30]), "+f"(d[31])
    : "r"(da), "r"(db), "r"(scale_d));
}
__device__ __forceinline__ void wgmma_rs_n128_tb(float (&d)[64], uint32_t a0, uint32_t a1, uint32_t a2, uint32_t a3, uint32_t db, int scale_d) {
  asm volatile("{\n.reg .pred p;\n.reg .b64 b;\nsetp.ne.b32 p, %69, 0;\nmov.b64 b, {%68, 0x40000040};\n"
    "wgmma.mma_async.sync.aligned.m64n128k16.f32.bf16.bf16 {%0, %1, %2, %3, %4, %5, %6, %7, %8, %9, %10, %11, %12, %13, %14, %15, %16, %17, %18, %19, %20, %21, %22, %23, %24, %25, %26, %27, %28, %29, %30, %31, %32, %33, %34, %35, %36, %37, %38, %39, %40, %41, %42, %43, %44, %45, %46, %47, %48, %49, %50, %51, %52, %53, %54, %55, %56, %57, %58, %59, %60, %61, %62, %63}, {%64, %65, %66, %67}, b, p, 1, 1, 1;\n}\n"
    : "+f"(d[0]), "+f"(d[1]), "+f"(d[2]), "+f"(d[3]), "+f"(d[4]), "+f"(d[5]), "+f"(d[6]), "+f"(d[7]), "+f"(d[8]), "+f"(d[9]), "+f"(d[10]), "+f"(d[11]), "+f"(d[12]), "+f"(d[13]), "+f"(d[14]), "+f"(d[15]), "+f"(d[16]), "+f"(d[17]), "+f"(d[18]), "+f"(d[19]), "+f"(d[20]), "+f"(d[21]), "+f"(d[22]), "+f"(d[23]), "+f"(d[24]), "+f"(d[25]), "+f"(d[26]), "+f"(d[27]), "+f"(d[28]), "+f"(d[29]), "+f"(d[30]), "+f"(d[31]), "+f"(d[32]), "+f"(d[33]), "+f"(d[34]), "+f"(d[35]), "+f"(d[36]), "+f"(d[37]), "+f"(d[38]), "+f"(d[39]), "+f"(d[40]), "+f"(d[41]), "+f"(d[42]), "+f"(d[43]), "+f"(d[44]), "+f"(d[45]), "+f"(d[46]), "+f"(d[47]), "+f"(d[48]), "+f"(d[49]), "+f"(d[50]), "+f"(d[51]), "+f"(d[52]), "+f"(d[53]), "+f"(d[54]), "+f"(d[55]), "+f"(d[56]), "+f"(d[57]), "+f"(d[58]), "+f"(d[59]), "+f"(d[60]), "+f"(d[61]), "+f"(d[62]), "+f"(d[63])
    : "r"(a0), "r"(a1), "r"(a2), "r"(a3), "r"(db), "r"(scale_d));
}
__device__ __forceinline__ void wgmma_ss_n72_init(float (&d)[36], uint32_t da, uint32_t db) {
  asm volatile("{\n.reg .pred p;\n.reg .b64 a, b;\nsetp.ne.b32 p, 0, 0;\nmov.b64 a, {%36, 0x40000040};\nmov.b64 b, {%37, 0x40000040};\n"
    "wgmma.mma_async.sync.aligned.m64n72k16.f32.bf16.bf16 {%0, %1, %2, %3, %4, %5, %6, %7, %8, %9, %10, %11, %12, %13, %14, %15, %16, %17, %18, %19, %20, %21, %22, %23, %24, %25, %26, %27, %28, %29, %30, %31, %32, %33, %34, %35}, a, b, p, 1, 1, 0, 0;\n}\n"
    : "=f"(d[0]), "=f"(d[1]), "=f"(d[2]), "=f"(d[3]), "=f"(d[4]), "=f"(d[5]), "=f"(d[6]), "=f"(d[7]), "=f"(d[8]), "=f"(d[9]), "=f"(d[10]), "=f"(d[11]), "=f"(d[12]), "=f"(d[13]), "=f"(d[14]), "=f"(d[15]), "=f"(d[16]), "=f"(d[17]), "=f"(d[18]), "=f"(d[19]), "=f"(d[20]), "=f"(d[21]), "=f"(d[22]), "=f"(d[23]), "=f"(d[24]), "=f"(d[25]), "=f"(d[26]), "=f"(d[27]), "=f"(d[28]), "=f"(d[29]), "=f"(d[30]), "=f"(d[31]), "=f"(d[32]), "=f"(d[33]), "=f"(d[34]), "=f"(d[35])
    : "r"(da), "r"(db));
}
__device__ __forceinline__ void wgmma_ss_n72(float (&d)[36], uint32_t da, uint32_t db, int scale_d) {
  asm volatile("{\n.reg .pred p;\n.reg .b64 a, b;\nsetp.ne.b32 p, %38, 0;\nmov.b64 a, {%36, 0x40000040};\nmov.b64 b, {%37, 0x40000040};\n"
    "wgmma.mma_async.sync.aligned.m64n72k16.f32.bf16.bf16 {%0, %1, %2, %3, %4, %5, %6, %7, %8, %9, %10, %11, %12, %13, %14, %15, %16, %17, %18, %19, %20, %21, %22, %23, %24, %25, %26, %27, %28, %29, %30, %31, %32, %33, %34, %35}, a, b, p, 1, 1, 0, 0;\n}\n"
    : "+f"(d[0]), "+f"(d[1]), "+f"(d[2]), "+f"(d[3]), "+f"(d[4]), "+f"(d[5]), "+f"(d[6]), "+f"(d[7]), "+f"(d[8]), "+f"(d[9]), "+f"(d[10]), "+f"(d[11]), "+f"(d[12]), "+f"(d[13]), "+f"(d[14]), "+f"(d[15]), "+f"(d[16]), "+f"(d[17]), "+f"(d[18]), "+f"(d[19]), "+f"(d[20]), "+f"(d[21]), "+f"(d[22]), "+f"(d[23]), "+f"(d[24]), "+f"(d[25]), "+f"(d[26]), "+f"(d[27]), "+f"(d[28]), "+f"(d[29]), "+f"(d[30]), "+f"(d[31]), "+f"(d[32]), "+f"(d[33]), "+f"(d[34]), "+f"(d[35])
    : "r"(da), "r"(db), "r"(scale_d));
}
template <int OA, int OB>
__device__ __forceinline__ void wgmma_ss_n128_tb(float (&d)[64], uint32_t da, uint32_t db, int scale_d) {
  asm volatile("{\n.reg .pred p;\n.reg .b64 a, b;\n.reg .b32 x, y;\nsetp.ne.b32 p, %66, 0;\nadd.u32 x, %64, %67;\nadd.u32 y, %65, %68;\nmov.b64 a, {x, 0x40000040};\nmov.b64 b, {y, 0x40000040};\n"
    "wgmma.mma_async.sync.aligned.m64n128k16.f32.bf16.bf16 {%0, %1, %2, %3, %4, %5, %6, %7, %8, %9, %10, %11, %12, %13, %14, %15, %16, %17, %18, %19, %20, %21, %22, %23, %24, %25, %26, %27, %28, %29, %30, %31, %32, %33, %34, %35, %36, %37, %38, %39, %40, %41, %42, %43, %44, %45, %46, %47, %48, %49, %50, %51, %52, %53, %54, %55, %56, %57, %58, %59, %60, %61, %62, %63}, a, b, p, 1, 1, 0, 1;\n}\n"
    : "+f"(d[0]), "+f"(d[1]), "+f"(d[2]), "+f"(d[3]), "+f"(d[4]), "+f"(d[5]), "+f"(d[6]), "+f"(d[7]), "+f"(d[8]), "+f"(d[9]), "+f"(d[10]), "+f"(d[11]), "+f"(d[12]), "+f"(d[13]), "+f"(d[14]), "+f"(d[15]), "+f"(d[16]), "+f"(d[17]), "+f"(d[18]), "+f"(d[19]), "+f"(d[20]), "+f"(d[21]), "+f"(d[22]), "+f"(d[23]), "+f"(d[24]), "+f"(d[25]), "+f"(d[26]), "+f"(d[27]), "+f"(d[28]), "+f"(d[29]), "+f"(d[30]), "+f"(d[31]), "+f"(d[32]), "+f"(d[33]), "+f"(d[34]), "+f"(d[35]), "+f"(d[36]), "+f"(d[37]), "+f"(d[38]), "+f"(d[39]), "+f"(d[40]), "+f"(d[41]), "+f"(d[42]), "+f"(d[43]), "+f"(d[44]), "+f"(d[45]), "+f"(d[46]), "+f"(d[47]), "+f"(d[48]), "+f"(d[49]), "+f"(d[50]), "+f"(d[51]), "+f"(d[52]), "+f"(d[53]), "+f"(d[54]), "+f"(d[55]), "+f"(d[56]), "+f"(d[57]), "+f"(d[58]), "+f"(d[59]), "+f"(d[60]), "+f"(d[61]), "+f"(d[62]), "+f"(d[63])
    : "r"(da), "r"(db), "r"(scale_d), "n"(OA), "n"(OB));
}
template <int OA, int OB>
__device__ __forceinline__ void wgmma_ss_n256_tbo(float (&d)[128], uint32_t da, uint32_t db, int scale_d) {
  asm volatile("{\n.reg .pred p;\n.reg .b64 a, b;\n.reg .b32 x, y;\nsetp.ne.b32 p, %130, 0;\nadd.u32 x, %128, %131;\nadd.u32 y, %129, %132;\nmov.b64 a, {x, 0x40000040};\nmov.b64 b, {y, 0x40000040};\n"
    "wgmma.mma_async.sync.aligned.m64n256k16.f32.bf16.bf16 {%0, %1, %2, %3, %4, %5, %6, %7, %8, %9, %10, %11, %12, %13, %14, %15, %16, %17, %18, %19, %20, %21, %22, %23, %24, %25, %26, %27, %28, %29, %30, %31, %32, %33, %34, %35, %36, %37, %38, %39, %40, %41, %42, %43, %44, %45, %46, %47, %48, %49, %50, %51, %52, %53, %54, %55, %56, %57, %58, %59, %60, %61, %62, %63, %64, %65, %66, %67, %68, %69, %70, %71, %72, %73, %74, %75, %76, %77, %78, %79, %80, %81, %82, %83, %84, %85, %86, %87, %88, %89, %90, %91, %92, %93, %94, %95, %96, %97, %98, %99, %100, %101, %102, %103, %104, %105, %106, %107, %108, %109, %110, %111, %112, %113, %114, %115, %116, %117, %118, %119, %120, %121, %122, %123, %124, %125, %126, %127}, a, b, p, 1, 1, 0, 1;\n}\n"
    : "+f"(d[0]), "+f"(d[1]), "+f"(d[2]), "+f"(d[3]), "+f"(d[4]), "+f"(d[5]), "+f"(d[6]), "+f"(d[7]), "+f"(d[8]), "+f"(d[9]), "+f"(d[10]), "+f"(d[11]), "+f"(d[12]), "+f"(d[13]), "+f"(d[14]), "+f"(d[15]), "+f"(d[16]), "+f"(d[17]), "+f"(d[18]), "+f"(d[19]), "+f"(d[20]), "+f"(d[21]), "+f"(d[22]), "+f"(d[23]), "+f"(d[24]), "+f"(d[25]), "+f"(d[26]), "+f"(d[27]), "+f"(d[28]), "+f"(d[29]), "+f"(d[30]), "+f"(d[31]), "+f"(d[32]), "+f"(d[33]), "+f"(d[34]), "+f"(d[35]), "+f"(d[36]), "+f"(d[37]), "+f"(d[38]), "+f"(d[39]), "+f"(d[40]), "+f"(d[41]), "+f"(d[42]), "+f"(d[43]), "+f"(d[44]), "+f"(d[45]), "+f"(d[46]), "+f"(d[47]), "+f"(d[48]), "+f"(d[49]), "+f"(d[50]), "+f"(d[51]), "+f"(d[52]), "+f"(d[53]), "+f"(d[54]), "+f"(d[55]), "+f"(d[56]), "+f"(d[57]), "+f"(d[58]), "+f"(d[59]), "+f"(d[60]), "+f"(d[61]), "+f"(d[62]), "+f"(d[63]), "+f"(d[64]), "+f"(d[65]), "+f"(d[66]), "+f"(d[67]), "+f"(d[68]), "+f"(d[69]), "+f"(d[70]), "+f"(d[71]), "+f"(d[72]), "+f"(d[73]), "+f"(d[74]), "+f"(d[75]), "+f"(d[76]), "+f"(d[77]), "+f"(d[78]), "+f"(d[79]), "+f"(d[80]), "+f"(d[81]), "+f"(d[82]), "+f"(d[83]), "+f"(d[84]), "+f"(d[85]), "+f"(d[86]), "+f"(d[87]), "+f"(d[88]), "+f"(d[89]), "+f"(d[90]), "+f"(d[91]), "+f"(d[92]), "+f"(d[93]), "+f"(d[94]), "+f"(d[95]), "+f"(d[96]), "+f"(d[97]), "+f"(d[98]), "+f"(d[99]), "+f"(d[100]), "+f"(d[101]), "+f"(d[102]), "+f"(d[103]), "+f"(d[104]), "+f"(d[105]), "+f"(d[106]), "+f"(d[107]), "+f"(d[108]), "+f"(d[109]), "+f"(d[110]), "+f"(d[111]), "+f"(d[112]), "+f"(d[113]), "+f"(d[114]), "+f"(d[115]), "+f"(d[116]), "+f"(d[117]), "+f"(d[118]), "+f"(d[119]), "+f"(d[120]), "+f"(d[121]), "+f"(d[122]), "+f"(d[123]), "+f"(d[124]), "+f"(d[125]), "+f"(d[126]), "+f"(d[127])
    : "r"(da), "r"(db), "r"(scale_d), "n"(OA), "n"(OB));
}

constexpr int NCTA = 132;
constexpr int NCLUSTER = 66;
constexpr int NPROB = 6;
#ifdef GEMM_ONLY
#define DO_LOCAL false
#define DO_ATT false
#else
#define DO_LOCAL true
#define DO_ATT true
#endif
#ifdef ATT_ONLY
#define NA_CL_ 0
#define NITEMS 768
#else
#define NA_CL_ 32
#define NITEMS 256
#endif
constexpr int G1_MAX = 24, NA_CL = NA_CL_, NB_CL = NCLUSTER - NA_CL;
constexpr int TILE32K = 32768;
constexpr uint32_t DBASE = 1024;
constexpr int OFF_STG = 4 * TILE32K;
constexpr int OFF_A = 5 * TILE32K;
constexpr int OFF_BAR = 7 * TILE32K;
constexpr int L_K = 8192, L_V = L_K + 9216, L_P = L_V + 9216;
constexpr int SMEM_BYTES = OFF_BAR + 1024;
constexpr int B_GFULL = 0, B_GEMPTY = 32, B_AFULL = 64, B_AEMPTY = 104, B_QFULL = 144, B_QEMPTY = 160,
              B_SFULL = 176, B_SEMPTY = 208, B_OFULL = 240, B_STGFREE = 256, S_CODE = 272, B_SFULL2 = 304,
              B_MAIL = 336, S_MAIL = 368;
#ifndef FS
#define FS 2
#endif
#ifndef HW
#define HW 1
#endif
#ifndef PACE
#define PACE 900u
#endif
#ifndef REG_C
#define REG_C 232
#define REG_P 40
#endif

struct Params {
  CUtensorMap ta[NPROB];
  CUtensorMap tb[NPROB];
  CUtensorMap tc[NPROB];
  CUtensorMap tq, tk, tv, to, tl, th;
  bf16* ob;
  uint16_t g[NCLUSTER][G1_MAX];
  uint16_t order[256];
};
__device__ __forceinline__ uint32_t tail_item(uint32_t code) {
  return (code & 0x7FFF) < 32 ? (5u << 8) | ((code & 4) << 4) | ((code & 0x18) << 1) | (code & 3) : 0xFFFFu;
}
#ifndef HM
#define HM 0x39383F00
#endif
#define HINT(b) ((HM >> (b) & 1) ? EV_FIRST : EV_NORMAL)
__device__ __forceinline__ uint32_t lds32(uint32_t a) {
  uint32_t v;
  asm volatile("ld.shared.u32 %0, [%1];" : "=r"(v) : "r"(a) : "memory");
  return v;
}
__device__ __forceinline__ uint4 lds128(uint32_t a) {
  uint4 v;
  asm volatile("ld.shared.v4.u32 {%0, %1, %2, %3}, [%4];" : "=r"(v.x), "=r"(v.y), "=r"(v.z), "=r"(v.w) : "r"(a) : "memory");
  return v;
}
__device__ __forceinline__ void sts64(uint32_t a, float x, float y) {
  asm volatile("st.shared.v2.f32 [%0], {%1, %2};" ::"r"(a), "f"(x), "f"(y) : "memory");
}
__device__ __forceinline__ void sts32(uint32_t a, uint32_t v) {
  asm volatile("st.shared.u32 [%0], %1;" ::"r"(a), "r"(v) : "memory");
}
__device__ __forceinline__ uint32_t opaque_tid() {
  uint32_t t;
  asm volatile("mov.u32 %0, %%tid.x;" : "=r"(t));
  return t;
}
__device__ __forceinline__ uint32_t stg_off(uint32_t tid) {
  return (tid >> 5) * 2048 + (tid & 15) * 128 + ((((tid >> 4) & 1) ^ (tid & 7)) << 4);
}
__device__ __forceinline__ int prob_nkb4(int prob) { return (0x4F4224 >> (prob * 4) & 15) + (prob == 4); }

constexpr float SM_C = 0.08838834764831845f * 1.4426950408889634f;
constexpr float SM_HI = 1099511627776.0f;
constexpr float SM_LO = 8.673617379884035e-19f;
__device__ __forceinline__ void softmax_max(const float (&s)[64], float& a0, float& a1) {
  a0 = fmaxf(s[0], s[1]);
  a1 = fmaxf(s[2], s[3]);
#pragma unroll
  for (int j = 1; j < 16; j++) {
    a0 = fmaxf(a0, fmaxf(s[4 * j], s[4 * j + 1]));
    a1 = fmaxf(a1, fmaxf(s[4 * j + 2], s[4 * j + 3]));
  }
  a0 = fmaxf(a0, __shfl_xor_sync(0xffffffffu, a0, 1));
  a1 = fmaxf(a1, __shfl_xor_sync(0xffffffffu, a1, 1));
  a0 = fmaxf(a0, __shfl_xor_sync(0xffffffffu, a0, 2));
  a1 = fmaxf(a1, __shfl_xor_sync(0xffffffffu, a1, 2));
}
template <int J0, int J1, bool OFS, int N>
__device__ __forceinline__ void softmax_exp(const float (&s)[64], float b0, float b1, uint32_t (&out)[N], float& t0,
                                            float& t1) {
#pragma unroll
  for (int j = J0; j < J1; j++) {
    const float e0 = ex2(OFS ? s[4 * j] + b0 : s[4 * j]);
    const float e1 = ex2(OFS ? s[4 * j + 1] + b0 : s[4 * j + 1]);
    const float e2 = ex2(OFS ? s[4 * j + 2] + b1 : s[4 * j + 2]);
    const float e3 = ex2(OFS ? s[4 * j + 3] + b1 : s[4 * j + 3]);
    t0 += e0 + e1;
    t1 += e2 + e3;
    out[2 * j] = pack_bf16(e0, e1);
    out[2 * j + 1] = pack_bf16(e2, e3);
  }
}

__device__ __forceinline__ uint32_t scale_q(uint32_t x) {
  uint32_t t, y;
  asm("mul.rn.bf16x2 %0, %1, %2;" : "=r"(t) : "r"(x), "r"(0xb9d8b9d8u));
  asm("fma.rn.bf16x2 %0, %1, %2, %3;" : "=r"(y) : "r"(x), "r"(0x3e033e03u), "r"(t));
  return y;
}

__global__ void __cluster_dims__(2, 1, 1) __launch_bounds__(384, 1) mega_kernel(const __grid_constant__ Params p) {
  extern __shared__ __align__(1024) uint8_t smem_raw[];
#ifdef TRACE
  const uint32_t c_entry = clock();
#endif
  const uint32_t sbase = smem_u32(smem_raw);
  const uint32_t s_bar = sbase + OFF_BAR;
  const int cluster_id = blockIdx.x >> 1;
  const bool isB = cluster_id >= NA_CL;
#if !defined(ATT_ONLY) && !defined(GEMM_ONLY)
#define EARLY 1
#else
#define EARLY 0
#endif
  const int prob0 = isB ? 3 : cluster_id >> 4;
  const int ng0 = (isB ? (cluster_id - NA_CL) >> 3 : (cluster_id >> 3) & 1) * 4;
  const uint32_t t0 = clock();
  auto early = [&](int s) {
    const uint32_t full = s_bar + B_GFULL + 8 * s;
    mbar_expect_tx(full, 49152);
    tma_load_3d(sbase + OFF_A + s * 16384, &p.ta[prob0], 0, (blockIdx.x & 15) * 128, s, full, EV_NORMAL);
    tma_load_3d(sbase + s * TILE32K, &p.tb[prob0], 0, s * 64, ng0, full, EV_NORMAL);
    tma_load_3d(sbase + s * TILE32K + 16384, &p.tb[prob0], 0, s * 64, ng0 + 2, full, EV_NORMAL);
  };
  if ((threadIdx.x >> 5) == 8) {
    if (elect_one()) {
      mbar_init(s_bar + B_GFULL, 1);
      asm volatile("fence.mbarrier_init.release.cluster;" ::: "memory");
      if (EARLY) early(0);
      for (int s = 1; s < 4; s++) mbar_init(s_bar + B_GFULL + 8 * s, 1);
      asm volatile("fence.mbarrier_init.release.cluster;" ::: "memory");
    }
    __syncwarp();
    named_bar_arrive(7, 288);
  }
  const int warp0 = __shfl_sync(0xffffffffu, threadIdx.x >> 5, 0);
  if (warp0 >= 8) reg_dealloc<REG_P>();
#define CLUSTER_ARRIVE() asm volatile("barrier.cluster.arrive.relaxed.aligned;" ::: "memory")
#define CLUSTER_WAIT() asm volatile("barrier.cluster.wait.acquire.aligned;" ::: "memory")

  if (warp0 >= 8) {
    if (warp0 == 10 && elect_one()) {
      if ((sbase & 0x3FFFFu) != DBASE) __trap();
      for (int s = 0; s < 4; s++) {
        mbar_init(s_bar + B_GEMPTY + 8 * s, 4);
        mbar_init(s_bar + B_SFULL + 8 * s, 4);
        mbar_init(s_bar + B_SFULL2 + 8 * s, 4);
        mbar_init(s_bar + B_SEMPTY + 8 * s, 1);
        mbar_init(s_bar + B_AFULL + 8 * s, 1);
        mbar_init(s_bar + B_AEMPTY + 8 * s, isB ? 4 : s ? 8 : 2);
        mbar_init(s_bar + B_MAIL + 8 * s, 1);
      }
      for (int s = 0; s < 2; s++) {
        mbar_init(s_bar + B_QFULL + 8 * s, 1);
        mbar_init(s_bar + B_QEMPTY + 8 * s, 2);
      }
      mbar_init(s_bar + B_OFULL, 8);
      mbar_init(s_bar + B_STGFREE, 1);
      asm volatile("fence.mbarrier_init.release.cluster;" ::: "memory");
    }
    __syncwarp();
    CLUSTER_ARRIVE();
    if (EARLY && warp0 == 8 && elect_one()) {
#pragma unroll 1
      for (int s = 1; s < 4; s++) {
        while ((uint32_t)clock() - t0 < s * PACE) {}
        early(s);
      }
    }
    __syncwarp();
    CLUSTER_WAIT();
    const uint32_t rank = blockIdx.x & 1;
    if (warp0 == 8) {
      if (elect_one()) {
        TL_DECL;
        uint32_t gphase = 1 - EARLY;
        uint32_t tail = 0;
        int gi = 0;
        uint32_t aswz = 0, lastq = 0, n = 0;
        uint32_t aprev = ~0u;
        for (int seg = 0; seg < 2; seg++) {
          for (;;) {
            uint32_t item = p.g[cluster_id][gi++];
            if (item == 0x500u) item = tail;
            if (item >= 0x600u) break;
            const int prob = item >> 8;
            const int rt = ((item >> 4) & 15) * 2 + rank;
            const int ngrp0 = (item & 15) * 4;
            const int nkb4 = prob_nkb4(prob);
            const CUtensorMap* ta = &p.ta[prob];
            const CUtensorMap* tb = &p.tb[prob];
            const uint64_t ahint = p.g[cluster_id][gi] >= 0x400u ? EV_FIRST : EV_NORMAL;
            const int rot4 = prob < 4 ? 1 - gi : 0;
            const uint32_t akey = (item + 0x100u) & 0x6F0u;
            const bool keep = akey == aprev;
            aprev = akey;
            TL(1, item);
            uint32_t seen = 0;
            if (prob == 5) {
              cnt_wait_bit(CNT_OB + (rt >> 2), 32u << (rt & 3) * 8, seen);
              fence_proxy_async_global();
            }
            for (int kb4 = EARLY && gi == 1; kb4 < nkb4; kb4++) {
#pragma unroll 1
              for (int s = 0; s < 4; s++) {
                const int bs = s ^ (n & 1);
                if (prob == 4 && !(s & 1)) {
                  cnt_wait_bit(CNT_CTX + rt, 1u << (kb4 * 2 + (s >> 1)), seen);
                  fence_proxy_async_global();
                }
                if (prob == 5 && kb4 == 0) {
                  mbar_wait(s_bar + B_AEMPTY + 8 * bs, (~(n + (s & 1)) >> 1) & 1);
                  if (s == 2) mbar_wait(s_bar + B_QEMPTY + (aswz ? 0 : 8), lastq);
                }
                mbar_wait(s_bar + B_GEMPTY + 8 * s, gphase);
                const uint32_t full = s_bar + B_GFULL + 8 * s;
                const int kb = ((kb4 + rot4) & (nkb4 - 1)) * 4 + s;
                if (keep && kb4 == 0) {
                  mbar_expect_tx(full, 32768);
                } else {
                  mbar_expect_tx(full, 49152);
                  tma_load_3d(sbase + OFF_A + ((s * 16384) ^ aswz), ta, 0, rt * 128, kb, full, ahint);
                }
                tma_load_3d_mc(sbase + bs * TILE32K + rank * 16384, tb, 0, kb * 64, ngrp0 + rank * 2, full,
                               (uint16_t)3, HINT(8 + prob));
              }
              gphase ^= 1;
            }
          }
          if (seg == 0 && isB && DO_ATT) {
            int pv_row = 0, pv_col = 0;
            uint64_t pv_hint = 0;
            bool pv_own = false;
#define ACQ_SLOT(slot, n)                                                              \
  {                                                                                    \
    if ((n) < 2) mbar_wait(s_bar + B_GEMPTY + 8 * (slot), gphase);                     \
    mbar_wait(s_bar + B_AEMPTY + 8 * (slot), (~(n) >> 1) & 1);                         \
  }
#define LOAD_KV(map, slot, row, col, own, hint)                                        \
  {                                                                                    \
    const uint32_t full = s_bar + B_AFULL + 8 * (slot);                                \
    mbar_expect_tx(full, TILE32K);                                                     \
    if (own) {                                                                         \
      tma_load_3d(sbase + (slot) * TILE32K, map, 0, row, col, full, hint);             \
      tma_load_3d(sbase + (slot) * TILE32K + 16384, map, 0, row, (col) + 1, full, hint); \
    } else {                                                                           \
      tma_load_3d_mc(sbase + (slot) * TILE32K + rank * 16384, map, 0, row, (col) + rank, full, (uint16_t)3, hint); \
    }                                                                                  \
  }
#define LOAD_V()                                                                       \
  {                                                                                    \
    const uint32_t vs = 3 - (n & 1);                                                   \
    ACQ_SLOT(vs, n - 1);                                                               \
    LOAD_KV(&p.tv, vs, pv_row, pv_col, pv_own, pv_hint)                                \
  }
#ifdef ATT_ONLY
#define NEXT_CODE() (nxt < NITEMS ? p.order[nxt & 255] : 0x8000u + 64)
#else
#define NEXT_CODE() (nxt < 256 ? p.order[nxt] : nxt + (0x8000u - 256))
#endif
            uint32_t code = p.order[cluster_id - NA_CL];
            int it = 0;
            uint32_t seen = 0;
            for (;; it++) {
              if (it == 1) mbar_wait(s_bar + B_STGFREE, 0);
              if (code & 0x8000u) break;
              const int head = code >> 4;
              const int q0 = code & 15, up = rank == (it & 1);
              uint32_t nxt = 0;
              TL(1, 0x1000 | code | up);
#ifndef ATT_ONLY
              if (seen < 48) cnt_wait(CNT_QKV + (head >> 1), 48);
#endif
              fence_proxy_async_global();
              {
                const int b = it & 1;
                if (it < 2) {
                  mbar_wait(s_bar + B_GEMPTY + 16 * b, gphase);
                  mbar_wait(s_bar + B_GEMPTY + 16 * b + 8, gphase);
                }
                mbar_wait(s_bar + B_QEMPTY + 8 * b, ((it >> 1) & 1) ^ 1);
                mbar_expect_tx(s_bar + B_QFULL + 8 * b, TILE32K);
                tma_load_3d(sbase + OFF_A + b * TILE32K, &p.tq, 0, (q0 + up) * 128, head * 2, s_bar + B_QFULL + 8 * b, HINT(24));
              }
#pragma unroll 1
              for (int i = q0 + (up & it); i >= -(up & ~it); i--) {
                const int t = i < 0 ? q0 + 1 : i;
                if (rank == 0 && i == min(q0, 1)) nxt = cnt_next(CNT_QUEUE) + NB_CL;
                if (i == 0) {
                  if (rank == 0) {
                    code = NEXT_CODE();
                    send_peer(s_bar + S_MAIL + 4 * (it & 3), s_bar + B_MAIL + 8 * (it & 3), code);
                  } else {
                    mbar_expect_tx(s_bar + B_MAIL + 8 * (it & 3), 4);
                    mbar_wait(s_bar + B_MAIL + 8 * (it & 3), (it >> 2) & 1);
                    code = lds32(s_bar + S_MAIL + 4 * (it & 3));
                  }
                  sts32(s_bar + S_CODE + 4 * ((it + 1) & 7), code);
                  seen = cnt_peek(CNT_QKV + ((code >> 5) & 15));
                }
                ACQ_SLOT(n & 1, n);
                LOAD_KV(&p.tk, n & 1, t * 128, head * 2, t > q0, HINT(t >= q0 ? 29 : 25))
                if (n) LOAD_V();
                n++;
                pv_row = t * 128;
                pv_col = head * 2;
                pv_own = t > q0;
                pv_hint = HINT(t >= q0 ? 29 : 26);
              }
            }
            ACQ_SLOT(n & 1, n);
            mbar_arrive(s_bar + B_AFULL + 8 * (n & 1));
            LOAD_V();
            if (rank & it) {
              ACQ_SLOT(2 + (n & 1), n);
#pragma unroll 1
              for (int i = 0; i < 8; i++) mbar_arrive_cluster_if(s_bar + B_AEMPTY + 8 * ((n & 1) + (i & 2)), i & 1, true);
              n++;
            }
            tail = tail_item(code);
            aswz = (it & 1) * TILE32K;
            mbar_wait(s_bar + B_QEMPTY + 8 * (it & 1), ((it >> 1) & 1) ^ 1);
            lastq = ((it - 1) >> 1) & 1;
            if (tail == 0xFFFFu) {
#pragma unroll 1
              for (int s = 0; s < 4; s++) mbar_wait(s_bar + B_AEMPTY + 8 * (s ^ (n & 1)), (~(n + (s & 1)) >> 1) & 1);
            }
          }
        }
        if (cnt_done(NCTA * 2)) cnt_rearm();
#pragma unroll 1
        for (int s = 0; s < 4; s++) mbar_wait(s_bar + B_GEMPTY + 8 * s, gphase);
        TL(1, 0xFFFF);
      }
    } else if (warp0 == 9) {
      if (elect_one()) {
        TL_DECL;
        uint32_t tail = 0;
        int gi = 0;
        uint32_t aswz = 0;
        bool rearm = false;
        for (int seg = 0; seg < 2; seg++) {
          for (;;) {
            uint32_t item = p.g[cluster_id][gi++];
            if (item == 0x500u) item = tail;
            if (item >= 0x600u) break;
            const int prob = item >> 8;
            const int rt = ((item >> 4) & 15) * 2 + rank;
            const int cg = (item & 15) * 4 + (prob == 5 ? 16 : 0);
            const CUtensorMap* tc = &p.tc[prob];
            const int nl = (p.g[cluster_id][gi] >> 8) == 4 && DO_LOCAL ? 8 : 1;
            const int grp = (blockIdx.x & 15) * 2 + ((blockIdx.x >> 4) & 1), r0 = (blockIdx.x >> 5) * 512;
            if (nl > 1) {
              cnt_wait(CNT_QKVB, 192);
              fence_proxy_async_global();
            }
            if (prob >= 4) rearm = cnt_done(NCTA * 2);
            const bool lastt = p.g[cluster_id][gi] >= 0x600u;
#pragma unroll 1
            for (int c = 0; c < 8; c++) {
              const int q = lastt ? c & 3 : c >> 1, w = lastt ? c >> 2 : c & 1;
              const int idx = w * 2 + (q & 1);
              const bool alt = lastt && q >= 2;
              mbar_wait(s_bar + (alt ? B_SFULL2 : B_SFULL) + 8 * idx, lastt ? seg : q >> 1);
              tma_store_4d(tc, sbase + (alt ? OFF_A + ((q * 16384) ^ aswz) + w * 8192 : OFF_STG + idx * 8192),
                           rt * 64 + w * 32, cg + q, HINT(16 + prob));
              bulk_commit();
              if (c > 0 && !lastt) {
                bulk_wait_read<1>();
                mbar_arrive(s_bar + B_SEMPTY + 8 * ((w ^ 1) * 2 + (((c - 1) >> 1) & 1)));
              }
            }
            bulk_wait_read<0>();
            mbar_arrive(s_bar + (lastt ? B_STGFREE : B_SEMPTY + 8 * 3));
#pragma unroll 1
            for (int c = 0; c < nl; c++) {
              if (nl > 1) {
                mbar_wait(s_bar + B_AEMPTY, (c & 1) ^ 1);
                mbar_expect_tx(s_bar + B_AFULL, L_V);
                tma_load_3d(sbase + OFF_STG, &p.tl, 0, r0 + c * 64, grp, s_bar + B_AFULL, HINT(28));
                tma_load_3d(sbase + OFF_STG + L_K, &p.th, 0, r0 + c * 64 - 8, 32 + grp, s_bar + B_AFULL, HINT(28));
                mbar_wait(s_bar + B_AEMPTY + 8, (c & 1) ^ 1);
                mbar_expect_tx(s_bar + B_AFULL + 8, 9216);
                tma_load_3d(sbase + OFF_STG + L_V, &p.th, 0, r0 + c * 64 - 8, 64 + grp, s_bar + B_AFULL + 8, HINT(28));
              }
              if (c) {
                mbar_wait(s_bar + B_OFULL, ~c & 1);
                cnt_signal(CNT_OB + (blockIdx.x >> 5) * 2 + ((c - 1) >> 2), 1u << ((c - 1) & 3) * 8);
              } else if (prob < 4) {
                bulk_wait<0>();
                cnt_signal_done(prob == 3 ? CNT_QKVB : CNT_QKV + (item & 15));
                TL(2, item);
              }
            }
            if (nl > 1) {
              mbar_wait(s_bar + B_OFULL, 1);
              cnt_signal(CNT_OB + (blockIdx.x >> 5) * 2 + 1, 1u << 24);
              TL(2, 0x600);
            }
          }
          if (seg == 0 && isB && DO_ATT) {
#ifdef ATT_ONLY
            mbar_arrive(s_bar + B_STGFREE);
#endif
            uint32_t code = p.order[cluster_id - NA_CL];
            for (int it = 0; !(code & 0x8000u); it++) {
              code |= rank == (it & 1);
              aswz = (~it & 1) * TILE32K;
              mbar_wait(s_bar + B_OFULL, it & 1);
              tma_store_3d(&p.to, sbase + OFF_STG, 0, (code & 15) * 128, (code >> 4) * 2, HINT(27));
              bulk_commit();
              const uint32_t nxt = lds32(s_bar + S_CODE + 4 * ((it + 1) & 7));
              bulk_wait_read<0>();
              mbar_arrive(s_bar + B_STGFREE);
              bulk_wait<0>();
              cnt_signal_done(CNT_CTX + (code & 15), 1u << (code >> 4));
              TL(2, 0x1000 | code);
              code = nxt;
            }
            tail = tail_item(code);
            if (tail == 0xFFFFu) rearm = cnt_done(NCTA * 2);
          }
        }
        if (rearm) cnt_rearm();
        TL(2, 0xFFFF);
      }
    }
  } else {
    CLUSTER_ARRIVE();
    reg_alloc<REG_C>();
    named_bar_sync(7, 288);
    const int warp = __shfl_sync(0xffffffffu, opaque_tid() >> 5, 0);
    const int wg = warp >> 2;
    const int lane = threadIdx.x & 31;
    TL_DECL;
    TR_DECL;
#ifdef TRACE
    if (tron) trp[trn] = (c_entry << 4) | 12;
    trn++;
    TRI(9, 13);
#endif
    named_bar_arrive_if(1, 256, wg == 1);
    uint32_t gphase = 0;
    uint32_t tail = 0, aswz = 0, rot = 0, stgpar = 1;
    const uint32_t etgt = warp & 1;
    int gi = 0;
    for (int seg = 0; seg < 2; seg++) {
      uint32_t item = p.g[cluster_id][gi++];
      if (item == 0x500u) item = tail;
      if (item < 0x600u) {
        float acc[128];
        uint32_t pk[64];
        int have = 0;
#define G_STORE_CHUNK(q)                                                                               \
  {                                                                                                    \
    const uint32_t st_base = sbase + OFF_STG + wg * 8192 + stg_off(opaque_tid());                      \
    if (have == 2) { _Pragma("unroll") for (int j = 0; j < 16; j++) pk[(q) * 16 + j] = scale_q(pk[(q) * 16 + j]); } \
    mbar_wait(s_bar + B_SEMPTY + 8 * (wg * 2 + ((q) & 1)), (((q) >> 1) & 1) ^ 1);                      \
    _Pragma("unroll") for (int j = 0; j < 4; j++)                                                      \
        stmatrix_x4((st_base ^ (j << 5)) + ((q) & 1) * 8192, pk[(q) * 16 + j * 4],                     \
                    pk[(q) * 16 + j * 4 + 1], pk[(q) * 16 + j * 4 + 2], pk[(q) * 16 + j * 4 + 3]);     \
    fence_proxy_async_smem();                                                                          \
    __syncwarp();                                                                                      \
    mbar_arrive_elect(s_bar + B_SFULL + 8 * (wg * 2 + ((q) & 1)), true);                              \
  }
#define G_STAGE(s) G_STAGE_Y(s, false, false, )
#define G_STAGE_X(s, ...) G_STAGE_Y(s, false, false, __VA_ARGS__)
#define G_STAGE_Y(s, first, last, ...)                                                                    \
  {                                                                                                       \
    mbar_wait_rest(s_bar + B_GFULL + 8 * (s), gphase, gok && (first));                                    \
    TR(9);                                                                                                \
    const uint32_t da = make_desc(DBASE + OFF_A + (((s) * 16384) ^ aswz) + wg * 8192, 16);                \
    const uint32_t db = make_desc(DBASE + ((s) ^ rot) * TILE32K, 8192);                                   \
    named_bar_sync_if(5 + wg, 256, !(first));                                                             \
    wgmma_fence();                                                                                        \
    _Pragma("unroll") for (int k = 0; k < 5; k++) {                                                       \
      __VA_ARGS__;                                                                                        \
      if (k == 0) wgmma_ss_n256_tbo<0, 0>(acc, da, db, !(first));                                         \
      if (k == 1) wgmma_ss_n256_tbo<2, 128>(acc, da, db, 1);                                              \
      if (k == 2) wgmma_ss_n256_tbo<4, 256>(acc, da, db, 1);                                              \
      if (k == 3) wgmma_ss_n256_tbo<6, 384>(acc, da, db, 1);                                              \
    }                                                                                                     \
    wgmma_commit();                                                                                       \
    named_bar_arrive_if(6 - wg, 256, !(wg ? (last) : (first)));                                           \
    if (!(first)) {                                                                                       \
      wgmma_wait<1>();                                                                                    \
      mbar_arrive_cluster_if(s_bar + B_GEMPTY + 8 * (((s) + 3) & 3), etgt, lane == 0 && (warp & 3) < 2);  \
    }                                                                                                     \
  }
        TL0(item);
        undef_regs(acc);
        {
          constexpr bool gok = false;
#ifdef TRE
          const uint32_t e0 = clock() - c_entry;
          mbar_wait(s_bar + B_GFULL, gphase);
          if (threadIdx.x == 0 && seg == 0) g_tr[16001 + 2 * blockIdx.x] = e0 | ((clock() - c_entry) << 16);
#endif
          G_STAGE_Y(0, true, false, )
        }
        if (seg == 0) CLUSTER_WAIT();
        undef_regs(pk);
        for (;;) {
          constexpr bool gok = false;
          const int nkb4 = prob_nkb4(item >> 8);
          const uint32_t next = p.g[cluster_id][gi++];
          G_STAGE(1)
          if (have) G_STORE_CHUNK(0)
          G_STAGE(2)
          G_STAGE(3)
          if (have) G_STORE_CHUNK(1)
          gphase ^= 1;
          G_STAGE(0)
          G_STAGE(1)
          if (have) G_STORE_CHUNK(2)
          G_STAGE(2)
          if (have) G_STORE_CHUNK(3)
          G_STAGE_Y(3, false, nkb4 == 2, )
          gphase ^= 1;
          int kb4 = 2;
          if (nkb4 == 16 && DO_LOCAL) {
            constexpr uint32_t aswz = 0, rot = 0;
            G_STAGE(0)
            G_STAGE(1)
            for (; kb4 < 10; kb4++) {
              float ls[36];
              TR(10);
              mbar_wait(s_bar + B_AFULL, kb4 & 1);
              TR(11);
              {
                const uint32_t dq = make_desc(DBASE + OFF_STG + wg * 64, 16);
                G_STAGE_X(2, if (k == 1) wgmma_ss_n72_init(ls, dq, dq + L_K / 16); if (k == 3) wgmma_ss_n72(ls, dq + 2, dq + L_K / 16 + 2, 1))
              }
              mbar_wait(s_bar + B_AFULL + 8, kb4 & 1);
              const int tid = opaque_tid();
              uint32_t vw[16];
              uint4 pw[8];
              {
                const uint32_t va = sbase + OFF_STG + L_V + ((tid >> 4) & 7) * 1024 + wg * 64 + (tid & 15) * 4;
#pragma unroll
                for (int j = 1; j < 16; j++) vw[j] = lds32((va ^ ((j & 7) << 4)) + j * 128);
              }
              G_STAGE(3)
              gphase ^= 1;
              fence_regs(ls);
              mbar_arrive_if(s_bar + B_AEMPTY, (threadIdx.x & 127) == 0);
              {
                const int d = (tid & 3) * 2 - ((tid >> 2) & 7);
                const bool p0 = d > 0, p1 = d >= 0;
                const int w = warp & 3;
                float x0, x1, y0, y1;
#define L_PICK(w_)                                   \
  {                                                  \
    x0 = p0 ? ls[8 * (w_)] : ls[8 * (w_) + 4];       \
    x1 = p1 ? ls[8 * (w_) + 1] : ls[8 * (w_) + 5];   \
    y0 = p0 ? ls[8 * (w_) + 6] : ls[8 * (w_) + 10];  \
    y1 = p1 ? ls[8 * (w_) + 7] : ls[8 * (w_) + 11];  \
  }
                if (w == 0) {
                  if (kb4 == 2 && blockIdx.x < 32) ls[0] = ls[1] = -INFINITY;
                  L_PICK(0)
                } else if (w == 1) L_PICK(1)
                else if (w == 2) L_PICK(2)
                else L_PICK(3)
                constexpr float C = 0.17677669529663687f * 1.4426950408889634f;
                float mx = fmaxf(x0, x1), my = fmaxf(y0, y1);
                mx = fmaxf(mx, __shfl_xor_sync(0xffffffffu, mx, 1));
                my = fmaxf(my, __shfl_xor_sync(0xffffffffu, my, 1));
                mx = -C * fmaxf(mx, __shfl_xor_sync(0xffffffffu, mx, 2));
                my = -C * fmaxf(my, __shfl_xor_sync(0xffffffffu, my, 2));
                x0 = ex2(fmaf(x0, C, mx));
                x1 = ex2(fmaf(x1, C, mx));
                y0 = ex2(fmaf(y0, C, my));
                y1 = ex2(fmaf(y1, C, my));
                float sx = x0 + x1, sy = y0 + y1;
                sx += __shfl_xor_sync(0xffffffffu, sx, 1);
                sy += __shfl_xor_sync(0xffffffffu, sy, 1);
                sx += __shfl_xor_sync(0xffffffffu, sx, 2);
                sy += __shfl_xor_sync(0xffffffffu, sy, 2);
                sx = rcp(sx);
                sy = rcp(sy);
                const uint32_t pa = sbase + OFF_STG + L_P + (tid >> 5) * 512 + (tid & 31) * 8;
                sts64(pa, x0 * sx, x1 * sx);
                sts64(pa + 256, y0 * sy, y1 * sy);
                __syncwarp();
              }
              const uint32_t pr = sbase + OFF_STG + L_P + (tid >> 4) * 256;
              uint32_t* dst = reinterpret_cast<uint32_t*>(p.ob) + (blockIdx.x & 15) * (SEQ * 32) + wg * 16 + (tid & 15) +
                              (((blockIdx.x >> 5) * 512 + (kb4 - 2) * 64 + ((tid >> 4) & 7) * 8) * 2 + ((blockIdx.x >> 4) & 1)) * 32;
#define L_PV(g0)                                                                                       \
  _Pragma("unroll") for (int g = (g0); g < (g0) + 4; g++) {                                            \
    const uint4 a = pw[2 * (g & 3)], b = pw[2 * (g & 3) + 1];                                          \
    const uint32_t w[8] = {a.x, a.y, a.z, a.w, b.x, b.y, b.z, b.w};                                    \
    float o0 = 0.f, o1 = 0.f;                                                                          \
    _Pragma("unroll") for (int c = 0; c < 8; c++) {                                                    \
      const uint32_t u = vw[c > g ? c : c + 8];                                                        \
      o0 = fmaf(__uint_as_float(w[c]), __uint_as_float(u << 16), o0);                                  \
      o1 = fmaf(__uint_as_float(w[c]), __uint_as_float(u & 0xFFFF0000u), o1);                          \
    }                                                                                                  \
    dst[g * 64] = pack_bf16(o0, o1);                                                                   \
  }
#pragma unroll
              for (int j = 0; j < 8; j++) pw[j] = lds128(pr + j * 16);
              mbar_arrive_elect(s_bar + B_AEMPTY + 8, true);
              G_STAGE(0)
              L_PV(0)
#pragma unroll
              for (int j = 0; j < 8; j++) pw[j] = lds128(pr + 128 + j * 16);
              G_STAGE(1)
              L_PV(4)
              __syncwarp();
              mbar_arrive_elect(s_bar + B_OFULL, true);
            }
            G_STAGE(2)
            G_STAGE(3)
            gphase ^= 1;
            kb4++;
          }
          const bool fin = next >= 0x600u;
          for (; kb4 < nkb4 - fin; kb4++) {
            G_STAGE(0)
            G_STAGE(1)
            G_STAGE(2)
            G_STAGE_Y(3, false, kb4 + 1 == nkb4, )
            gphase ^= 1;
          }
          if (fin) break;
          wgmma_wait<0>();
          mbar_arrive_cluster_if(s_bar + B_GEMPTY + 8 * 3, etgt, lane == 0 && (warp & 3) < 2);
          {
            const bool gok = mbar_test(s_bar + B_GFULL, gphase);
            fence_regs(acc);
#pragma unroll
            for (int j = 0; j < 64; j++) pk[j] = pack_bf16(acc[2 * j], acc[2 * j + 1]);
            have = item < 0x100u ? 2 : 1;
            item = next;
            TL0(item);
            G_STAGE_Y(0, true, false, )
          }
        }
        {
          constexpr bool gok = false;
          G_STAGE(0)
#if FS == 2
          G_STAGE(1)
#endif
          wgmma_wait<0>();
          mbar_arrive_cluster_if(s_bar + B_GEMPTY + 8 * (FS - 1), etgt, lane == 0 && (warp & 3) < 2);
          fence_regs(acc);
          float lo[64], hi[64];
#pragma unroll
          for (int j = 0; j < 64; j++) {
            asm volatile("mov.b32 %0, %1;" : "=f"(lo[j]) : "f"(acc[j]));
            asm volatile("mov.b32 %0, %1;" : "=f"(hi[j]) : "f"(acc[64 + j]));
          }
#pragma unroll
          for (int s = FS; s < 4; s++) {
            mbar_wait(s_bar + B_GFULL + 8 * s, gphase);
            const uint32_t da = make_desc(DBASE + OFF_A + ((s * 16384) ^ aswz) + wg * 8192, 16);
            const uint32_t db = make_desc(DBASE + (s ^ rot) * TILE32K, 8192);
            if (s == FS) named_bar_sync(5 + wg, 256);
            wgmma_fence();
            wgmma_ss_n128_tb<0, 0>(lo, da, db, 1);
            wgmma_ss_n128_tb<2, 128>(lo, da, db, 1);
            wgmma_ss_n128_tb<4, 256>(lo, da, db, 1);
            wgmma_ss_n128_tb<6, 384>(lo, da, db, 1);
            wgmma_commit();
          }
          wgmma_fence();
#pragma unroll
          for (int s = FS; s < 4; s++) {
            const uint32_t da = make_desc(DBASE + OFF_A + ((s * 16384) ^ aswz) + wg * 8192, 16);
            const uint32_t db = make_desc(DBASE + (s ^ rot) * TILE32K, 8192);
            wgmma_ss_n128_tb<0, 1024>(hi, da, db, 1);
            wgmma_ss_n128_tb<2, 1152>(hi, da, db, 1);
            wgmma_ss_n128_tb<4, 1280>(hi, da, db, 1);
            wgmma_ss_n128_tb<6, 1408>(hi, da, db, 1);
          }
          wgmma_commit();
          named_bar_arrive_if(6, 256, wg == 0);
          gphase ^= 1;
          const uint32_t so = sbase + stg_off(opaque_tid());
          mbar_wait(s_bar + B_STGFREE, stgpar);
          mbar_wait(s_bar + B_SEMPTY + 16 * wg, 1);
          mbar_wait(s_bar + B_SEMPTY + 16 * wg + 8, 1);
#define FIN_HALF(x, base, stride, bar, pub)                                                                                \
  fence_regs(x);                                                                                                      \
  _Pragma("unroll") for (int j = 0; j < 8; j++)                                                                       \
      stmatrix_x4(((base) ^ ((j & 3) << 5)) + (j >> 2) * (stride), pack_bf16(x[8 * j], x[8 * j + 1]),                 \
                  pack_bf16(x[8 * j + 2], x[8 * j + 3]), pack_bf16(x[8 * j + 4], x[8 * j + 5]), pack_bf16(x[8 * j + 6], x[8 * j + 7])); \
  if (pub) FIN_PUBLISH(bar)
#define FIN_PUBLISH(bar)                                   \
  {                                                        \
    fence_proxy_async_smem();                              \
    __syncwarp();                                          \
    mbar_arrive_elect(s_bar + (bar) + 16 * wg, true);      \
    mbar_arrive_elect(s_bar + (bar) + 16 * wg + 8, true);  \
  }
          wgmma_wait<1>();
          FIN_HALF(lo, so + OFF_STG + wg * 8192, 8192, B_SFULL, true)
          wgmma_wait<0>();
          TRI(12, 8);
#pragma unroll
          for (int s = FS; s < 4; s++) mbar_arrive_cluster_if(s_bar + B_GEMPTY + 8 * s, etgt, lane == 0 && (warp & 3) < 2);
          FIN_HALF(hi, so + OFF_A + (32768 ^ aswz), 16384, B_SFULL2, !(seg == 0 && isB && DO_ATT))
          TRI(12, 10);
        }
      }
#ifdef ATT_ONLY
      if (seg == 0) CLUSTER_WAIT();
#endif
      if (seg == 0 && isB && DO_ATT) {
        float o[64], s[64];
        uint32_t pa[32], pb[32];
        undef_regs(o);
        undef_regs(s);
        undef_regs(pa);
        undef_regs(pb);
        uint32_t phase = 0;
        const bool sig = (threadIdx.x & 127) == 0, sig2 = (threadIdx.x & 95) == 0;
#ifndef ATT_ONLY
        FIN_PUBLISH(B_SFULL2)
#endif

#define ISSUE_PV(pr, slot_)                                                             \
  {                                                                                     \
    const uint32_t dv = make_desc(DBASE + (slot_) * TILE32K, 16384);                    \
    if (!phalf) {                                                                       \
      wgmma_fence();                                                                    \
      _Pragma("unroll") for (int k = 0; k < 8; k++)                                     \
          wgmma_rs_n128_tb(o, pr[4 * k], pr[4 * k + 1], pr[4 * k + 2], pr[4 * k + 3], dv + k * 128, (k != 0) || !pfirst); \
      wgmma_commit();                                                                   \
    } else {                                                                            \
      wgmma_fence();                                                                    \
      _Pragma("unroll") for (int k = 0; k < 4; k++)                                     \
          wgmma_rs_n128_tb(o, pr[16 + 4 * k], pr[17 + 4 * k], pr[18 + 4 * k], pr[19 + 4 * k], dv + k * 128, (k != 0) || !pfirst); \
      wgmma_commit();                                                                   \
    }                                                                                   \
  }
#define EPILOGUE(on_)                                                                             \
  _Pragma("unroll") for (int j = 0; j < 8; j++) {                                                 \
    const int b = j * 8;                                                                          \
    stmatrix_x4_p((st_o ^ ((j & 3) << 5)) + (j >> 2) * 16384,                                     \
                  pack_bf16(o[b] * sc0, o[b + 1] * sc0), pack_bf16(o[b + 2] * sc1, o[b + 3] * sc1),   \
                  pack_bf16(o[b + 4] * sc0, o[b + 5] * sc0), pack_bf16(o[b + 6] * sc1, o[b + 7] * sc1), on_); \
  }
#define PUBLISH_O()                                  \
  {                                                  \
    fence_proxy_async_smem();                        \
    __syncwarp();                                    \
    mbar_arrive_elect(s_bar + B_OFULL, true);        \
  }
#define FINAL_SCALE()     \
  {                                                    \
    sc0 = t0 + __shfl_xor_sync(0xffffffffu, t0, 1);    \
    sc1 = t1 + __shfl_xor_sync(0xffffffffu, t1, 1);    \
    t0 = t1 = 0.f;                                     \
    sc0 += __shfl_xor_sync(0xffffffffu, sc0, 2);       \
    sc1 += __shfl_xor_sync(0xffffffffu, sc1, 2);       \
    sc0 = rcp(sc0);            \
    sc1 = rcp(sc1);                                    \
  }
        float l0 = 1.f, l1 = 1.f, t0 = 1.f, t1 = 1.f;
        float b0 = 0.f, b1 = 0.f, sc0 = 0.f, sc1 = 0.f;
        int gen = 0;
        int pfirst = 1;
        int phalf = 2;
        int fresh = 1;
        int diag = blockIdx.x & 1, dlast = !diag;
        int opub = 0;
        int last = 0;
        float rdy;
        float x0 = 0.f, x1 = 0.f, x2 = 0.f, x3 = 0.f;
        bool rs = false;
        uint32_t code = p.order[cluster_id - NA_CL];
        int it = 0, nit = 0, rem = (code & 15) + dlast;
        TL0(0x1000 | code | rem);
        const float mrow = float((warp & 3) * 16 + (lane >> 2) - (lane & 3) * 2);
        const float lo0 = mrow < 0.f && wg == HW ? 0.f : SM_LO;
        const uint32_t st_o = sbase + OFF_STG + stg_off(opaque_tid() ^ (HW * 128));
#define MMA_PART(N_, acc_, PIN, PAR)                                                                       \
  {                                                                                                        \
    const uint32_t dq = make_desc(DBASE + OFF_A + (it & 1) * TILE32K + (wg ^ HW) * 8192, 16);              \
    const uint32_t dk = make_desc(DBASE + (PAR) * TILE32K, 16);                                            \
    TRI(0, fresh ? 7 : 0);                                                                                 \
    named_bar_sync(1 + wg, 256);                                                                           \
    TRI(1, fresh ? 6 : 1);                                                                                 \
    wgmma_fence();                                                                                         \
    uint32_t cv;                                                                                           \
    bool rv;                                                                                               \
    _Pragma("unroll") for (int k = 0; k < 8; k++) {                                                        \
      wgmma_ss_n##N_(acc_, dq + (k >> 2) * 1024 + (k & 3) * 2, dk + (k >> 2) * 1024 + (k & 3) * 2, k != 0); \
      if (k == 1) cv = lds32(s_bar + S_CODE + 4 * ((it + 1) & 7));        \
      if (k == 3) rv = mbar_test(s_bar + B_AFULL + 8 * (3 - (PAR)), phase ^ (1 - (PAR)));                  \
    }                                                                                                      \
    wgmma_commit();                                                                                        \
    code = __reduce_or_sync(0xffffffffu, cv);                                                              \
    if (opub) PUBLISH_O();                                                                                 \
    if (N_ == 128 && fresh) FINAL_SCALE();                                                                 \
    last = rem == 0 && (code & 0x8000u);                                                                   \
    nit = it + (rem == 0 && !last);                                                                        \
    mbar_wait_rest(s_bar + B_AFULL + 8 * (3 - (PAR)), phase ^ (1 - (PAR)), rv);                            \
    ISSUE_PV(PIN, 3 - (PAR));                                                                              \
    named_bar_arrive(2 - wg, 256);                                                                         \
    TR(2);                                                                                                 \
    wgmma_wait<1>();                                                                                       \
    fence_regs(acc_);                                                                                      \
    TR(3);                                                                                                 \
    mbar_arrive_cluster_if(s_bar + B_AEMPTY + 8 * (PAR), etgt, sig2);                                      \
    mbar_arrive_if(s_bar + B_QEMPTY + 8 * (it & 1), sig && rem == 0);                                      \
    if (N_ == 64 && fresh) FINAL_SCALE();                                                                  \
    l0 = t0;                                                                                               \
    l1 = t1;                                                                                               \
  }
#define LOW_SUM() ((t0 < lo0) | (t1 < SM_LO))
#define SECOND_HALF(POUT, PAR, FRESH, ...)                                                                 \
  wgmma_wait<0>();                                                                                         \
  fence_regs(o);                                                                                           \
  mbar_arrive_cluster_if(s_bar + B_AEMPTY + 8 * (3 - (PAR)), etgt, sig2 && ((PAR) || !(FRESH) || it > 0)); \
  TR(8);                                                                                                   \
  __VA_ARGS__;                                                                                             \
  t0 += x0 + x1;                                                                                           \
  t1 += x2 + x3;                                                                                           \
  POUT[16] = pack_bf16(x0, x1);                                                                            \
  POUT[17] = pack_bf16(x2, x3);                                                                            \
  softmax_exp<9, ZPOS, false>(s, 0.f, 0.f, POUT, t0, t1);                                                  \
  {                                                                                                        \
           \
    const uint32_t z = (__float_as_uint(t0) | __float_as_uint(t1)) >> 31;                                  \
    rdy = mbar_test2(s_bar + B_AFULL + 8 * (1 - (PAR)), (phase ^ (PAR)) + z, s_bar + B_QFULL + 8 * (nit & 1), ((nit >> 1) & 1) + z); \
  }                                                                                                        \
  softmax_exp<ZPOS, TPOS, false>(s, 0.f, 0.f, POUT, t0, t1);                                               \
  t0 = addv(t0, rdy);                                                                                      \
  softmax_exp<TPOS, 16, false>(s, 0.f, 0.f, POUT, t0, t1);                                                 \
                                                                                \
  phalf = diag && wg == HW;                                                                                \
  opub = (FRESH) && it > 0;                                                                                \
  pfirst = FRESH;                                                                                          \
  fresh = rem == 0;                                                                                        \
  it = nit;                                                                                                \
  rem = fresh ? (code & 15) + ((blockIdx.x ^ ~it) & 1) : rem - 1;                                          \
  dlast = !((blockIdx.x | it) & 1);                                                                        \
  diag = dlast ? rem == 0 : fresh;                                                                         \
  if (fresh && !last) { TL0(0x1000 | code | rem); }                                                        \
  if (PAR) phase ^= 1;                                                                                     \
                                                      \
  const float lim = __uint_as_float(__float_as_uint(last ? -1.f : SM_HI) | __float_as_uint(rdy));   \
  TR(4);
#ifndef TPOS
#define TPOS 15
#define ZPOS 13
#endif
#define TEST_STG() rs = mbar_test(s_bar + B_STGFREE, ~it & 1) | (it == 0);
#define SHIFT_S(j0_)                                                                                       \
  if (gen) { _Pragma("unroll") for (int j = (j0_); j < 64; j++) s[j] += (j & 2) ? b1 : b0; }
#define NEXT_STEP(NEXT, LOW)                                                                               \
  if (!__any_sync(0xffffffffu, !(t0 + t1 <= (diag && wg == HW ? -1.f : lim)) | (LOW))) goto plain##NEXT;   \
  if (!__any_sync(0xffffffffu, !(t0 + t1 <= lim) | (LOW))) goto half##NEXT;
#define STEP_END(POUT, PAR, NEXT, ...)                                                                     \
  if (fresh) {                                                                                             \
    __VA_ARGS__;                                                                                           \
    mbar_wait_rest(s_bar + B_STGFREE, ~it & 1, rs);                                                        \
    SECOND_HALF(POUT, PAR, 1, EPILOGUE(it > 0))                                                            \
    if (phalf && opub) {                                                     \
      PUBLISH_O();                                                                                         \
      opub = 0;                                                                                            \
    }                                                                                                      \
    NEXT_STEP(NEXT, LOW_SUM())                                                                             \
  } else {                                                                                                 \
    SECOND_HALF(POUT, PAR, 0, )                                                                            \
    NEXT_STEP(NEXT, false)                                                                                 \
  }
#define STEP_BEGIN(PIN, POUT, PAR, ...)                                                                    \
  {                                                                                                        \
    if (__any_sync(0xffffffffu, !(t0 + t1 <= SM_HI) | (LOW_SUM() & (pfirst != 0)))) {                           \
              \
      if (phalf) { _Pragma("unroll") for (int j = 0; j < 32; j++) asm volatile("mov.b32 %0, 0xff800000;" : "=f"(s[j])); } \
      float d0, d1;                                                                                        \
      softmax_max(s, d0, d1);                                                                              \
      if (!pfirst) {                                                                                       \
        d0 = fmaxf(d0, 0.f);                                                                               \
        d1 = fmaxf(d1, 0.f);                                                                               \
      }                                                                                                    \
      const float r0 = pfirst ? 1.f : ex2(-d0), r1 = pfirst ? 1.f : ex2(-d1);                              \
      t0 = l0 * r0;                                                                                        \
      t1 = l1 * r1;                                                                                        \
      softmax_exp<0, 16, true>(s, -d0, -d1, PIN, t0, t1);                                                  \
      b0 -= d0;                                                                                            \
      b1 -= d1;                                                                                            \
      gen = 1;                                                                                             \
      _Pragma("unroll") for (int j = 0; j < 16; j++) {                                                     \
        o[4 * j] *= r0;                                                                                    \
        o[4 * j + 1] *= r0;                                                                                \
        o[4 * j + 2] *= r1;                                                                                \
        o[4 * j + 3] *= r1;                                                                                \
      }                                                                                                    \
    }                                                                                                      \
    if (last) {                                                                                            \
      __VA_ARGS__;                                                                                         \
      break;                                                                                               \
    }                                                                                                      \
  }                                                                                                        \
  inputs##PAR:                                                                                             \
  {                                                                                                        \
    const bool rq = mbar_test(s_bar + B_QFULL + 8 * (it & 1), (it >> 1) & 1);                              \
    mbar_wait(s_bar + B_AFULL + 8 * (PAR), phase);                                                         \
    mbar_wait_rest(s_bar + B_QFULL + 8 * (it & 1), (it >> 1) & 1, rq);                                     \
  }                                                                                                        \
  if (diag && wg == HW) {                                                                                  \
  half##PAR:                                                                                               \
                                                     \
    float sl[32];                                                                                          \
    undef_regs(sl);                                                                                        \
    MMA_PART(64, sl, PIN, PAR)                                                                             \
    _Pragma("unroll") for (int j = 0; j < 32; j++) asm volatile("mov.b32 %0, %1;" : "=f"(s[32 + j]) : "f"(sl[j])); \
    SHIFT_S(32)                                                                                            \
    TEST_STG()                                                                                             \
    _Pragma("unroll") for (int j = 0; j < 8; j++) {                                                        \
      if (float(8 * j) > mrow) s[32 + 4 * j] = -3e38f;                                                     \
      if (float(8 * j + 1) > mrow) s[33 + 4 * j] = -3e38f;                                                 \
      if (float(8 * j - 8) > mrow) s[34 + 4 * j] = -3e38f;                                                 \
      if (float(8 * j - 7) > mrow) s[35 + 4 * j] = -3e38f;                                                 \
    }                                                                                                      \
    x0 = ex2v(s[32]), x1 = ex2v(s[33]), x2 = ex2v(s[34]), x3 = ex2v(s[35]);                                \
  } else {                                                                                                 \
  plain##PAR:                                                                                              \
    MMA_PART(128, s, PIN, PAR)                                                                             \
    if (diag || gen) {                                                                                     \
      SHIFT_S(0)                                                                                           \
                                     \
      TEST_STG()                                                                                           \
      const float rowf = diag ? mrow : 64.f;                                                               \
      _Pragma("unroll") for (int j = 0; j < 8; j++) {                                                      \
        s[32 + 4 * j] = fmaf(__saturatef(float(8 * j) - rowf), -3e38f, s[32 + 4 * j]);                     \
        s[33 + 4 * j] = fmaf(__saturatef(float(8 * j + 1) - rowf), -3e38f, s[33 + 4 * j]);                 \
        s[34 + 4 * j] = fmaf(__saturatef(float(8 * j - 8) - rowf), -3e38f, s[34 + 4 * j]);                 \
        s[35 + 4 * j] = fmaf(__saturatef(float(8 * j - 7) - rowf), -3e38f, s[35 + 4 * j]);                 \
      }                                                                                                    \
      softmax_exp<0, 8, false>(s, 0.f, 0.f, POUT, t0, t1);                                                 \
      x0 = ex2v(s[32]), x1 = ex2v(s[33]), x2 = ex2v(s[34]), x3 = ex2v(s[35]);                              \
    } else {                                                                                               \
      TEST_STG()                                                                                           \
      softmax_exp<0, 8, false>(s, 0.f, 0.f, POUT, t0, t1);                                                 \
      x0 = ex2v(s[32]), x1 = ex2v(s[33]), x2 = ex2v(s[34]), x3 = ex2v(s[35]);                              \
    }                                                                                                      \
  }
        for (;;) {
          STEP_END(pa, 1, 0, if (phalf == 2) { wgmma_wait<0>(); goto inputs0; })
          STEP_BEGIN(pa, pb, 0, rot = 0; phase ^= 1)
          STEP_END(pb, 0, 1, )
          STEP_BEGIN(pb, pa, 1, rot = 1; _Pragma("unroll") for (int j = 0; j < 32; j++) asm volatile("mov.b32 %0, %1;" : "=r"(pa[j]) : "r"(pb[j])))
        }
        {
          mbar_wait(s_bar + B_AFULL + 8 * (3 - rot), phase);
          TRI(12, 2);
          ISSUE_PV(pa, 3 - rot);
          if (opub) PUBLISH_O();
          FINAL_SCALE();
          mbar_wait(s_bar + B_STGFREE, it & 1);
          wgmma_wait<0>();
          fence_regs(o);
          TRI(12, 4);
          mbar_arrive_cluster_if(s_bar + B_AEMPTY + 8 * (3 - rot), etgt, sig2);
          EPILOGUE(true);
          PUBLISH_O();
          TRI(12, 5);
          stgpar = ~it & 1;
          tail = tail_item(code);
          aswz = (~it & 1) * TILE32K;
          rot ^= blockIdx.x & ~it & 1;
        }
      }
    }
    TL0(0xFFFF);
    TRI(15, 15);
  }
}

typedef CUresult (*EncodeFn)(CUtensorMap*, CUtensorMapDataType, cuuint32_t, void*, const cuuint64_t*,
                             const cuuint64_t*, const cuuint32_t*, const cuuint32_t*, CUtensorMapInterleave,
                             CUtensorMapSwizzle, CUtensorMapL2promotion, CUtensorMapFloatOOBfill);

EncodeFn get_encode() {
  static EncodeFn fn = nullptr;
  if (!fn) {
    void* p = nullptr;
    cudaDriverEntryPointQueryResult st;
    cudaGetDriverEntryPoint("cuTensorMapEncodeTiled", &p, cudaEnableDefault, &st);
    fn = (EncodeFn)p;
  }
  return fn;
}

void make_map(CUtensorMap* m, const void* ptr, int rows, int cols, int box_rows, int box_groups, bool blocked = false) {
  cuuint64_t dims[3] = {64, (cuuint64_t)rows, (cuuint64_t)(cols / 64)};
  cuuint64_t strides[2] = {(cuuint64_t)(blocked ? 128 : cols * 2), (cuuint64_t)(blocked ? rows * 128 : 128)};
  cuuint32_t box[3] = {64, (cuuint32_t)box_rows, (cuuint32_t)box_groups};
  cuuint32_t es[3] = {1, 1, 1};
  CUtensorMapL2promotion prom = blocked || box_groups == 1 ? CU_TENSOR_MAP_L2_PROMOTION_NONE : CU_TENSOR_MAP_L2_PROMOTION_L2_256B;
  get_encode()(m, CU_TENSOR_MAP_DATA_TYPE_BFLOAT16, 3, const_cast<void*>(ptr), dims, strides, box, es,
               CU_TENSOR_MAP_INTERLEAVE_NONE, CU_TENSOR_MAP_SWIZZLE_128B, prom,
               CU_TENSOR_MAP_FLOAT_OOB_FILL_NONE);
}

void make_store_map(CUtensorMap* m, const void* ptr, int cols, uint64_t s_par, uint64_t s_pair, uint64_t s_grp) {
  cuuint64_t dims[4] = {64, 2, SEQ / 2, (cuuint64_t)(cols / 64)};
  cuuint64_t strides[3] = {s_par, s_pair, s_grp};
  cuuint32_t box[4] = {64, 2, 32, 1};
  cuuint32_t es[4] = {1, 1, 1, 1};
  get_encode()(m, CU_TENSOR_MAP_DATA_TYPE_BFLOAT16, 4, const_cast<void*>(ptr), dims, strides, box, es,
               CU_TENSOR_MAP_INTERLEAVE_NONE, CU_TENSOR_MAP_SWIZZLE_128B, CU_TENSOR_MAP_L2_PROMOTION_NONE,
               CU_TENSOR_MAP_FLOAT_OOB_FILL_NONE);
}

#ifdef SCHED_PRINT
static int envi(const char* n, int d) { const char* e = getenv(n); return e ? (int)strtol(e, 0, 0) : d; }
#define PARAM(name, val) const int name = envi(#name, val)
#else
#define PARAM(name, val) const int name = val
#endif
void build_schedule(Params& p) {
  PARAM(C_KB, 1028);
  PARAM(C_TILE, 10);
  PARAM(C_QX, 0);
  PARAM(C_START, 4500);
  PARAM(C_STEP, 2052);
  PARAM(C_ITEM, 300);
  PARAM(C_LAG, 8000);
  PARAM(C_SP, 5200);
  PARAM(C_TAIL, 22000);
  PARAM(C_SHORT, 0);
  PARAM(C_AT, 72);
  PARAM(C_LATE, 0);
  PARAM(C_LMASK, 0xAA0);
  PARAM(C_AM, 100);
  PARAM(C_ODD, 1300);
  PARAM(C_READY, 10000);
  auto gemm_cost = [&](int prob) {
    static const int nkb[NPROB] = {16, 8, 8, 16, 64, 16};
    return nkb[prob] * C_KB + C_TILE + (prob == 0 ? C_QX : 0);
  };
  memset(p.g, 0xFF, sizeof(p.g));
  int n1[NCLUSTER];
  long t1[NCLUSTER];
  long ready[16];
  for (int c = 0; c < NCLUSTER; c++) { n1[c] = 0; t1[c] = C_START; }
  for (int i = 0; i < 16; i++) ready[i] = 0;
  auto add = [&](int c, int prob, int mp, int nt) {
    p.g[c][n1[c]++] = (uint16_t)((prob << 8) | (mp << 4) | nt);
    t1[c] += gemm_cost(prob);
    if (prob < 3) {
      const long r = t1[c] + C_READY;
      if (r > ready[nt]) ready[nt] = r;
    }
  };
#ifdef GEMM_ONLY
  for (int c = 0; c < NCLUSTER; c++) {
    for (int i = 0; i < 13; i++) add(c, 0, c & 7, (i + (c >> 3) * 2) & 15);
    p.g[c][n1[c]++] = 0x600;
  }
  return;
#endif
#ifdef ATT_ONLY
  for (int c = 0; c < NCLUSTER; c++) { p.g[c][0] = 0x600; p.g[c][1] = 0x500; }
  for (int i = 0; i < 256; i++) p.order[i] = (uint16_t)(((i & 31) << 4) | (14 - 2 * (i >> 5)));
  return;
#endif
  for (int r = 0; r < 8; r++)
    for (int c = 0; c < NA_CL; c++) {
      const int mp = c & 7, nt = 2 * r + ((c >> 3) & 1);
      for (int j = 0; j < (c < 16 ? 1 : 2); j++) {
        add(c, c < 16 ? 0 : 1 + j, mp, nt);
      }
    }
  long tA = 0;
  for (int c = 0; c < NA_CL; c++) {
    if (t1[c] > tA) tA = t1[c];
    add(c, 4, c & 7, c >> 3);
  }
  for (int r = 0; r < 3; r++)
    for (int j = 0; j < 34; j++) {
      if (j >= 32) { if (r < 2) add(NA_CL + j, 3, j & 7, 4 + r); }
      else if (r < 2 || j >= 16 || (j & 7) >= 2) add(NA_CL + j, 3, j & 7, (j >> 3) + (r == 0 ? 0 : r == 1 ? 8 : 4));
    }
  for (int c = NA_CL; c < NCLUSTER; c++) {
    p.g[c][n1[c]++] = 0x600;
    p.g[c][n1[c]++] = 0x500;
  }
  static const uint16_t order[256] = {
    14, 30, 10, 44, 26, 78, 60, 94, 12, 46, 8, 42, 24, 76, 58, 110, 92, 6, 126, 40, 22, 74, 56, 108,
    90, 4, 124, 38, 20, 72, 54, 106, 28, 62, 142, 158, 88, 2, 140, 122, 36, 18, 174, 156, 70, 52, 190, 104,
    86, 0, 138, 120, 34, 16, 172, 154, 68, 50, 206, 188, 102, 84, 222, 136, 118, 32, 170, 152, 66, 48, 204, 186,
    100, 82, 238, 220, 134, 116, 254, 168, 150, 64, 202, 184, 98, 80, 236, 218, 132, 114, 270, 252, 166, 148, 286, 200,
    182, 96, 234, 216, 130, 112, 268, 250, 164, 146, 302, 284, 198, 180, 318, 232, 214, 128, 266, 248, 162, 144, 300, 282,
    196, 178, 334, 316, 230, 212, 350, 264, 246, 160, 310, 328, 382, 194, 314, 360, 192, 340, 278, 298, 274, 208, 342, 366,
    210, 260, 290, 312, 336, 378, 306, 292, 240, 330, 364, 224, 228, 346, 380, 434, 376, 244, 362, 226, 344, 348, 408, 272,
    304, 176, 320, 368, 280, 412, 390, 332, 262, 288, 258, 256, 242, 402, 294, 388, 422, 296, 406, 398, 384, 374, 326, 352,
    400, 414, 394, 276, 322, 418, 392, 396, 370, 356, 324, 410, 386, 430, 462, 494, 446, 510, 478, 484, 482, 354, 498, 404,
    308, 416, 428, 492, 508, 460, 476, 444, 452, 358, 426, 372, 490, 506, 458, 442, 474, 338, 424, 472, 456, 440, 488, 454,
    450, 438, 470, 486, 420, 436, 468, 500, 504, 466, 502, 448, 496, 432, 480, 464,
  };
  memcpy(p.order, order, sizeof(order));
#ifdef SCHED_PRINT
  uint16_t fixed[256];
  memcpy(fixed, p.order, sizeof(fixed));
  long tf[NB_CL];
  bool done[512], started[NB_CL];
  long fin[16];
  int cnt[NB_CL] = {};
  for (int c = 0; c < NB_CL; c++) { tf[c] = t1[NA_CL + c] + 2000; started[c] = false; }
  for (int i = 0; i < 512; i++) done[i] = i & 1;
  for (int i = 0; i < 16; i++) fin[i] = 0;
  auto alen = [&](int qt) { return (long)(2 * qt + 3) * C_STEP / 2 + C_ITEM + (qt < 2 ? C_SHORT : 0); };
  int nq = NB_CL;
  for (int n = 0; n < 256; n++) {
    int cb = 0;
    for (int c = 1; c < NB_CL; c++)
      if (tf[c] < tf[cb]) cb = c;
    int best = -1;
    long bkey = 0;
    for (int i = 0; i < 512; i++) {
      if (done[i]) continue;
      const int hp = i >> 5;
      long dl = -(long)(16 - hp) * C_SP - C_LAG + ((i >> 4) & 1) * C_ODD;
      if (dl > -C_TAIL) dl = -C_TAIL;
      long key = dl - alen(i & 15) * (dl == -C_TAIL ? C_AT : C_AM) / 100;
      if ((i >> 4) == 31 && (C_LMASK >> (i & 15) & 1)) key += C_LATE;
      if (ready[hp] > tf[cb]) key += (1L << 40) + (ready[hp] - tf[cb]) * 1024;
      if (best < 0 || key < bkey) { best = i; bkey = key; }
    }
    done[best] = true;
    if (!started[cb]) { p.order[cb] = (uint16_t)best; started[cb] = true; }
    else p.order[nq++] = (uint16_t)best;
    if (ready[best >> 5] > tf[cb]) tf[cb] = ready[best >> 5];
    tf[cb] += alen(best & 15) + (cnt[cb]++ & 1 ? -C_STEP / 2 : C_STEP / 2);
    if (tf[cb] + C_LAG > fin[best >> 5]) fin[best >> 5] = tf[cb] + C_LAG;
  }
  if (!getenv("HEUR")) memcpy(p.order, fixed, sizeof(fixed));
#endif
#ifdef SCHED_PRINT
  ord_hook(p.order);
  long t = tA, tmin = tf[0], tmax = tf[0];
  printf("sched: outA start %ld, fin:", t);
  for (int hp = 0; hp < 16; hp++) {
    printf(" %ld", fin[hp] - t);
    if (fin[hp] > t) t = fin[hp];
    t += 4 * C_KB;
  }
  for (int c = 0; c < NB_CL; c++) { if (tf[c] < tmin) tmin = tf[c]; if (tf[c] > tmax) tmax = tf[c]; }
  printf("\nA end %ld, attention end %ld..%ld (+%d), ready[15] %ld nq %d\n", t, tmin, tmax, gemm_cost(5), ready[15], nq);
#endif
}

}

extern "C" void kernel_launch(void* const* d_in, const int* in_sizes, int n_in, void* d_out, int out_size) {
  const bf16* A_x = (const bf16*)d_in[0];
  const bf16* A_c = (const bf16*)d_in[1];
  const bf16* A_wq = (const bf16*)d_in[2];
  const bf16* A_wuk = (const bf16*)d_in[3];
  const bf16* A_wuv = (const bf16*)d_in[4];
  const bf16* A_wo = (const bf16*)d_in[5];
  const bf16* B_x = (const bf16*)d_in[6];
  const bf16* B_wqkv = (const bf16*)d_in[7];
  const bf16* B_wo = (const bf16*)d_in[8];
  bf16* out = (bf16*)d_out;

  static Params p;
  static bf16 *q, *k, *v, *ctx, *qkvb, *ob;
  static bool init = false;
  if (!init) {
    cudaGetSymbolAddress((void**)&q, g_q);
    cudaGetSymbolAddress((void**)&k, g_k);
    cudaGetSymbolAddress((void**)&v, g_v);
    cudaGetSymbolAddress((void**)&qkvb, g_qkvb);
    cudaGetSymbolAddress((void**)&ob, g_ob);
    cudaFuncSetAttribute(mega_kernel, cudaFuncAttributeMaxDynamicSharedMemorySize, SMEM_BYTES);
    build_schedule(p);
    ctx = q;
    init = true;
  }
  make_map(&p.ta[0], A_x, SEQ, DM, 128, 1);
  make_map(&p.tb[0], A_wq, DM, HHD, 64, 2);
  make_store_map(&p.tc[0], q, HHD, 128, 256, SEQ * 128);
  make_map(&p.ta[1], A_c, SEQ, DC, 128, 1);
  make_map(&p.tb[1], A_wuk, DC, HHD, 64, 2);
  make_store_map(&p.tc[1], k, HHD, 128, 256, SEQ * 128);
  make_map(&p.ta[2], A_c, SEQ, DC, 128, 1);
  make_map(&p.tb[2], A_wuv, DC, HHD, 64, 2);
  make_store_map(&p.tc[2], v, HHD, 128, 256, SEQ * 128);
  make_map(&p.ta[3], B_x, SEQ, DM, 128, 1);
  make_map(&p.tb[3], B_wqkv, DM, 3 * DM, 64, 2);
  make_store_map(&p.tc[3], qkvb, 3 * DM, SEQ * 64, 128, SEQ * 128);
  make_map(&p.ta[4], ctx, SEQ, HHD, 128, 1, true);
  make_map(&p.tb[4], A_wo, HHD, DM, 64, 2);
  make_store_map(&p.tc[4], out, 2 * DM, 4 * DM, 8 * DM, 128);
  make_map(&p.ta[5], ob, SEQ, DM, 128, 1, true);
  make_map(&p.tb[5], B_wo, DM, DM, 64, 2);
  make_store_map(&p.tc[5], out, 2 * DM, 4 * DM, 8 * DM, 128);
  make_map(&p.tq, q, SEQ, HHD, 128, 2, true);
  make_map(&p.tk, k, SEQ, HHD, 128, 1, true);
  make_map(&p.tv, v, SEQ, HHD, 128, 1, true);
  make_map(&p.tl, qkvb, SEQ / 2, 6 * DM, 64, 1, true);
  make_map(&p.th, qkvb, SEQ / 2, 6 * DM, 72, 1, true);
  make_map(&p.to, ctx, SEQ, HHD, 128, 2, true);
  p.ob = ob;
  mega_kernel<<<NCTA, 384, SMEM_BYTES, cudaStreamPerThread>>>(p);
}
```

```cpp
#include <cuda_runtime.h>
#include <cuda_bf16.h>
#include <cuda.h>
#include <stdint.h>
#include <string.h>

namespace {

typedef __nv_bfloat16 bf16;

constexpr int SEQ = 2048;
constexpr int NHEAD = 32;
constexpr int HD = 128;
constexpr int DM = 1024;
constexpr int DC = 512;
constexpr int HHD = NHEAD * HD;

__device__ __align__(1024) bf16 g_q[SEQ * HHD];
__device__ __align__(1024) bf16 g_k[SEQ * HHD];
__device__ __align__(1024) bf16 g_v[SEQ * HHD];
__device__ __align__(1024) bf16 g_qkvb[SEQ * 3 * DM];
__device__ __align__(1024) bf16 g_ob[SEQ * DM];
constexpr int CNT_QKV = 0, CNT_CTX = 16, CNT_QKVB = 32, CNT_DONE = 33, CNT_QUEUE = 34, CNT_OB = 35, CNT_N = 39;
__device__ uint32_t g_cnt[CNT_N * 8];
#ifdef TIMELINE
__device__ __align__(16) unsigned long long g_tl[132 * 4 * 64];
#endif


__device__ __forceinline__ uint32_t smem_u32(const void* p) {
  return static_cast<uint32_t>(__cvta_generic_to_shared(p));
}
__device__ __forceinline__ void mbar_init(uint32_t bar, uint32_t count) {
  asm volatile("mbarrier.init.shared::cta.b64 [%0], %1;" ::"r"(bar), "r"(count) : "memory");
}
__device__ __forceinline__ void mbar_expect_tx(uint32_t bar, uint32_t bytes) {
  asm volatile("mbarrier.arrive.expect_tx.shared::cta.b64 _, [%0], %1;" ::"r"(bar), "r"(bytes) : "memory");
}
__device__ __forceinline__ void mbar_arrive(uint32_t bar) {
  asm volatile("mbarrier.arrive.shared::cta.b64 _, [%0];" ::"r"(bar) : "memory");
}
__device__ __forceinline__ void mbar_arrive_if(uint32_t bar, bool on) {
  asm volatile("{\n.reg .pred p;\nsetp.ne.b32 p, %1, 0;\n@p mbarrier.arrive.shared::cta.b64 _, [%0];\n}" ::"r"(bar),
               "r"((int)on)
               : "memory");
}
__device__ __forceinline__ void mbar_arrive_cluster_if(uint32_t bar, uint32_t cta, bool on) {
  asm volatile(
      "{\n.reg .b32 ra;\n.reg .pred p;\nsetp.ne.b32 p, %2, 0;\nmapa.shared::cluster.u32 ra, %0, %1;\n"
      "@p mbarrier.arrive.shared::cluster.b64 _, [ra];\n}" ::"r"(bar),
      "r"(cta), "r"((int)on)
      : "memory");
}
__device__ __forceinline__ bool mbar_try_wait(uint32_t bar, uint32_t parity) {
  uint32_t ok;
  asm volatile(
      "{\n.reg .pred p;\nmbarrier.try_wait.parity.shared::cta.b64 p, [%1], %2;\nselp.u32 %0, 1, 0, p;\n}"
      : "=r"(ok)
      : "r"(bar), "r"(parity)
      : "memory");
  return ok != 0;
}
__device__ __forceinline__ bool mbar_test(uint32_t bar, uint32_t parity) {
  uint32_t ok;
  asm volatile(
      "{\n.reg .pred p;\nmbarrier.test_wait.parity.shared::cta.b64 p, [%1], %2;\nselp.u32 %0, 1, 0, p;\n}"
      : "=r"(ok)
      : "r"(bar), "r"(parity)
      : "memory");
  return ok != 0;
}
#ifdef DBGW
__device__ uint32_t* g_dbg;
__device__ __forceinline__ void mbar_wait_l(uint32_t bar, uint32_t parity, int line) {
  uint32_t t0 = clock();
  bool rec = false;
  while (!mbar_try_wait(bar, parity)) {
    uint32_t d = clock() - t0;
    if (d > (1u << 26) && !rec) { rec = true; g_dbg[blockIdx.x * 16 + (threadIdx.x >> 5)] = (bar & 1023) | (parity << 12) | (line << 16); __threadfence_system(); }
    if (d > (1u << 28)) __trap();
  }
}
#define mbar_wait(b, p) mbar_wait_l(b, p, __LINE__)
#define DBG(i, v) *(volatile uint32_t*)(g_dbg + blockIdx.x * 16 + (i)) = (v)
__device__ __forceinline__ void mbar_wait_unused(uint32_t bar, uint32_t parity) {
#else
#define DBG(i, v)
__device__ __forceinline__ void mbar_wait(uint32_t bar, uint32_t parity) {
#endif
  asm volatile(
      "{\n.reg .pred p;\n.reg .u32 t;\n"
      "mbarrier.try_wait.parity.shared::cta.b64 p, [%0], %1;\n"
      "@p bra DONE;\n"
      "mov.u32 t, 0x100000;\n"
      "LAB_WAIT:\n"
      "mbarrier.try_wait.parity.shared::cta.b64 p, [%0], %1;\n"
      "@p bra DONE;\n"
      "sub.u32 t, t, 1;\n"
      "setp.ne.u32 p, t, 0;\n"
      "@p bra LAB_WAIT;\n"
      "trap;\n"
      "DONE:\n}" ::"r"(bar),
      "r"(parity)
      : "memory");
}
constexpr uint64_t EV_NORMAL = 0x1000000000000000ull;
__device__ __forceinline__ uint64_t policy_first() {
  uint64_t p;
  asm("createpolicy.fractional.L2::evict_first.b64 %0, 1.0;" : "=l"(p));
  return p;
}
#define EV_FIRST policy_first()
__device__ __forceinline__ void tma_load_3d(uint32_t dst, const CUtensorMap* map, int c0, int c1, int c2,
                                            uint32_t bar, uint64_t hint) {
  asm volatile(
      "cp.async.bulk.tensor.3d.shared::cluster.global.mbarrier::complete_tx::bytes.L2::cache_hint [%0], [%1, {%3, %4, %5}], [%2], %6;" ::"r"(dst),
      "l"(map), "r"(bar), "r"(c0), "r"(c1), "r"(c2), "l"(hint)
      : "memory");
}
__device__ __forceinline__ void tma_load_3d_mc(uint32_t dst, const CUtensorMap* map, int c0, int c1, int c2,
                                               uint32_t bar, uint16_t mask, uint64_t hint) {
  asm volatile(
      "cp.async.bulk.tensor.3d.shared::cluster.global.mbarrier::complete_tx::bytes.multicast::cluster.L2::cache_hint [%0], [%1, {%3, %4, %5}], [%2], %6, %7;" ::"r"(dst),
      "l"(map), "r"(bar), "r"(c0), "r"(c1), "r"(c2), "h"(mask), "l"(hint)
      : "memory");
}
__device__ __forceinline__ void tma_store_3d(const CUtensorMap* map, uint32_t src, int c0, int c1, int c2, uint64_t hint) {
  asm volatile("cp.async.bulk.tensor.3d.global.shared::cta.bulk_group.L2::cache_hint [%0, {%2, %3, %4}], [%1], %5;" ::"l"(map),
               "r"(src), "r"(c0), "r"(c1), "r"(c2), "l"(hint)
               : "memory");
}
__device__ __forceinline__ void tma_store_4d(const CUtensorMap* map, uint32_t src, int c2, int c3, uint64_t hint) {
  asm volatile("cp.async.bulk.tensor.4d.global.shared::cta.bulk_group.L2::cache_hint [%0, {%2, %2, %3, %4}], [%1], %5;" ::"l"(map),
               "r"(src), "r"(0), "r"(c2), "r"(c3), "l"(hint)
               : "memory");
}
__device__ __forceinline__ void bulk_commit() { asm volatile("cp.async.bulk.commit_group;" ::: "memory"); }
template <int N>
__device__ __forceinline__ void bulk_wait_read() {
  asm volatile("cp.async.bulk.wait_group.read %0;" ::"n"(N) : "memory");
}
template <int N>
__device__ __forceinline__ void bulk_wait() {
  asm volatile("cp.async.bulk.wait_group %0;" ::"n"(N) : "memory");
}
__device__ __forceinline__ void fence_proxy_async_smem() {
  asm volatile("fence.proxy.async.shared::cta;" ::: "memory");
}
__device__ __forceinline__ bool elect_one() {
  uint32_t pred;
  asm volatile("{\n.reg .pred P;\nelect.sync _|P, 0xffffffff;\nselp.b32 %0, 1, 0, P;\n}" : "=r"(pred));
  return pred != 0;
}
__device__ __forceinline__ void named_bar_sync(int id, int n) {
  asm volatile("bar.sync %0, %1;" ::"r"(id), "r"(n) : "memory");
}
__device__ __forceinline__ void named_bar_arrive(int id, int n) {
  asm volatile("bar.arrive %0, %1;" ::"r"(id), "r"(n) : "memory");
}
__device__ __forceinline__ void named_bar_sync_if(int id, int n, bool on) {
  asm volatile("{\n.reg .pred p;\nsetp.ne.b32 p, %2, 0;\n@p bar.sync %0, %1;\n}" ::"r"(id), "r"(n), "r"((int)on) : "memory");
}
__device__ __forceinline__ void named_bar_arrive_if(int id, int n, bool on) {
  asm volatile("{\n.reg .pred p;\nsetp.ne.b32 p, %2, 0;\n@p bar.arrive %0, %1;\n}" ::"r"(id), "r"(n), "r"((int)on) : "memory");
}
template <int N>
__device__ __forceinline__ void reg_alloc() {
  asm volatile("setmaxnreg.inc.sync.aligned.u32 %0;" ::"n"(N));
}
template <int N>
__device__ __forceinline__ void reg_dealloc() {
  asm volatile("setmaxnreg.dec.sync.aligned.u32 %0;" ::"n"(N));
}
__device__ __forceinline__ void wgmma_fence() { asm volatile("wgmma.fence.sync.aligned;" ::: "memory"); }
__device__ __forceinline__ void wgmma_commit() { asm volatile("wgmma.commit_group.sync.aligned;" ::: "memory"); }
template <int N>
__device__ __forceinline__ void wgmma_wait() {
  asm volatile("wgmma.wait_group.sync.aligned %0;" ::"n"(N) : "memory");
}
template <int N>
__device__ __forceinline__ void fence_regs(float (&d)[N]) {
#pragma unroll
  for (int i = 0; i < N; i++) asm volatile("" : "+f"(d[i])::"memory");
}
__device__ __forceinline__ void fence_regs(uint32_t (&d)[32]) {
#pragma unroll
  for (int i = 0; i < 16; i++) asm volatile("" : "+r"(d[i])::"memory");
}
template <int N>
__device__ __forceinline__ void undef_regs(float (&d)[N]) {
#pragma unroll
  for (int i = 0; i < N; i++) d[i] = 0.f;
}
template <int N>
__device__ __forceinline__ void undef_regs(uint32_t (&d)[N]) {
#pragma unroll
  for (int i = 0; i < N; i++) d[i] = 0u;
}
__device__ __forceinline__ uint32_t pack_bf16(float lo, float hi) {
  uint32_t r;
  asm("cvt.rn.bf16x2.f32 %0, %1, %2;" : "=r"(r) : "f"(hi), "f"(lo));
  return r;
}
__device__ __forceinline__ void stmatrix_x4(uint32_t addr, uint32_t r0, uint32_t r1, uint32_t r2, uint32_t r3) {
  asm volatile("stmatrix.sync.aligned.m8n8.x4.shared.b16 [%0], {%1, %2, %3, %4};" ::"r"(addr), "r"(r0), "r"(r1),
               "r"(r2), "r"(r3)
               : "memory");
}
__device__ __forceinline__ void stmatrix_x4_p(uint32_t addr, uint32_t r0, uint32_t r1, uint32_t r2, uint32_t r3,
                                              bool on) {
  asm volatile("{\n.reg .pred p;\nsetp.ne.b32 p, %5, 0;\n@p stmatrix.sync.aligned.m8n8.x4.shared.b16 [%0], {%1, %2, %3, %4};\n}" ::"r"(addr),
               "r"(r0), "r"(r1), "r"(r2), "r"(r3), "r"((int)on)
               : "memory");
}
__device__ __forceinline__ float ex2(float x) {
  float y;
  asm("ex2.approx.ftz.f32 %0, %1;" : "=f"(y) : "f"(x));
  return y;
}
__device__ __forceinline__ float rcp(float x) {
  float y;
  asm("rcp.approx.ftz.f32 %0, %1;" : "=f"(y) : "f"(x));
  return y;
}
__device__ __forceinline__ float ex2v(float x) {
  float y;
  asm volatile("ex2.approx.ftz.f32 %0, %1;" : "=f"(y) : "f"(x));
  return y;
}
__device__ __forceinline__ float addv(float a, float b) {
  float y;
  asm volatile("add.f32 %0, %1, %2;" : "=f"(y) : "f"(a), "f"(b));
  return y;
}
__device__ __forceinline__ void mbar_arrive_elect(uint32_t bar, bool on) {
  asm volatile("{\n.reg .pred p, q;\nelect.sync _|q, 0xffffffff;\nsetp.ne.and.b32 p, %1, 0, q;\n@p mbarrier.arrive.shared::cta.b64 _, [%0];\n}" ::"r"(bar),
               "r"((int)on)
               : "memory");
}
__device__ __forceinline__ float mbar_test2(uint32_t bar0, uint32_t par0, uint32_t bar1, uint32_t par1) {
  float f;
  asm volatile(
      "{\n.reg .pred p, q;\nmbarrier.test_wait.parity.shared::cta.b64 p, [%1], %2;\n"
      "mbarrier.test_wait.parity.shared::cta.b64 q, [%3], %4;\nand.pred p, p, q;\nselp.f32 %0, 0f00000000, 0f80000000, p;\n}"
      : "=f"(f)
      : "r"(bar0), "r"(par0), "r"(bar1), "r"(par1)
      : "memory");
  return f;
}
__device__ __forceinline__ void mbar_wait_rest(uint32_t bar, uint32_t parity, bool ok) {
  asm volatile(
      "{\n.reg .pred p;\n.reg .u32 t;\n"
      "setp.ne.b32 p, %2, 0;\n"
      "@p bra DONE;\n"
      "mov.u32 t, 0x100000;\n"
      "LAB_WAIT:\n"
      "mbarrier.try_wait.parity.shared::cta.b64 p, [%0], %1;\n"
      "@p bra DONE;\n"
      "sub.u32 t, t, 1;\n"
      "setp.ne.u32 p, t, 0;\n"
      "@p bra LAB_WAIT;\n"
      "trap;\n"
      "DONE:\n}" ::"r"(bar),
      "r"(parity), "r"((int)ok)
      : "memory");
}
__device__ __forceinline__ void send_peer(uint32_t addr, uint32_t bar, uint32_t v) {
  asm volatile(
      "{\n.reg .b32 ra, rb;\nmapa.shared::cluster.u32 ra, %0, 1;\nmapa.shared::cluster.u32 rb, %1, 1;\n"
      "st.async.weak.shared::cluster.mbarrier::complete_tx::bytes.b32 [ra], %2, [rb];\n}" ::"r"(addr),
      "r"(bar), "r"(v)
      : "memory");
}
__device__ __forceinline__ void cnt_signal(int idx, uint32_t inc = 1) {
  asm volatile("red.release.gpu.global.add.u32 [%0], %1;" ::"l"(g_cnt + idx * 8), "r"(inc) : "memory");
}
__device__ __forceinline__ void cnt_signal_done(int idx, uint32_t inc = 1) {
  asm volatile("fence.proxy.async.global;" ::: "memory");
  cnt_signal(idx, inc);
}
__device__ __forceinline__ uint32_t cnt_next(int idx) {
  uint32_t v;
  asm volatile("atom.relaxed.gpu.global.add.u32 %0, [%1], 1;" : "=r"(v) : "l"(g_cnt + idx * 8) : "memory");
  return v;
}
__device__ __forceinline__ uint32_t cnt_peek(int idx) {
  uint32_t v;
  asm volatile("ld.acquire.gpu.global.u32 %0, [%1];" : "=r"(v) : "l"(g_cnt + idx * 8) : "memory");
  return v;
}
__device__ __forceinline__ void cnt_wait(int idx, uint32_t target) {
  asm volatile(
      "{\n.reg .pred p;\n.reg .u32 v, t0, t1;\n"
      "ld.acquire.gpu.global.u32 v, [%0];\n"
      "setp.ge.u32 p, v, %1;\n"
      "@p bra DONE;\n"
      "mov.u32 t0, %%clock;\n"
      "LAB_WAIT:\n"
      "nanosleep.u32 100;\n"
      "ld.acquire.gpu.global.u32 v, [%0];\n"
      "setp.ge.u32 p, v, %1;\n"
      "@p bra DONE;\n"
      "mov.u32 t1, %%clock;\n"
      "sub.u32 t1, t1, t0;\n"
      "setp.lt.u32 p, t1, 0x80000000;\n"
      "@p bra LAB_WAIT;\n"
      "trap;\n"
      "DONE:\n}" ::"l"(g_cnt + idx * 8),
      "r"(target)
      : "memory");
}
__device__ __forceinline__ void cnt_wait_bit(int idx, uint32_t bit, uint32_t& v) {
  asm volatile(
      "{\n.reg .pred p;\n.reg .u32 x, t0, t1;\n"
      "and.b32 x, %0, %2;\n"
      "setp.ne.u32 p, x, 0;\n"
      "@p bra DONE;\n"
      "mov.u32 t0, %%clock;\n"
      "LAB_WAIT:\n"
      "ld.acquire.gpu.global.u32 %0, [%1];\n"
      "and.b32 x, %0, %2;\n"
      "setp.ne.u32 p, x, 0;\n"
      "@p bra DONE;\n"
      "nanosleep.u32 64;\n"
      "mov.u32 t1, %%clock;\n"
      "sub.u32 t1, t1, t0;\n"
      "setp.lt.u32 p, t1, 0x80000000;\n"
      "@p bra LAB_WAIT;\n"
      "trap;\n"
      "DONE:\n}" : "+r"(v) : "l"(g_cnt + idx * 8),
      "r"(bit)
      : "memory");
}
__device__ __forceinline__ bool cnt_done(uint32_t total) {
  uint32_t old;
  asm volatile("atom.acq_rel.gpu.global.add.u32 %0, [%1], 1;" : "=r"(old) : "l"(g_cnt + CNT_DONE * 8) : "memory");
  return old == total - 1;
}
__device__ __forceinline__ void cnt_rearm() {
#pragma unroll
  for (int i = 0; i < CNT_N; i++) g_cnt[i * 8] = 0;
}
__device__ __forceinline__ void fence_proxy_async_global() { asm volatile("fence.proxy.async.global;" ::: "memory"); }
#ifdef TIMELINE
__device__ __forceinline__ void tl_rec(int role, int& n, uint32_t code) {
  unsigned long long t;
  asm volatile("mov.u64 %0, %%globaltimer;" : "=l"(t));
  uint32_t c;
  asm volatile("mov.u32 %0, %%clock;" : "=r"(c));
  if (n < 32) {
    g_tl[(blockIdx.x * 4 + role) * 64 + 2 * n] = t;
    g_tl[(blockIdx.x * 4 + role) * 64 + 2 * n + 1] = ((unsigned long long)code << 32) | c;
  }
  n++;
}
#define TL(role, code) tl_rec(role, tln, code)
__device__ __forceinline__ void tl_rec_p(int role, int& n, uint32_t code, bool on) {
  unsigned long long t;
  asm volatile("mov.u64 %0, %%globaltimer;" : "=l"(t));
  uint32_t c;
  asm volatile("mov.u32 %0, %%clock;" : "=r"(c));
  asm volatile("{\n.reg .pred p;\nsetp.ne.b32 p, %3, 0;\n@p st.global.v2.u64 [%0], {%1, %2};\n}" ::"l"(g_tl + (blockIdx.x * 4 + role) * 64 + 2 * n),
               "l"(t), "l"(((unsigned long long)code << 32) | c), "r"((int)(on && n < 32)) : "memory");
  n++;
}
#define TL0(code) tl_rec_p(0, tln, code, threadIdx.x == 0)
#define TL_DECL int tln = 0
#ifdef TLWAIT
#define TW_DECL uint32_t w0 = 0, w1 = 0, w2 = 0, w3 = 0; int tln3 = 0
#define TW(w, stmt) { uint32_t c0_ = clock(); stmt; w += clock() - c0_; }
#define TW_FLUSH() { tl_rec_p(3, tln3, (min(w0, 65534u) << 16) | min(w1, 65534u), threadIdx.x == TLWAIT); tl_rec_p(3, tln3, (min(w2, 65534u) << 16) | min(w3, 65534u), threadIdx.x == TLWAIT); w0 = w1 = w2 = w3 = 0; }
#define TW_END() tl_rec_p(3, tln3, 0xFFFF, threadIdx.x == TLWAIT)
#endif
#else
#define TL(role, code)
#define TL0(code)
#define TL_DECL
#endif
#ifdef TRACE
__device__ uint32_t g_tr[2 * 2 * 4096];
#define TR_DECL int trn = 0; const bool tron = (blockIdx.x == TRACE || blockIdx.x == TRACE2) && (threadIdx.x & 127) == TRW * 32; uint32_t* trp = g_tr + ((blockIdx.x == TRACE ? 0 : 2) + (threadIdx.x >> 7)) * 4096
#ifndef TRW
#define TRW 0
#endif
#ifndef TRM
#define TRM 0xFFFF
#endif
#define TRI(id, code) if ((TRM >> (id)) & 1) { asm volatile("{\n.reg .pred p;\nsetp.ne.b32 p, %2, 0;\n@p st.global.u32 [%0], %1;\n}" ::"l"(trp + trn), "r"(((uint32_t)clock() << 4) | (code)), "r"((int)(tron && trn < 4095)) : "memory"); trn++; }
#define TR(code) TRI(code, code)
#else
#define TR_DECL
#define TR(code)
#define TRI(id, code)
#endif
#ifndef TLWAIT
#define TW_DECL
#define TW(w, stmt) stmt
#define TW_FLUSH()
#define TW_END()
#endif

__device__ __forceinline__ uint32_t make_desc(uint32_t addr, uint32_t lbo_bytes) {
  return (addr >> 4) + ((lbo_bytes >> 4) << 16);
}

__device__ __forceinline__ void wgmma_ss_n128(float (&d)[64], uint32_t da, uint32_t db, int scale_d) {
  asm volatile("{\n.reg .pred p;\n.reg .b64 a, b;\nsetp.ne.b32 p, %66, 0;\nmov.b64 a, {%64, 0x40000040};\nmov.b64 b, {%65, 0x40000040};\n"
    "wgmma.mma_async.sync.aligned.m64n128k16.f32.bf16.bf16 {%0, %1, %2, %3, %4, %5, %6, %7, %8, %9, %10, %11, %12, %13, %14, %15, %16, %17, %18, %19, %20, %21, %22, %23, %24, %25, %26, %27, %28, %29, %30, %31, %32, %33, %34, %35, %36, %37, %38, %39, %40, %41, %42, %43, %44, %45, %46, %47, %48, %49, %50, %51, %52, %53, %54, %55, %56, %57, %58, %59, %60, %61, %62, %63}, a, b, p, 1, 1, 0, 0;\n}\n"
    : "+f"(d[0]), "+f"(d[1]), "+f"(d[2]), "+f"(d[3]), "+f"(d[4]), "+f"(d[5]), "+f"(d[6]), "+f"(d[7]), "+f"(d[8]), "+f"(d[9]), "+f"(d[10]), "+f"(d[11]), "+f"(d[12]), "+f"(d[13]), "+f"(d[14]), "+f"(d[15]), "+f"(d[16]), "+f"(d[17]), "+f"(d[18]), "+f"(d[19]), "+f"(d[20]), "+f"(d[21]), "+f"(d[22]), "+f"(d[23]), "+f"(d[24]), "+f"(d[25]), "+f"(d[26]), "+f"(d[27]), "+f"(d[28]), "+f"(d[29]), "+f"(d[30]), "+f"(d[31]), "+f"(d[32]), "+f"(d[33]), "+f"(d[34]), "+f"(d[35]), "+f"(d[36]), "+f"(d[37]), "+f"(d[38]), "+f"(d[39]), "+f"(d[40]), "+f"(d[41]), "+f"(d[42]), "+f"(d[43]), "+f"(d[44]), "+f"(d[45]), "+f"(d[46]), "+f"(d[47]), "+f"(d[48]), "+f"(d[49]), "+f"(d[50]), "+f"(d[51]), "+f"(d[52]), "+f"(d[53]), "+f"(d[54]), "+f"(d[55]), "+f"(d[56]), "+f"(d[57]), "+f"(d[58]), "+f"(d[59]), "+f"(d[60]), "+f"(d[61]), "+f"(d[62]), "+f"(d[63])
    : "r"(da), "r"(db), "r"(scale_d));
}
__device__ __forceinline__ void wgmma_ss_n64(float (&d)[32], uint32_t da, uint32_t db, int scale_d) {
  asm volatile("{\n.reg .pred p;\n.reg .b64 a, b;\nsetp.ne.b32 p, %34, 0;\nmov.b64 a, {%32, 0x40000040};\nmov.b64 b, {%33, 0x40000040};\n"
    "wgmma.mma_async.sync.aligned.m64n64k16.f32.bf16.bf16 {%0, %1, %2, %3, %4, %5, %6, %7, %8, %9, %10, %11, %12, %13, %14, %15, %16, %17, %18, %19, %20, %21, %22, %23, %24, %25, %26, %27, %28, %29, %30, %31}, a, b, p, 1, 1, 0, 0;\n}\n"
    : "+f"(d[0]), "+f"(d[1]), "+f"(d[2]), "+f"(d[3]), "+f"(d[4]), "+f"(d[5]), "+f"(d[6]), "+f"(d[7]), "+f"(d[8]), "+f"(d[9]), "+f"(d[10]), "+f"(d[11]), "+f"(d[12]), "+f"(d[13]), "+f"(d[14]), "+f"(d[15]), "+f"(d[16]), "+f"(d[17]), "+f"(d[18]), "+f"(d[19]), "+f"(d[20]), "+f"(d[21]), "+f"(d[22]), "+f"(d[23]), "+f"(d[24]), "+f"(d[25]), "+f"(d[26]), "+f"(d[27]), "+f"(d[28]), "+f"(d[29]), "+f"(d[30]), "+f"(d[31])
    : "r"(da), "r"(db), "r"(scale_d));
}
__device__ __forceinline__ void wgmma_rs_n128_tb(float (&d)[64], uint32_t a0, uint32_t a1, uint32_t a2, uint32_t a3, uint32_t db, int scale_d) {
  asm volatile("{\n.reg .pred p;\n.reg .b64 b;\nsetp.ne.b32 p, %69, 0;\nmov.b64 b, {%68, 0x40000040};\n"
    "wgmma.mma_async.sync.aligned.m64n128k16.f32.bf16.bf16 {%0, %1, %2, %3, %4, %5, %6, %7, %8, %9, %10, %11, %12, %13, %14, %15, %16, %17, %18, %19, %20, %21, %22, %23, %24, %25, %26, %27, %28, %29, %30, %31, %32, %33, %34, %35, %36, %37, %38, %39, %40, %41, %42, %43, %44, %45, %46, %47, %48, %49, %50, %51, %52, %53, %54, %55, %56, %57, %58, %59, %60, %61, %62, %63}, {%64, %65, %66, %67}, b, p, 1, 1, 1;\n}\n"
    : "+f"(d[0]), "+f"(d[1]), "+f"(d[2]), "+f"(d[3]), "+f"(d[4]), "+f"(d[5]), "+f"(d[6]), "+f"(d[7]), "+f"(d[8]), "+f"(d[9]), "+f"(d[10]), "+f"(d[11]), "+f"(d[12]), "+f"(d[13]), "+f"(d[14]), "+f"(d[15]), "+f"(d[16]), "+f"(d[17]), "+f"(d[18]), "+f"(d[19]), "+f"(d[20]), "+f"(d[21]), "+f"(d[22]), "+f"(d[23]), "+f"(d[24]), "+f"(d[25]), "+f"(d[26]), "+f"(d[27]), "+f"(d[28]), "+f"(d[29]), "+f"(d[30]), "+f"(d[31]), "+f"(d[32]), "+f"(d[33]), "+f"(d[34]), "+f"(d[35]), "+f"(d[36]), "+f"(d[37]), "+f"(d[38]), "+f"(d[39]), "+f"(d[40]), "+f"(d[41]), "+f"(d[42]), "+f"(d[43]), "+f"(d[44]), "+f"(d[45]), "+f"(d[46]), "+f"(d[47]), "+f"(d[48]), "+f"(d[49]), "+f"(d[50]), "+f"(d[51]), "+f"(d[52]), "+f"(d[53]), "+f"(d[54]), "+f"(d[55]), "+f"(d[56]), "+f"(d[57]), "+f"(d[58]), "+f"(d[59]), "+f"(d[60]), "+f"(d[61]), "+f"(d[62]), "+f"(d[63])
    : "r"(a0), "r"(a1), "r"(a2), "r"(a3), "r"(db), "r"(scale_d));
}
__device__ __forceinline__ void wgmma_ss_n72_init(float (&d)[36], uint32_t da, uint32_t db) {
  asm volatile("{\n.reg .pred p;\n.reg .b64 a, b;\nsetp.ne.b32 p, 0, 0;\nmov.b64 a, {%36, 0x40000040};\nmov.b64 b, {%37, 0x40000040};\n"
    "wgmma.mma_async.sync.aligned.m64n72k16.f32.bf16.bf16 {%0, %1, %2, %3, %4, %5, %6, %7, %8, %9, %10, %11, %12, %13, %14, %15, %16, %17, %18, %19, %20, %21, %22, %23, %24, %25, %26, %27, %28, %29, %30, %31, %32, %33, %34, %35}, a, b, p, 1, 1, 0, 0;\n}\n"
    : "=f"(d[0]), "=f"(d[1]), "=f"(d[2]), "=f"(d[3]), "=f"(d[4]), "=f"(d[5]), "=f"(d[6]), "=f"(d[7]), "=f"(d[8]), "=f"(d[9]), "=f"(d[10]), "=f"(d[11]), "=f"(d[12]), "=f"(d[13]), "=f"(d[14]), "=f"(d[15]), "=f"(d[16]), "=f"(d[17]), "=f"(d[18]), "=f"(d[19]), "=f"(d[20]), "=f"(d[21]), "=f"(d[22]), "=f"(d[23]), "=f"(d[24]), "=f"(d[25]), "=f"(d[26]), "=f"(d[27]), "=f"(d[28]), "=f"(d[29]), "=f"(d[30]), "=f"(d[31]), "=f"(d[32]), "=f"(d[33]), "=f"(d[34]), "=f"(d[35])
    : "r"(da), "r"(db));
}
__device__ __forceinline__ void wgmma_ss_n72(float (&d)[36], uint32_t da, uint32_t db, int scale_d) {
  asm volatile("{\n.reg .pred p;\n.reg .b64 a, b;\nsetp.ne.b32 p, %38, 0;\nmov.b64 a, {%36, 0x40000040};\nmov.b64 b, {%37, 0x40000040};\n"
    "wgmma.mma_async.sync.aligned.m64n72k16.f32.bf16.bf16 {%0, %1, %2, %3, %4, %5, %6, %7, %8, %9, %10, %11, %12, %13, %14, %15, %16, %17, %18, %19, %20, %21, %22, %23, %24, %25, %26, %27, %28, %29, %30, %31, %32, %33, %34, %35}, a, b, p, 1, 1, 0, 0;\n}\n"
    : "+f"(d[0]), "+f"(d[1]), "+f"(d[2]), "+f"(d[3]), "+f"(d[4]), "+f"(d[5]), "+f"(d[6]), "+f"(d[7]), "+f"(d[8]), "+f"(d[9]), "+f"(d[10]), "+f"(d[11]), "+f"(d[12]), "+f"(d[13]), "+f"(d[14]), "+f"(d[15]), "+f"(d[16]), "+f"(d[17]), "+f"(d[18]), "+f"(d[19]), "+f"(d[20]), "+f"(d[21]), "+f"(d[22]), "+f"(d[23]), "+f"(d[24]), "+f"(d[25]), "+f"(d[26]), "+f"(d[27]), "+f"(d[28]), "+f"(d[29]), "+f"(d[30]), "+f"(d[31]), "+f"(d[32]), "+f"(d[33]), "+f"(d[34]), "+f"(d[35])
    : "r"(da), "r"(db), "r"(scale_d));
}
template <int OA, int OB>
__device__ __forceinline__ void wgmma_ss_n128_tb(float (&d)[64], uint32_t da, uint32_t db, int scale_d) {
  asm volatile("{\n.reg .pred p;\n.reg .b64 a, b;\n.reg .b32 x, y;\nsetp.ne.b32 p, %66, 0;\nadd.u32 x, %64, %67;\nadd.u32 y, %65, %68;\nmov.b64 a, {x, 0x40000040};\nmov.b64 b, {y, 0x40000040};\n"
    "wgmma.mma_async.sync.aligned.m64n128k16.f32.bf16.bf16 {%0, %1, %2, %3, %4, %5, %6, %7, %8, %9, %10, %11, %12, %13, %14, %15, %16, %17, %18, %19, %20, %21, %22, %23, %24, %25, %26, %27, %28, %29, %30, %31, %32, %33, %34, %35, %36, %37, %38, %39, %40, %41, %42, %43, %44, %45, %46, %47, %48, %49, %50, %51, %52, %53, %54, %55, %56, %57, %58, %59, %60, %61, %62, %63}, a, b, p, 1, 1, 0, 1;\n}\n"
    : "+f"(d[0]), "+f"(d[1]), "+f"(d[2]), "+f"(d[3]), "+f"(d[4]), "+f"(d[5]), "+f"(d[6]), "+f"(d[7]), "+f"(d[8]), "+f"(d[9]), "+f"(d[10]), "+f"(d[11]), "+f"(d[12]), "+f"(d[13]), "+f"(d[14]), "+f"(d[15]), "+f"(d[16]), "+f"(d[17]), "+f"(d[18]), "+f"(d[19]), "+f"(d[20]), "+f"(d[21]), "+f"(d[22]), "+f"(d[23]), "+f"(d[24]), "+f"(d[25]), "+f"(d[26]), "+f"(d[27]), "+f"(d[28]), "+f"(d[29]), "+f"(d[30]), "+f"(d[31]), "+f"(d[32]), "+f"(d[33]), "+f"(d[34]), "+f"(d[35]), "+f"(d[36]), "+f"(d[37]), "+f"(d[38]), "+f"(d[39]), "+f"(d[40]), "+f"(d[41]), "+f"(d[42]), "+f"(d[43]), "+f"(d[44]), "+f"(d[45]), "+f"(d[46]), "+f"(d[47]), "+f"(d[48]), "+f"(d[49]), "+f"(d[50]), "+f"(d[51]), "+f"(d[52]), "+f"(d[53]), "+f"(d[54]), "+f"(d[55]), "+f"(d[56]), "+f"(d[57]), "+f"(d[58]), "+f"(d[59]), "+f"(d[60]), "+f"(d[61]), "+f"(d[62]), "+f"(d[63])
    : "r"(da), "r"(db), "r"(scale_d), "n"(OA), "n"(OB));
}
template <int OA, int OB>
__device__ __forceinline__ void wgmma_ss_n256_tbo(float (&d)[128], uint32_t da, uint32_t db, int scale_d) {
  asm volatile("{\n.reg .pred p;\n.reg .b64 a, b;\n.reg .b32 x, y;\nsetp.ne.b32 p, %130, 0;\nadd.u32 x, %128, %131;\nadd.u32 y, %129, %132;\nmov.b64 a, {x, 0x40000040};\nmov.b64 b, {y, 0x40000040};\n"
    "wgmma.mma_async.sync.aligned.m64n256k16.f32.bf16.bf16 {%0, %1, %2, %3, %4, %5, %6, %7, %8, %9, %10, %11, %12, %13, %14, %15, %16, %17, %18, %19, %20, %21, %22, %23, %24, %25, %26, %27, %28, %29, %30, %31, %32, %33, %34, %35, %36, %37, %38, %39, %40, %41, %42, %43, %44, %45, %46, %47, %48, %49, %50, %51, %52, %53, %54, %55, %56, %57, %58, %59, %60, %61, %62, %63, %64, %65, %66, %67, %68, %69, %70, %71, %72, %73, %74, %75, %76, %77, %78, %79, %80, %81, %82, %83, %84, %85, %86, %87, %88, %89, %90, %91, %92, %93, %94, %95, %96, %97, %98, %99, %100, %101, %102, %103, %104, %105, %106, %107, %108, %109, %110, %111, %112, %113, %114, %115, %116, %117, %118, %119, %120, %121, %122, %123, %124, %125, %126, %127}, a, b, p, 1, 1, 0, 1;\n}\n"
    : "+f"(d[0]), "+f"(d[1]), "+f"(d[2]), "+f"(d[3]), "+f"(d[4]), "+f"(d[5]), "+f"(d[6]), "+f"(d[7]), "+f"(d[8]), "+f"(d[9]), "+f"(d[10]), "+f"(d[11]), "+f"(d[12]), "+f"(d[13]), "+f"(d[14]), "+f"(d[15]), "+f"(d[16]), "+f"(d[17]), "+f"(d[18]), "+f"(d[19]), "+f"(d[20]), "+f"(d[21]), "+f"(d[22]), "+f"(d[23]), "+f"(d[24]), "+f"(d[25]), "+f"(d[26]), "+f"(d[27]), "+f"(d[28]), "+f"(d[29]), "+f"(d[30]), "+f"(d[31]), "+f"(d[32]), "+f"(d[33]), "+f"(d[34]), "+f"(d[35]), "+f"(d[36]), "+f"(d[37]), "+f"(d[38]), "+f"(d[39]), "+f"(d[40]), "+f"(d[41]), "+f"(d[42]), "+f"(d[43]), "+f"(d[44]), "+f"(d[45]), "+f"(d[46]), "+f"(d[47]), "+f"(d[48]), "+f"(d[49]), "+f"(d[50]), "+f"(d[51]), "+f"(d[52]), "+f"(d[53]), "+f"(d[54]), "+f"(d[55]), "+f"(d[56]), "+f"(d[57]), "+f"(d[58]), "+f"(d[59]), "+f"(d[60]), "+f"(d[61]), "+f"(d[62]), "+f"(d[63]), "+f"(d[64]), "+f"(d[65]), "+f"(d[66]), "+f"(d[67]), "+f"(d[68]), "+f"(d[69]), "+f"(d[70]), "+f"(d[71]), "+f"(d[72]), "+f"(d[73]), "+f"(d[74]), "+f"(d[75]), "+f"(d[76]), "+f"(d[77]), "+f"(d[78]), "+f"(d[79]), "+f"(d[80]), "+f"(d[81]), "+f"(d[82]), "+f"(d[83]), "+f"(d[84]), "+f"(d[85]), "+f"(d[86]), "+f"(d[87]), "+f"(d[88]), "+f"(d[89]), "+f"(d[90]), "+f"(d[91]), "+f"(d[92]), "+f"(d[93]), "+f"(d[94]), "+f"(d[95]), "+f"(d[96]), "+f"(d[97]), "+f"(d[98]), "+f"(d[99]), "+f"(d[100]), "+f"(d[101]), "+f"(d[102]), "+f"(d[103]), "+f"(d[104]), "+f"(d[105]), "+f"(d[106]), "+f"(d[107]), "+f"(d[108]), "+f"(d[109]), "+f"(d[110]), "+f"(d[111]), "+f"(d[112]), "+f"(d[113]), "+f"(d[114]), "+f"(d[115]), "+f"(d[116]), "+f"(d[117]), "+f"(d[118]), "+f"(d[119]), "+f"(d[120]), "+f"(d[121]), "+f"(d[122]), "+f"(d[123]), "+f"(d[124]), "+f"(d[125]), "+f"(d[126]), "+f"(d[127])
    : "r"(da), "r"(db), "r"(scale_d), "n"(OA), "n"(OB));
}

constexpr int NCTA = 132;
constexpr int NCLUSTER = 66;
constexpr int NPROB = 6;
#ifdef GEMM_ONLY
#define DO_LOCAL false
#define DO_ATT false
#else
#define DO_LOCAL true
#define DO_ATT true
#endif
#ifdef ATT_ONLY
#define NA_CL_ 0
#define NITEMS 768
#else
#define NA_CL_ 32
#define NITEMS 256
#endif
constexpr int G1_MAX = 24, NA_CL = NA_CL_, NB_CL = NCLUSTER - NA_CL;
constexpr int TILE32K = 32768;
constexpr uint32_t DBASE = 1024;
constexpr int OFF_STG = 4 * TILE32K;
constexpr int OFF_A = 5 * TILE32K;
constexpr int OFF_BAR = 7 * TILE32K;
constexpr int L_K = 8192, L_V = L_K + 9216, L_P = L_V + 9216;
constexpr int SMEM_BYTES = OFF_BAR + 1024;
constexpr int B_GFULL = 0, B_GEMPTY = 32, B_AFULL = 64, B_AEMPTY = 104, B_QFULL = 144, B_QEMPTY = 160,
              B_SFULL = 176, B_SEMPTY = 208, B_OFULL = 240, B_STGFREE = 256, S_CODE = 272, B_SFULL2 = 304,
              B_MAIL = 336, S_MAIL = 368;
#ifndef FS
#define FS 2
#endif
#ifndef HW
#define HW 1
#endif
#ifndef PACE
#define PACE 900u
#define DELAY 1300u
#endif
#ifndef REG_C
#define REG_C 232
#define REG_P 40
#endif

struct Params {
  CUtensorMap ta[NPROB];
  CUtensorMap tb[NPROB];
  CUtensorMap tc[NPROB];
  CUtensorMap tq, tk, tv, to, tl, th;
  bf16* ob;
  uint16_t g[NCLUSTER][G1_MAX];
  uint16_t order[256];
};
__device__ __forceinline__ uint32_t tail_item(uint32_t code) {
  return (code & 0x7FFF) < 32 ? (5u << 8) | ((code & 4) << 4) | ((code & 0x18) << 1) | (code & 3) : 0xFFFFu;
}
#ifndef HM
#define HM 0x39383F00
#endif
#define HINT(b) ((HM >> (b) & 1) ? EV_FIRST : EV_NORMAL)
__device__ __forceinline__ uint32_t lds32(uint32_t a) {
  uint32_t v;
  asm volatile("ld.shared.u32 %0, [%1];" : "=r"(v) : "r"(a) : "memory");
  return v;
}
__device__ __forceinline__ uint4 lds128(uint32_t a) {
  uint4 v;
  asm volatile("ld.shared.v4.u32 {%0, %1, %2, %3}, [%4];" : "=r"(v.x), "=r"(v.y), "=r"(v.z), "=r"(v.w) : "r"(a) : "memory");
  return v;
}
__device__ __forceinline__ void sts64(uint32_t a, float x, float y) {
  asm volatile("st.shared.v2.f32 [%0], {%1, %2};" ::"r"(a), "f"(x), "f"(y) : "memory");
}
__device__ __forceinline__ void sts32(uint32_t a, uint32_t v) {
  asm volatile("st.shared.u32 [%0], %1;" ::"r"(a), "r"(v) : "memory");
}
__device__ __forceinline__ uint32_t opaque_tid() {
  uint32_t t;
  asm volatile("mov.u32 %0, %%tid.x;" : "=r"(t));
  return t;
}
__device__ __forceinline__ uint32_t stg_off(uint32_t tid) {
  return (tid >> 5) * 2048 + (tid & 15) * 128 + ((((tid >> 4) & 1) ^ (tid & 7)) << 4);
}
__device__ __forceinline__ int prob_nkb4(int prob) { return (0x4F4224 >> (prob * 4) & 15) + (prob == 4); }

constexpr float SM_C = 0.08838834764831845f * 1.4426950408889634f;
constexpr float SM_HI = 1099511627776.0f;
constexpr float SM_LO = 8.673617379884035e-19f;
__device__ __forceinline__ void softmax_max(const float (&s)[64], float& a0, float& a1) {
  a0 = fmaxf(s[0], s[1]);
  a1 = fmaxf(s[2], s[3]);
#pragma unroll
  for (int j = 1; j < 16; j++) {
    a0 = fmaxf(a0, fmaxf(s[4 * j], s[4 * j + 1]));
    a1 = fmaxf(a1, fmaxf(s[4 * j + 2], s[4 * j + 3]));
  }
  a0 = fmaxf(a0, __shfl_xor_sync(0xffffffffu, a0, 1));
  a1 = fmaxf(a1, __shfl_xor_sync(0xffffffffu, a1, 1));
  a0 = fmaxf(a0, __shfl_xor_sync(0xffffffffu, a0, 2));
  a1 = fmaxf(a1, __shfl_xor_sync(0xffffffffu, a1, 2));
}
template <int J0, int J1, bool OFS, int N>
__device__ __forceinline__ void softmax_exp(const float (&s)[64], float b0, float b1, uint32_t (&out)[N], float& t0,
                                            float& t1) {
#pragma unroll
  for (int j = J0; j < J1; j++) {
    const float e0 = ex2(OFS ? s[4 * j] + b0 : s[4 * j]);
    const float e1 = ex2(OFS ? s[4 * j + 1] + b0 : s[4 * j + 1]);
    const float e2 = ex2(OFS ? s[4 * j + 2] + b1 : s[4 * j + 2]);
    const float e3 = ex2(OFS ? s[4 * j + 3] + b1 : s[4 * j + 3]);
    t0 += e0 + e1;
    t1 += e2 + e3;
    out[2 * j] = pack_bf16(e0, e1);
    out[2 * j + 1] = pack_bf16(e2, e3);
  }
}

__device__ __forceinline__ uint32_t scale_q(uint32_t x) {
  uint32_t t, y;
  asm("mul.rn.bf16x2 %0, %1, %2;" : "=r"(t) : "r"(x), "r"(0xb9d8b9d8u));
  asm("fma.rn.bf16x2 %0, %1, %2, %3;" : "=r"(y) : "r"(x), "r"(0x3e033e03u), "r"(t));
  return y;
}

__global__ void __cluster_dims__(2, 1, 1) __launch_bounds__(384, 1) mega_kernel(const __grid_constant__ Params p) {
  extern __shared__ __align__(1024) uint8_t smem_raw[];
#ifdef TRACE
  const uint32_t c_entry = clock();
#endif
  const uint32_t sbase = smem_u32(smem_raw);
  const uint32_t s_bar = sbase + OFF_BAR;
  const int cluster_id = blockIdx.x >> 1;
  const bool isB = cluster_id >= NA_CL;
#if !defined(ATT_ONLY) && !defined(GEMM_ONLY)
#define EARLY 1
#else
#define EARLY 0
#endif
  const int prob0 = isB ? 3 : cluster_id >> 4;
  const int ng0 = (isB ? (cluster_id - NA_CL) >> 3 : (cluster_id >> 3) & 1) * 4;
  const uint32_t t0 = clock();
  auto early = [&](int s) {
    const uint32_t full = s_bar + B_GFULL + 8 * s;
    mbar_expect_tx(full, 49152);
    tma_load_3d(sbase + OFF_A + s * 16384, &p.ta[prob0], 0, (blockIdx.x & 15) * 128, s, full, EV_NORMAL);
    tma_load_3d(sbase + s * TILE32K, &p.tb[prob0], 0, s * 64, ng0, full, EV_NORMAL);
    tma_load_3d(sbase + s * TILE32K + 16384, &p.tb[prob0], 0, s * 64, ng0 + 2, full, EV_NORMAL);
  };
  if ((threadIdx.x >> 5) == 8) {
    if (elect_one()) {
      mbar_init(s_bar + B_GFULL, 1);
      asm volatile("fence.mbarrier_init.release.cluster;" ::: "memory");
      if (EARLY && !isB) early(0);
      for (int s = 1; s < 4; s++) mbar_init(s_bar + B_GFULL + 8 * s, 1);
      asm volatile("fence.mbarrier_init.release.cluster;" ::: "memory");
    }
    __syncwarp();
    named_bar_arrive(7, 288);
  }
  const int warp0 = __shfl_sync(0xffffffffu, threadIdx.x >> 5, 0);
  if (warp0 >= 8) reg_dealloc<REG_P>();
#define CLUSTER_ARRIVE() asm volatile("barrier.cluster.arrive.relaxed.aligned;" ::: "memory")
#define CLUSTER_WAIT() asm volatile("barrier.cluster.wait.acquire.aligned;" ::: "memory")

  if (warp0 >= 8) {
    if (warp0 == 10 && elect_one()) {
      if ((sbase & 0x3FFFFu) != DBASE) __trap();
      for (int s = 0; s < 4; s++) {
        mbar_init(s_bar + B_GEMPTY + 8 * s, 4);
        mbar_init(s_bar + B_SFULL + 8 * s, 4);
        mbar_init(s_bar + B_SFULL2 + 8 * s, 4);
        mbar_init(s_bar + B_SEMPTY + 8 * s, 1);
        mbar_init(s_bar + B_AFULL + 8 * s, 1);
        mbar_init(s_bar + B_AEMPTY + 8 * s, isB ? 4 : s ? 8 : 2);
        mbar_init(s_bar + B_MAIL + 8 * s, 1);
      }
      for (int s = 0; s < 2; s++) {
        mbar_init(s_bar + B_QFULL + 8 * s, 1);
        mbar_init(s_bar + B_QEMPTY + 8 * s, 2);
      }
      mbar_init(s_bar + B_OFULL, 8);
      mbar_init(s_bar + B_STGFREE, 1);
      asm volatile("fence.mbarrier_init.release.cluster;" ::: "memory");
    }
    __syncwarp();
    CLUSTER_ARRIVE();
    if (EARLY && warp0 == 8 && elect_one()) {
#pragma unroll 1
      for (int s = !isB; s < 4; s++) {
        while ((uint32_t)clock() - t0 < s * PACE + (isB ? DELAY : 0u)) {}
        early(s);
      }
    }
    __syncwarp();
    CLUSTER_WAIT();
    const uint32_t rank = blockIdx.x & 1;
    if (warp0 == 8) {
      if (elect_one()) {
        TL_DECL;
        uint32_t gphase = 1 - EARLY;
        uint32_t tail = 0;
        int gi = 0;
        uint32_t aswz = 0, lastq = 0, n = 0;
        uint32_t aprev = ~0u;
        for (int seg = 0; seg < 2; seg++) {
          for (;;) {
            uint32_t item = p.g[cluster_id][gi++];
            if (item == 0x500u) item = tail;
            if (item >= 0x600u) break;
            const int prob = item >> 8;
            const int rt = ((item >> 4) & 15) * 2 + rank;
            const int ngrp0 = (item & 15) * 4;
            const int nkb4 = prob_nkb4(prob);
            const CUtensorMap* ta = &p.ta[prob];
            const CUtensorMap* tb = &p.tb[prob];
            const uint64_t ahint = p.g[cluster_id][gi] >= 0x400u ? EV_FIRST : EV_NORMAL;
            const int rot4 = prob < 4 ? 1 - gi : 0;
            const uint32_t akey = (item + 0x100u) & 0x6F0u;
            const bool keep = akey == aprev;
            aprev = akey;
            TL(1, item);
            uint32_t seen = 0;
            if (prob == 5) {
              cnt_wait_bit(CNT_OB + (rt >> 2), 32u << (rt & 3) * 8, seen);
              fence_proxy_async_global();
            }
            for (int kb4 = EARLY && gi == 1; kb4 < nkb4; kb4++) {
#pragma unroll 1
              for (int s = 0; s < 4; s++) {
                const int bs = s ^ (n & 1);
                if (prob == 4 && !(s & 1)) {
                  cnt_wait_bit(CNT_CTX + rt, 1u << (kb4 * 2 + (s >> 1)), seen);
                  fence_proxy_async_global();
                }
                if (prob == 5 && kb4 == 0) {
                  mbar_wait(s_bar + B_AEMPTY + 8 * bs, (~(n + (s & 1)) >> 1) & 1);
                  if (s == 2) mbar_wait(s_bar + B_QEMPTY + (aswz ? 0 : 8), lastq);
                }
                mbar_wait(s_bar + B_GEMPTY + 8 * s, gphase);
                const uint32_t full = s_bar + B_GFULL + 8 * s;
                const int kb = ((kb4 + rot4) & (nkb4 - 1)) * 4 + s;
                if (keep && kb4 == 0) {
                  mbar_expect_tx(full, 32768);
                } else {
                  mbar_expect_tx(full, 49152);
                  tma_load_3d(sbase + OFF_A + ((s * 16384) ^ aswz), ta, 0, rt * 128, kb, full, ahint);
                }
                tma_load_3d_mc(sbase + bs * TILE32K + rank * 16384, tb, 0, kb * 64, ngrp0 + rank * 2, full,
                               (uint16_t)3, HINT(8 + prob));
              }
              gphase ^= 1;
            }
          }
          if (seg == 0 && isB && DO_ATT) {
            int pv_row = 0, pv_col = 0;
            uint64_t pv_hint = 0;
            bool pv_own = false;
#define ACQ_SLOT(slot, n)                                                              \
  {                                                                                    \
    if ((n) < 2) mbar_wait(s_bar + B_GEMPTY + 8 * (slot), gphase);                     \
    mbar_wait(s_bar + B_AEMPTY + 8 * (slot), (~(n) >> 1) & 1);                         \
  }
#define LOAD_KV(map, slot, row, col, own, hint)                                        \
  {                                                                                    \
    const uint32_t full = s_bar + B_AFULL + 8 * (slot);                                \
    mbar_expect_tx(full, TILE32K);                                                     \
    if (own) {                                                                         \
      tma_load_3d(sbase + (slot) * TILE32K, map, 0, row, col, full, hint);             \
      tma_load_3d(sbase + (slot) * TILE32K + 16384, map, 0, row, (col) + 1, full, hint); \
    } else {                                                                           \
      tma_load_3d_mc(sbase + (slot) * TILE32K + rank * 16384, map, 0, row, (col) + rank, full, (uint16_t)3, hint); \
    }                                                                                  \
  }
#define LOAD_V()                                                                       \
  {                                                                                    \
    const uint32_t vs = 3 - (n & 1);                                                   \
    ACQ_SLOT(vs, n - 1);                                                               \
    LOAD_KV(&p.tv, vs, pv_row, pv_col, pv_own, pv_hint)                                \
  }
#ifdef ATT_ONLY
#define NEXT_CODE() (nxt < NITEMS ? p.order[nxt & 255] : 0x8000u + 64)
#else
#define NEXT_CODE() (nxt < 256 ? p.order[nxt] : nxt + (0x8000u - 256))
#endif
            uint32_t code = p.order[cluster_id - NA_CL];
            int it = 0;
            uint32_t seen = 0;
            for (;; it++) {
              if (it == 1) mbar_wait(s_bar + B_STGFREE, 0);
              if (code & 0x8000u) break;
              const int head = code >> 4;
              const int q0 = code & 15, up = rank == (it & 1);
              uint32_t nxt = 0;
              TL(1, 0x1000 | code | up);
#ifndef ATT_ONLY
              if (seen < 48) cnt_wait(CNT_QKV + (head >> 1), 48);
#endif
              fence_proxy_async_global();
              {
                const int b = it & 1;
                if (it < 2) {
                  mbar_wait(s_bar + B_GEMPTY + 16 * b, gphase);
                  mbar_wait(s_bar + B_GEMPTY + 16 * b + 8, gphase);
                }
                mbar_wait(s_bar + B_QEMPTY + 8 * b, ((it >> 1) & 1) ^ 1);
                mbar_expect_tx(s_bar + B_QFULL + 8 * b, TILE32K);
                tma_load_3d(sbase + OFF_A + b * TILE32K, &p.tq, 0, (q0 + up) * 128, head * 2, s_bar + B_QFULL + 8 * b, HINT(24));
              }
#pragma unroll 1
              for (int i = q0 + (up & it); i >= -(up & ~it); i--) {
                const int t = i < 0 ? q0 + 1 : i;
                if (rank == 0 && i == min(q0, 1)) nxt = cnt_next(CNT_QUEUE) + NB_CL;
                if (i == 0) {
                  if (rank == 0) {
                    code = NEXT_CODE();
                    send_peer(s_bar + S_MAIL + 4 * (it & 3), s_bar + B_MAIL + 8 * (it & 3), code);
                  } else {
                    mbar_expect_tx(s_bar + B_MAIL + 8 * (it & 3), 4);
                    mbar_wait(s_bar + B_MAIL + 8 * (it & 3), (it >> 2) & 1);
                    code = lds32(s_bar + S_MAIL + 4 * (it & 3));
                  }
                  sts32(s_bar + S_CODE + 4 * ((it + 1) & 7), code);
                  seen = cnt_peek(CNT_QKV + ((code >> 5) & 15));
                }
                ACQ_SLOT(n & 1, n);
                LOAD_KV(&p.tk, n & 1, t * 128, head * 2, t > q0, HINT(t >= q0 ? 29 : 25))
                if (n) LOAD_V();
                n++;
                pv_row = t * 128;
                pv_col = head * 2;
                pv_own = t > q0;
                pv_hint = HINT(t >= q0 ? 29 : 26);
              }
            }
            ACQ_SLOT(n & 1, n);
            mbar_arrive(s_bar + B_AFULL + 8 * (n & 1));
            LOAD_V();
            if (rank & it) {
              ACQ_SLOT(2 + (n & 1), n);
#pragma unroll 1
              for (int i = 0; i < 8; i++) mbar_arrive_cluster_if(s_bar + B_AEMPTY + 8 * ((n & 1) + (i & 2)), i & 1, true);
              n++;
            }
            tail = tail_item(code);
            aswz = (it & 1) * TILE32K;
            mbar_wait(s_bar + B_QEMPTY + 8 * (it & 1), ((it >> 1) & 1) ^ 1);
            lastq = ((it - 1) >> 1) & 1;
            if (tail == 0xFFFFu) {
#pragma unroll 1
              for (int s = 0; s < 4; s++) mbar_wait(s_bar + B_AEMPTY + 8 * (s ^ (n & 1)), (~(n + (s & 1)) >> 1) & 1);
            }
          }
        }
        if (cnt_done(NCTA * 2)) cnt_rearm();
#pragma unroll 1
        for (int s = 0; s < 4; s++) mbar_wait(s_bar + B_GEMPTY + 8 * s, gphase);
        TL(1, 0xFFFF);
      }
    } else if (warp0 == 9) {
      if (elect_one()) {
        TL_DECL;
        uint32_t tail = 0;
        int gi = 0;
        uint32_t aswz = 0;
        bool rearm = false;
        for (int seg = 0; seg < 2; seg++) {
          for (;;) {
            uint32_t item = p.g[cluster_id][gi++];
            if (item == 0x500u) item = tail;
            if (item >= 0x600u) break;
            const int prob = item >> 8;
            const int rt = ((item >> 4) & 15) * 2 + rank;
            const int cg = (item & 15) * 4 + (prob == 5 ? 16 : 0);
            const CUtensorMap* tc = &p.tc[prob];
            const int nl = (p.g[cluster_id][gi] >> 8) == 4 && DO_LOCAL ? 8 : 1;
            const int grp = (blockIdx.x & 15) * 2 + ((blockIdx.x >> 4) & 1), r0 = (blockIdx.x >> 5) * 512;
            if (nl > 1) {
              cnt_wait(CNT_QKVB, 192);
              fence_proxy_async_global();
            }
            if (prob >= 4) rearm = cnt_done(NCTA * 2);
            const bool lastt = p.g[cluster_id][gi] >= 0x600u;
#pragma unroll 1
            for (int c = 0; c < 8; c++) {
              const int q = lastt ? c & 3 : c >> 1, w = lastt ? c >> 2 : c & 1;
              const int idx = w * 2 + (q & 1);
              const bool alt = lastt && q >= 2;
              mbar_wait(s_bar + (alt ? B_SFULL2 : B_SFULL) + 8 * idx, lastt ? seg : q >> 1);
              tma_store_4d(tc, sbase + (alt ? OFF_A + ((q * 16384) ^ aswz) + w * 8192 : OFF_STG + idx * 8192),
                           rt * 64 + w * 32, cg + q, HINT(16 + prob));
              bulk_commit();
              if (c > 0 && !lastt) {
                bulk_wait_read<1>();
                mbar_arrive(s_bar + B_SEMPTY + 8 * ((w ^ 1) * 2 + (((c - 1) >> 1) & 1)));
              }
            }
            bulk_wait_read<0>();
            mbar_arrive(s_bar + (lastt ? B_STGFREE : B_SEMPTY + 8 * 3));
#pragma unroll 1
            for (int c = 0; c < nl; c++) {
              if (nl > 1) {
                mbar_wait(s_bar + B_AEMPTY, (c & 1) ^ 1);
                mbar_expect_tx(s_bar + B_AFULL, L_V);
                tma_load_3d(sbase + OFF_STG, &p.tl, 0, r0 + c * 64, grp, s_bar + B_AFULL, HINT(28));
                tma_load_3d(sbase + OFF_STG + L_K, &p.th, 0, r0 + c * 64 - 8, 32 + grp, s_bar + B_AFULL, HINT(28));
                mbar_wait(s_bar + B_AEMPTY + 8, (c & 1) ^ 1);
                mbar_expect_tx(s_bar + B_AFULL + 8, 9216);
                tma_load_3d(sbase + OFF_STG + L_V, &p.th, 0, r0 + c * 64 - 8, 64 + grp, s_bar + B_AFULL + 8, HINT(28));
              }
              if (c) {
                mbar_wait(s_bar + B_OFULL, ~c & 1);
                cnt_signal(CNT_OB + (blockIdx.x >> 5) * 2 + ((c - 1) >> 2), 1u << ((c - 1) & 3) * 8);
              } else if (prob < 4) {
                bulk_wait<0>();
                cnt_signal_done(prob == 3 ? CNT_QKVB : CNT_QKV + (item & 15));
                TL(2, item);
              }
            }
            if (nl > 1) {
              mbar_wait(s_bar + B_OFULL, 1);
              cnt_signal(CNT_OB + (blockIdx.x >> 5) * 2 + 1, 1u << 24);
              TL(2, 0x600);
            }
          }
          if (seg == 0 && isB && DO_ATT) {
#ifdef ATT_ONLY
            mbar_arrive(s_bar + B_STGFREE);
#endif
            uint32_t code = p.order[cluster_id - NA_CL];
            for (int it = 0; !(code & 0x8000u); it++) {
              code |= rank == (it & 1);
              aswz = (~it & 1) * TILE32K;
              mbar_wait(s_bar + B_OFULL, it & 1);
              tma_store_3d(&p.to, sbase + OFF_STG, 0, (code & 15) * 128, (code >> 4) * 2, HINT(27));
              bulk_commit();
              const uint32_t nxt = lds32(s_bar + S_CODE + 4 * ((it + 1) & 7));
              bulk_wait_read<0>();
              mbar_arrive(s_bar + B_STGFREE);
              bulk_wait<0>();
              cnt_signal_done(CNT_CTX + (code & 15), 1u << (code >> 4));
              TL(2, 0x1000 | code);
              code = nxt;
            }
            tail = tail_item(code);
            if (tail == 0xFFFFu) rearm = cnt_done(NCTA * 2);
          }
        }
        if (rearm) cnt_rearm();
        TL(2, 0xFFFF);
      }
    }
  } else {
    CLUSTER_ARRIVE();
    reg_alloc<REG_C>();
    named_bar_sync(7, 288);
    const int warp = __shfl_sync(0xffffffffu, opaque_tid() >> 5, 0);
    const int wg = warp >> 2;
    const int lane = threadIdx.x & 31;
    TL_DECL;
    TR_DECL;
#ifdef TRACE
    if (tron) trp[trn] = (c_entry << 4) | 12;
    trn++;
    TRI(9, 13);
#endif
    named_bar_arrive_if(1, 256, wg == 1);
    uint32_t gphase = 0;
    uint32_t tail = 0, aswz = 0, rot = 0, stgpar = 1;
    const uint32_t etgt = warp & 1;
    int gi = 0;
    for (int seg = 0; seg < 2; seg++) {
      uint32_t item = p.g[cluster_id][gi++];
      if (item == 0x500u) item = tail;
      if (item < 0x600u) {
        float acc[128];
        uint32_t pk[64];
        int have = 0;
#define G_STORE_CHUNK(q)                                                                               \
  {                                                                                                    \
    const uint32_t st_base = sbase + OFF_STG + wg * 8192 + stg_off(opaque_tid());                      \
    if (have == 2) { _Pragma("unroll") for (int j = 0; j < 16; j++) pk[(q) * 16 + j] = scale_q(pk[(q) * 16 + j]); } \
    mbar_wait(s_bar + B_SEMPTY + 8 * (wg * 2 + ((q) & 1)), (((q) >> 1) & 1) ^ 1);                      \
    _Pragma("unroll") for (int j = 0; j < 4; j++)                                                      \
        stmatrix_x4((st_base ^ (j << 5)) + ((q) & 1) * 8192, pk[(q) * 16 + j * 4],                     \
                    pk[(q) * 16 + j * 4 + 1], pk[(q) * 16 + j * 4 + 2], pk[(q) * 16 + j * 4 + 3]);     \
    fence_proxy_async_smem();                                                                          \
    __syncwarp();                                                                                      \
    mbar_arrive_elect(s_bar + B_SFULL + 8 * (wg * 2 + ((q) & 1)), true);                              \
  }
#define G_STAGE(s) G_STAGE_Y(s, false, false, )
#define G_STAGE_X(s, ...) G_STAGE_Y(s, false, false, __VA_ARGS__)
#define G_STAGE_Y(s, first, last, ...)                                                                    \
  {                                                                                                       \
    mbar_wait_rest(s_bar + B_GFULL + 8 * (s), gphase, gok && (first));                                    \
    TR(9);                                                                                                \
    const uint32_t da = make_desc(DBASE + OFF_A + (((s) * 16384) ^ aswz) + wg * 8192, 16);                \
    const uint32_t db = make_desc(DBASE + ((s) ^ rot) * TILE32K, 8192);                                   \
    named_bar_sync_if(5 + wg, 256, !(first));                                                             \
    wgmma_fence();                                                                                        \
    _Pragma("unroll") for (int k = 0; k < 5; k++) {                                                       \
      __VA_ARGS__;                                                                                        \
      if (k == 0) wgmma_ss_n256_tbo<0, 0>(acc, da, db, !(first));                                         \
      if (k == 1) wgmma_ss_n256_tbo<2, 128>(acc, da, db, 1);                                              \
      if (k == 2) wgmma_ss_n256_tbo<4, 256>(acc, da, db, 1);                                              \
      if (k == 3) wgmma_ss_n256_tbo<6, 384>(acc, da, db, 1);                                              \
    }                                                                                                     \
    wgmma_commit();                                                                                       \
    named_bar_arrive_if(6 - wg, 256, !(wg ? (last) : (first)));                                           \
    if (!(first)) {                                                                                       \
      wgmma_wait<1>();                                                                                    \
      mbar_arrive_cluster_if(s_bar + B_GEMPTY + 8 * (((s) + 3) & 3), etgt, lane == 0 && (warp & 3) < 2);  \
    }                                                                                                     \
  }
        TL0(item);
        undef_regs(acc);
        {
          constexpr bool gok = false;
#ifdef TRE
          const uint32_t e0 = clock() - c_entry;
          mbar_wait(s_bar + B_GFULL, gphase);
          if (threadIdx.x == 0 && seg == 0) g_tr[16001 + 2 * blockIdx.x] = e0 | ((clock() - c_entry) << 16);
#endif
          G_STAGE_Y(0, true, false, )
        }
        if (seg == 0) CLUSTER_WAIT();
        undef_regs(pk);
        for (;;) {
          constexpr bool gok = false;
          const int nkb4 = prob_nkb4(item >> 8);
          const uint32_t next = p.g[cluster_id][gi++];
          G_STAGE(1)
          if (have) G_STORE_CHUNK(0)
          G_STAGE(2)
          G_STAGE(3)
          if (have) G_STORE_CHUNK(1)
          gphase ^= 1;
          G_STAGE(0)
          G_STAGE(1)
          if (have) G_STORE_CHUNK(2)
          G_STAGE(2)
          if (have) G_STORE_CHUNK(3)
          G_STAGE_Y(3, false, nkb4 == 2, )
          gphase ^= 1;
          int kb4 = 2;
          if (nkb4 == 16 && DO_LOCAL) {
            constexpr uint32_t aswz = 0, rot = 0;
            G_STAGE(0)
            G_STAGE(1)
            for (; kb4 < 10; kb4++) {
              float ls[36];
              TR(10);
              mbar_wait(s_bar + B_AFULL, kb4 & 1);
              TR(11);
              {
                const uint32_t dq = make_desc(DBASE + OFF_STG + wg * 64, 16);
                G_STAGE_X(2, if (k == 1) wgmma_ss_n72_init(ls, dq, dq + L_K / 16); if (k == 3) wgmma_ss_n72(ls, dq + 2, dq + L_K / 16 + 2, 1))
              }
              mbar_wait(s_bar + B_AFULL + 8, kb4 & 1);
              const int tid = opaque_tid();
              uint32_t vw[16];
              uint4 pw[8];
              {
                const uint32_t va = sbase + OFF_STG + L_V + ((tid >> 4) & 7) * 1024 + wg * 64 + (tid & 15) * 4;
#pragma unroll
                for (int j = 1; j < 16; j++) vw[j] = lds32((va ^ ((j & 7) << 4)) + j * 128);
              }
              G_STAGE(3)
              gphase ^= 1;
              fence_regs(ls);
              mbar_arrive_if(s_bar + B_AEMPTY, (threadIdx.x & 127) == 0);
              {
                const int d = (tid & 3) * 2 - ((tid >> 2) & 7);
                const bool p0 = d > 0, p1 = d >= 0;
                const int w = warp & 3;
                float x0, x1, y0, y1;
#define L_PICK(w_)                                   \
  {                                                  \
    x0 = p0 ? ls[8 * (w_)] : ls[8 * (w_) + 4];       \
    x1 = p1 ? ls[8 * (w_) + 1] : ls[8 * (w_) + 5];   \
    y0 = p0 ? ls[8 * (w_) + 6] : ls[8 * (w_) + 10];  \
    y1 = p1 ? ls[8 * (w_) + 7] : ls[8 * (w_) + 11];  \
  }
                if (w == 0) {
                  if (kb4 == 2 && blockIdx.x < 32) ls[0] = ls[1] = -INFINITY;
                  L_PICK(0)
                } else if (w == 1) L_PICK(1)
                else if (w == 2) L_PICK(2)
                else L_PICK(3)
                constexpr float C = 0.17677669529663687f * 1.4426950408889634f;
                float mx = fmaxf(x0, x1), my = fmaxf(y0, y1);
                mx = fmaxf(mx, __shfl_xor_sync(0xffffffffu, mx, 1));
                my = fmaxf(my, __shfl_xor_sync(0xffffffffu, my, 1));
                mx = -C * fmaxf(mx, __shfl_xor_sync(0xffffffffu, mx, 2));
                my = -C * fmaxf(my, __shfl_xor_sync(0xffffffffu, my, 2));
                x0 = ex2(fmaf(x0, C, mx));
                x1 = ex2(fmaf(x1, C, mx));
                y0 = ex2(fmaf(y0, C, my));
                y1 = ex2(fmaf(y1, C, my));
                float sx = x0 + x1, sy = y0 + y1;
                sx += __shfl_xor_sync(0xffffffffu, sx, 1);
                sy += __shfl_xor_sync(0xffffffffu, sy, 1);
                sx += __shfl_xor_sync(0xffffffffu, sx, 2);
                sy += __shfl_xor_sync(0xffffffffu, sy, 2);
                sx = rcp(sx);
                sy = rcp(sy);
                const uint32_t pa = sbase + OFF_STG + L_P + (tid >> 5) * 512 + (tid & 31) * 8;
                sts64(pa, x0 * sx, x1 * sx);
                sts64(pa + 256, y0 * sy, y1 * sy);
                __syncwarp();
              }
              const uint32_t pr = sbase + OFF_STG + L_P + (tid >> 4) * 256;
              uint32_t* dst = reinterpret_cast<uint32_t*>(p.ob) + (blockIdx.x & 15) * (SEQ * 32) + wg * 16 + (tid & 15) +
                              (((blockIdx.x >> 5) * 512 + (kb4 - 2) * 64 + ((tid >> 4) & 7) * 8) * 2 + ((blockIdx.x >> 4) & 1)) * 32;
#define L_PV(g0)                                                                                       \
  _Pragma("unroll") for (int g = (g0); g < (g0) + 4; g++) {                                            \
    const uint4 a = pw[2 * (g & 3)], b = pw[2 * (g & 3) + 1];                                          \
    const uint32_t w[8] = {a.x, a.y, a.z, a.w, b.x, b.y, b.z, b.w};                                    \
    float o0 = 0.f, o1 = 0.f;                                                                          \
    _Pragma("unroll") for (int c = 0; c < 8; c++) {                                                    \
      const uint32_t u = vw[c > g ? c : c + 8];                                                        \
      o0 = fmaf(__uint_as_float(w[c]), __uint_as_float(u << 16), o0);                                  \
      o1 = fmaf(__uint_as_float(w[c]), __uint_as_float(u & 0xFFFF0000u), o1);                          \
    }                                                                                                  \
    dst[g * 64] = pack_bf16(o0, o1);                                                                   \
  }
#pragma unroll
              for (int j = 0; j < 8; j++) pw[j] = lds128(pr + j * 16);
              mbar_arrive_elect(s_bar + B_AEMPTY + 8, true);
              G_STAGE(0)
              L_PV(0)
#pragma unroll
              for (int j = 0; j < 8; j++) pw[j] = lds128(pr + 128 + j * 16);
              G_STAGE(1)
              L_PV(4)
              __syncwarp();
              mbar_arrive_elect(s_bar + B_OFULL, true);
            }
            G_STAGE(2)
            G_STAGE(3)
            gphase ^= 1;
            kb4++;
          }
          const bool fin = next >= 0x600u;
          for (; kb4 < nkb4 - fin; kb4++) {
            G_STAGE(0)
            G_STAGE(1)
            G_STAGE(2)
            G_STAGE_Y(3, false, kb4 + 1 == nkb4, )
            gphase ^= 1;
          }
          if (fin) break;
          wgmma_wait<0>();
          mbar_arrive_cluster_if(s_bar + B_GEMPTY + 8 * 3, etgt, lane == 0 && (warp & 3) < 2);
          {
            const bool gok = mbar_test(s_bar + B_GFULL, gphase);
            fence_regs(acc);
#pragma unroll
            for (int j = 0; j < 64; j++) pk[j] = pack_bf16(acc[2 * j], acc[2 * j + 1]);
            have = item < 0x100u ? 2 : 1;
            item = next;
            TL0(item);
            G_STAGE_Y(0, true, false, )
          }
        }
        {
          constexpr bool gok = false;
          G_STAGE(0)
#if FS == 2
          G_STAGE(1)
#endif
          wgmma_wait<0>();
          mbar_arrive_cluster_if(s_bar + B_GEMPTY + 8 * (FS - 1), etgt, lane == 0 && (warp & 3) < 2);
          fence_regs(acc);
          float lo[64], hi[64];
#pragma unroll
          for (int j = 0; j < 64; j++) {
            asm volatile("mov.b32 %0, %1;" : "=f"(lo[j]) : "f"(acc[j]));
            asm volatile("mov.b32 %0, %1;" : "=f"(hi[j]) : "f"(acc[64 + j]));
          }
#pragma unroll
          for (int s = FS; s < 4; s++) {
            mbar_wait(s_bar + B_GFULL + 8 * s, gphase);
            const uint32_t da = make_desc(DBASE + OFF_A + ((s * 16384) ^ aswz) + wg * 8192, 16);
            const uint32_t db = make_desc(DBASE + (s ^ rot) * TILE32K, 8192);
            if (s == FS) named_bar_sync(5 + wg, 256);
            wgmma_fence();
            wgmma_ss_n128_tb<0, 0>(lo, da, db, 1);
            wgmma_ss_n128_tb<2, 128>(lo, da, db, 1);
            wgmma_ss_n128_tb<4, 256>(lo, da, db, 1);
            wgmma_ss_n128_tb<6, 384>(lo, da, db, 1);
            wgmma_commit();
          }
          wgmma_fence();
#pragma unroll
          for (int s = FS; s < 4; s++) {
            const uint32_t da = make_desc(DBASE + OFF_A + ((s * 16384) ^ aswz) + wg * 8192, 16);
            const uint32_t db = make_desc(DBASE + (s ^ rot) * TILE32K, 8192);
            wgmma_ss_n128_tb<0, 1024>(hi, da, db, 1);
            wgmma_ss_n128_tb<2, 1152>(hi, da, db, 1);
            wgmma_ss_n128_tb<4, 1280>(hi, da, db, 1);
            wgmma_ss_n128_tb<6, 1408>(hi, da, db, 1);
          }
          wgmma_commit();
          named_bar_arrive_if(6, 256, wg == 0);
          gphase ^= 1;
          const uint32_t so = sbase + stg_off(opaque_tid());
          mbar_wait(s_bar + B_STGFREE, stgpar);
          mbar_wait(s_bar + B_SEMPTY + 16 * wg, 1);
          mbar_wait(s_bar + B_SEMPTY + 16 * wg + 8, 1);
#define FIN_HALF(x, base, stride, bar, pub)                                                                                \
  fence_regs(x);                                                                                                      \
  _Pragma("unroll") for (int j = 0; j < 8; j++)                                                                       \
      stmatrix_x4(((base) ^ ((j & 3) << 5)) + (j >> 2) * (stride), pack_bf16(x[8 * j], x[8 * j + 1]),                 \
                  pack_bf16(x[8 * j + 2], x[8 * j + 3]), pack_bf16(x[8 * j + 4], x[8 * j + 5]), pack_bf16(x[8 * j + 6], x[8 * j + 7])); \
  if (pub) FIN_PUBLISH(bar)
#define FIN_PUBLISH(bar)                                   \
  {                                                        \
    fence_proxy_async_smem();                              \
    __syncwarp();                                          \
    mbar_arrive_elect(s_bar + (bar) + 16 * wg, true);      \
    mbar_arrive_elect(s_bar + (bar) + 16 * wg + 8, true);  \
  }
          wgmma_wait<1>();
          FIN_HALF(lo, so + OFF_STG + wg * 8192, 8192, B_SFULL, true)
          wgmma_wait<0>();
          TRI(12, 8);
#pragma unroll
          for (int s = FS; s < 4; s++) mbar_arrive_cluster_if(s_bar + B_GEMPTY + 8 * s, etgt, lane == 0 && (warp & 3) < 2);
          FIN_HALF(hi, so + OFF_A + (32768 ^ aswz), 16384, B_SFULL2, !(seg == 0 && isB && DO_ATT))
          TRI(12, 10);
        }
      }
#ifdef ATT_ONLY
      if (seg == 0) CLUSTER_WAIT();
#endif
      if (seg == 0 && isB && DO_ATT) {
        float o[64], s[64];
        uint32_t pa[32], pb[32];
        undef_regs(o);
        undef_regs(s);
        undef_regs(pa);
        undef_regs(pb);
        uint32_t phase = 0;
        const bool sig = (threadIdx.x & 127) == 0, sig2 = (threadIdx.x & 95) == 0;
#ifndef ATT_ONLY
        FIN_PUBLISH(B_SFULL2)
#endif

#define ISSUE_PV(pr, slot_)                                                             \
  {                                                                                     \
    const uint32_t dv = make_desc(DBASE + (slot_) * TILE32K, 16384);                    \
    if (!phalf) {                                                                       \
      wgmma_fence();                                                                    \
      _Pragma("unroll") for (int k = 0; k < 8; k++)                                     \
          wgmma_rs_n128_tb(o, pr[4 * k], pr[4 * k + 1], pr[4 * k + 2], pr[4 * k + 3], dv + k * 128, (k != 0) || !pfirst); \
      wgmma_commit();                                                                   \
    } else {                                                                            \
      wgmma_fence();                                                                    \
      _Pragma("unroll") for (int k = 0; k < 4; k++)                                     \
          wgmma_rs_n128_tb(o, pr[16 + 4 * k], pr[17 + 4 * k], pr[18 + 4 * k], pr[19 + 4 * k], dv + k * 128, (k != 0) || !pfirst); \
      wgmma_commit();                                                                   \
    }                                                                                   \
  }
#define EPILOGUE(on_)                                                                             \
  _Pragma("unroll") for (int j = 0; j < 8; j++) {                                                 \
    const int b = j * 8;                                                                          \
    stmatrix_x4_p((st_o ^ ((j & 3) << 5)) + (j >> 2) * 16384,                                     \
                  pack_bf16(o[b] * sc0, o[b + 1] * sc0), pack_bf16(o[b + 2] * sc1, o[b + 3] * sc1),   \
                  pack_bf16(o[b + 4] * sc0, o[b + 5] * sc0), pack_bf16(o[b + 6] * sc1, o[b + 7] * sc1), on_); \
  }
#define PUBLISH_O()                                  \
  {                                                  \
    fence_proxy_async_smem();                        \
    __syncwarp();                                    \
    mbar_arrive_elect(s_bar + B_OFULL, true);        \
  }
#define FINAL_SCALE()     \
  {                                                    \
    sc0 = t0 + __shfl_xor_sync(0xffffffffu, t0, 1);    \
    sc1 = t1 + __shfl_xor_sync(0xffffffffu, t1, 1);    \
    t0 = t1 = 0.f;                                     \
    sc0 += __shfl_xor_sync(0xffffffffu, sc0, 2);       \
    sc1 += __shfl_xor_sync(0xffffffffu, sc1, 2);       \
    sc0 = rcp(sc0);            \
    sc1 = rcp(sc1);                                    \
  }
        float l0 = 1.f, l1 = 1.f, t0 = 1.f, t1 = 1.f;
        float b0 = 0.f, b1 = 0.f, sc0 = 0.f, sc1 = 0.f;
        int gen = 0;
        int pfirst = 1;
        int phalf = 2;
        int fresh = 1;
        int diag = blockIdx.x & 1, dlast = !diag;
        int opub = 0;
        int last = 0;
        float rdy;
        float x0 = 0.f, x1 = 0.f, x2 = 0.f, x3 = 0.f;
        bool rs = false;
        uint32_t code = p.order[cluster_id - NA_CL];
        int it = 0, nit = 0, rem = (code & 15) + dlast;
        TL0(0x1000 | code | rem);
        const float mrow = float((warp & 3) * 16 + (lane >> 2) - (lane & 3) * 2);
        const float lo0 = mrow < 0.f && wg == HW ? 0.f : SM_LO;
        const uint32_t st_o = sbase + OFF_STG + stg_off(opaque_tid() ^ (HW * 128));
#define MMA_PART(N_, acc_, PIN, PAR)                                                                       \
  {                                                                                                        \
    const uint32_t dq = make_desc(DBASE + OFF_A + (it & 1) * TILE32K + (wg ^ HW) * 8192, 16);              \
    const uint32_t dk = make_desc(DBASE + (PAR) * TILE32K, 16);                                            \
    TRI(0, fresh ? 7 : 0);                                                                                 \
    named_bar_sync(1 + wg, 256);                                                                           \
    TRI(1, fresh ? 6 : 1);                                                                                 \
    wgmma_fence();                                                                                         \
    uint32_t cv;                                                                                           \
    bool rv;                                                                                               \
    _Pragma("unroll") for (int k = 0; k < 8; k++) {                                                        \
      wgmma_ss_n##N_(acc_, dq + (k >> 2) * 1024 + (k & 3) * 2, dk + (k >> 2) * 1024 + (k & 3) * 2, k != 0); \
      if (k == 1) cv = lds32(s_bar + S_CODE + 4 * ((it + 1) & 7));        \
      if (k == 3) rv = mbar_test(s_bar + B_AFULL + 8 * (3 - (PAR)), phase ^ (1 - (PAR)));                  \
    }                                                                                                      \
    wgmma_commit();                                                                                        \
    code = __reduce_or_sync(0xffffffffu, cv);                                                              \
    if (opub) PUBLISH_O();                                                                                 \
    if (N_ == 128 && fresh) FINAL_SCALE();                                                                 \
    last = rem == 0 && (code & 0x8000u);                                                                   \
    nit = it + (rem == 0 && !last);                                                                        \
    mbar_wait_rest(s_bar + B_AFULL + 8 * (3 - (PAR)), phase ^ (1 - (PAR)), rv);                            \
    ISSUE_PV(PIN, 3 - (PAR));                                                                              \
    named_bar_arrive(2 - wg, 256);                                                                         \
    TR(2);                                                                                                 \
    wgmma_wait<1>();                                                                                       \
    fence_regs(acc_);                                                                                      \
    TR(3);                                                                                                 \
    mbar_arrive_cluster_if(s_bar + B_AEMPTY + 8 * (PAR), etgt, sig2);                                      \
    mbar_arrive_if(s_bar + B_QEMPTY + 8 * (it & 1), sig && rem == 0);                                      \
    if (N_ == 64 && fresh) FINAL_SCALE();                                                                  \
    l0 = t0;                                                                                               \
    l1 = t1;                                                                                               \
  }
#define LOW_SUM() ((t0 < lo0) | (t1 < SM_LO))
#define SECOND_HALF(POUT, PAR, FRESH, ...)                                                                 \
  wgmma_wait<0>();                                                                                         \
  fence_regs(o);                                                                                           \
  mbar_arrive_cluster_if(s_bar + B_AEMPTY + 8 * (3 - (PAR)), etgt, sig2 && ((PAR) || !(FRESH) || it > 0)); \
  TR(8);                                                                                                   \
  __VA_ARGS__;                                                                                             \
  t0 += x0 + x1;                                                                                           \
  t1 += x2 + x3;                                                                                           \
  POUT[16] = pack_bf16(x0, x1);                                                                            \
  POUT[17] = pack_bf16(x2, x3);                                                                            \
  softmax_exp<9, ZPOS, false>(s, 0.f, 0.f, POUT, t0, t1);                                                  \
  {                                                                                                        \
           \
    const uint32_t z = (__float_as_uint(t0) | __float_as_uint(t1)) >> 31;                                  \
    rdy = mbar_test2(s_bar + B_AFULL + 8 * (1 - (PAR)), (phase ^ (PAR)) + z, s_bar + B_QFULL + 8 * (nit & 1), ((nit >> 1) & 1) + z); \
  }                                                                                                        \
  softmax_exp<ZPOS, TPOS, false>(s, 0.f, 0.f, POUT, t0, t1);                                               \
  t0 = addv(t0, rdy);                                                                                      \
  softmax_exp<TPOS, 16, false>(s, 0.f, 0.f, POUT, t0, t1);                                                 \
                                                                                \
  phalf = diag && wg == HW;                                                                                \
  opub = (FRESH) && it > 0;                                                                                \
  pfirst = FRESH;                                                                                          \
  fresh = rem == 0;                                                                                        \
  it = nit;                                                                                                \
  rem = fresh ? (code & 15) + ((blockIdx.x ^ ~it) & 1) : rem - 1;                                          \
  dlast = !((blockIdx.x | it) & 1);                                                                        \
  diag = dlast ? rem == 0 : fresh;                                                                         \
  if (fresh && !last) { TL0(0x1000 | code | rem); }                                                        \
  if (PAR) phase ^= 1;                                                                                     \
                                                      \
  const float lim = __uint_as_float(__float_as_uint(last ? -1.f : SM_HI) | __float_as_uint(rdy));   \
  TR(4);
#ifndef TPOS
#define TPOS 15
#define ZPOS 13
#endif
#define TEST_STG() rs = mbar_test(s_bar + B_STGFREE, ~it & 1) | (it == 0);
#define SHIFT_S(j0_)                                                                                       \
  if (gen) { _Pragma("unroll") for (int j = (j0_); j < 64; j++) s[j] += (j & 2) ? b1 : b0; }
#define NEXT_STEP(NEXT, LOW)                                                                               \
  if (!__any_sync(0xffffffffu, !(t0 + t1 <= (diag && wg == HW ? -1.f : lim)) | (LOW))) goto plain##NEXT;   \
  if (!__any_sync(0xffffffffu, !(t0 + t1 <= lim) | (LOW))) goto half##NEXT;
#define STEP_END(POUT, PAR, NEXT, ...)                                                                     \
  if (fresh) {                                                                                             \
    __VA_ARGS__;                                                                                           \
    mbar_wait_rest(s_bar + B_STGFREE, ~it & 1, rs);                                                        \
    SECOND_HALF(POUT, PAR, 1, EPILOGUE(it > 0))                                                            \
    if (phalf && opub) {                                                     \
      PUBLISH_O();                                                                                         \
      opub = 0;                                                                                            \
    }                                                                                                      \
    NEXT_STEP(NEXT, LOW_SUM())                                                                             \
  } else {                                                                                                 \
    SECOND_HALF(POUT, PAR, 0, )                                                                            \
    NEXT_STEP(NEXT, false)                                                                                 \
  }
#define STEP_BEGIN(PIN, POUT, PAR, ...)                                                                    \
  {                                                                                                        \
    if (__any_sync(0xffffffffu, !(t0 + t1 <= SM_HI) | (LOW_SUM() & (pfirst != 0)))) {                           \
              \
      if (phalf) { _Pragma("unroll") for (int j = 0; j < 32; j++) asm volatile("mov.b32 %0, 0xff800000;" : "=f"(s[j])); } \
      float d0, d1;                                                                                        \
      softmax_max(s, d0, d1);                                                                              \
      if (!pfirst) {                                                                                       \
        d0 = fmaxf(d0, 0.f);                                                                               \
        d1 = fmaxf(d1, 0.f);                                                                               \
      }                                                                                                    \
      const float r0 = pfirst ? 1.f : ex2(-d0), r1 = pfirst ? 1.f : ex2(-d1);                              \
      t0 = l0 * r0;                                                                                        \
      t1 = l1 * r1;                                                                                        \
      softmax_exp<0, 16, true>(s, -d0, -d1, PIN, t0, t1);                                                  \
      b0 -= d0;                                                                                            \
      b1 -= d1;                                                                                            \
      gen = 1;                                                                                             \
      _Pragma("unroll") for (int j = 0; j < 16; j++) {                                                     \
        o[4 * j] *= r0;                                                                                    \
        o[4 * j + 1] *= r0;                                                                                \
        o[4 * j + 2] *= r1;                                                                                \
        o[4 * j + 3] *= r1;                                                                                \
      }                                                                                                    \
    }                                                                                                      \
    if (last) {                                                                                            \
      __VA_ARGS__;                                                                                         \
      break;                                                                                               \
    }                                                                                                      \
  }                                                                                                        \
  inputs##PAR:                                                                                             \
  {                                                                                                        \
    const bool rq = mbar_test(s_bar + B_QFULL + 8 * (it & 1), (it >> 1) & 1);                              \
    mbar_wait(s_bar + B_AFULL + 8 * (PAR), phase);                                                         \
    mbar_wait_rest(s_bar + B_QFULL + 8 * (it & 1), (it >> 1) & 1, rq);                                     \
  }                                                                                                        \
  if (diag && wg == HW) {                                                                                  \
  half##PAR:                                                                                               \
                                                     \
    float sl[32];                                                                                          \
    undef_regs(sl);                                                                                        \
    MMA_PART(64, sl, PIN, PAR)                                                                             \
    _Pragma("unroll") for (int j = 0; j < 32; j++) asm volatile("mov.b32 %0, %1;" : "=f"(s[32 + j]) : "f"(sl[j])); \
    SHIFT_S(32)                                                                                            \
    TEST_STG()                                                                                             \
    _Pragma("unroll") for (int j = 0; j < 8; j++) {                                                        \
      if (float(8 * j) > mrow) s[32 + 4 * j] = -3e38f;                                                     \
      if (float(8 * j + 1) > mrow) s[33 + 4 * j] = -3e38f;                                                 \
      if (float(8 * j - 8) > mrow) s[34 + 4 * j] = -3e38f;                                                 \
      if (float(8 * j - 7) > mrow) s[35 + 4 * j] = -3e38f;                                                 \
    }                                                                                                      \
    x0 = ex2v(s[32]), x1 = ex2v(s[33]), x2 = ex2v(s[34]), x3 = ex2v(s[35]);                                \
  } else {                                                                                                 \
  plain##PAR:                                                                                              \
    MMA_PART(128, s, PIN, PAR)                                                                             \
    if (diag || gen) {                                                                                     \
      SHIFT_S(0)                                                                                           \
                                     \
      TEST_STG()                                                                                           \
      const float rowf = diag ? mrow : 64.f;                                                               \
      _Pragma("unroll") for (int j = 0; j < 8; j++) {                                                      \
        s[32 + 4 * j] = fmaf(__saturatef(float(8 * j) - rowf), -3e38f, s[32 + 4 * j]);                     \
        s[33 + 4 * j] = fmaf(__saturatef(float(8 * j + 1) - rowf), -3e38f, s[33 + 4 * j]);                 \
        s[34 + 4 * j] = fmaf(__saturatef(float(8 * j - 8) - rowf), -3e38f, s[34 + 4 * j]);                 \
        s[35 + 4 * j] = fmaf(__saturatef(float(8 * j - 7) - rowf), -3e38f, s[35 + 4 * j]);                 \
      }                                                                                                    \
      softmax_exp<0, 8, false>(s, 0.f, 0.f, POUT, t0, t1);                                                 \
      x0 = ex2v(s[32]), x1 = ex2v(s[33]), x2 = ex2v(s[34]), x3 = ex2v(s[35]);                              \
    } else {                                                                                               \
      TEST_STG()                                                                                           \
      softmax_exp<0, 8, false>(s, 0.f, 0.f, POUT, t0, t1);                                                 \
      x0 = ex2v(s[32]), x1 = ex2v(s[33]), x2 = ex2v(s[34]), x3 = ex2v(s[35]);                              \
    }                                                                                                      \
  }
        for (;;) {
          STEP_END(pa, 1, 0, if (phalf == 2) { wgmma_wait<0>(); goto inputs0; })
          STEP_BEGIN(pa, pb, 0, rot = 0; phase ^= 1)
          STEP_END(pb, 0, 1, )
          STEP_BEGIN(pb, pa, 1, rot = 1; _Pragma("unroll") for (int j = 0; j < 32; j++) asm volatile("mov.b32 %0, %1;" : "=r"(pa[j]) : "r"(pb[j])))
        }
        {
          mbar_wait(s_bar + B_AFULL + 8 * (3 - rot), phase);
          TRI(12, 2);
          ISSUE_PV(pa, 3 - rot);
          if (opub) PUBLISH_O();
          FINAL_SCALE();
          mbar_wait(s_bar + B_STGFREE, it & 1);
          wgmma_wait<0>();
          fence_regs(o);
          TRI(12, 4);
          mbar_arrive_cluster_if(s_bar + B_AEMPTY + 8 * (3 - rot), etgt, sig2);
          EPILOGUE(true);
          PUBLISH_O();
          TRI(12, 5);
          stgpar = ~it & 1;
          tail = tail_item(code);
          aswz = (~it & 1) * TILE32K;
          rot ^= blockIdx.x & ~it & 1;
        }
      }
    }
    TL0(0xFFFF);
    TRI(15, 15);
  }
}

typedef CUresult (*EncodeFn)(CUtensorMap*, CUtensorMapDataType, cuuint32_t, void*, const cuuint64_t*,
                             const cuuint64_t*, const cuuint32_t*, const cuuint32_t*, CUtensorMapInterleave,
                             CUtensorMapSwizzle, CUtensorMapL2promotion, CUtensorMapFloatOOBfill);

EncodeFn get_encode() {
  static EncodeFn fn = nullptr;
  if (!fn) {
    void* p = nullptr;
    cudaDriverEntryPointQueryResult st;
    cudaGetDriverEntryPoint("cuTensorMapEncodeTiled", &p, cudaEnableDefault, &st);
    fn = (EncodeFn)p;
  }
  return fn;
}

void make_map(CUtensorMap* m, const void* ptr, int rows, int cols, int box_rows, int box_groups, bool blocked = false) {
  cuuint64_t dims[3] = {64, (cuuint64_t)rows, (cuuint64_t)(cols / 64)};
  cuuint64_t strides[2] = {(cuuint64_t)(blocked ? 128 : cols * 2), (cuuint64_t)(blocked ? rows * 128 : 128)};
  cuuint32_t box[3] = {64, (cuuint32_t)box_rows, (cuuint32_t)box_groups};
  cuuint32_t es[3] = {1, 1, 1};
  CUtensorMapL2promotion prom = blocked || box_groups == 1 ? CU_TENSOR_MAP_L2_PROMOTION_NONE : CU_TENSOR_MAP_L2_PROMOTION_L2_256B;
  get_encode()(m, CU_TENSOR_MAP_DATA_TYPE_BFLOAT16, 3, const_cast<void*>(ptr), dims, strides, box, es,
               CU_TENSOR_MAP_INTERLEAVE_NONE, CU_TENSOR_MAP_SWIZZLE_128B, prom,
               CU_TENSOR_MAP_FLOAT_OOB_FILL_NONE);
}

void make_store_map(CUtensorMap* m, const void* ptr, int cols, uint64_t s_par, uint64_t s_pair, uint64_t s_grp) {
  cuuint64_t dims[4] = {64, 2, SEQ / 2, (cuuint64_t)(cols / 64)};
  cuuint64_t strides[3] = {s_par, s_pair, s_grp};
  cuuint32_t box[4] = {64, 2, 32, 1};
  cuuint32_t es[4] = {1, 1, 1, 1};
  get_encode()(m, CU_TENSOR_MAP_DATA_TYPE_BFLOAT16, 4, const_cast<void*>(ptr), dims, strides, box, es,
               CU_TENSOR_MAP_INTERLEAVE_NONE, CU_TENSOR_MAP_SWIZZLE_128B, CU_TENSOR_MAP_L2_PROMOTION_NONE,
               CU_TENSOR_MAP_FLOAT_OOB_FILL_NONE);
}

#ifdef SCHED_PRINT
static int envi(const char* n, int d) { const char* e = getenv(n); return e ? (int)strtol(e, 0, 0) : d; }
#define PARAM(name, val) const int name = envi(#name, val)
#else
#define PARAM(name, val) const int name = val
#endif
void build_schedule(Params& p) {
  PARAM(C_KB, 1028);
  PARAM(C_TILE, 10);
  PARAM(C_QX, 0);
  PARAM(C_START, 4500);
  PARAM(C_STEP, 2052);
  PARAM(C_ITEM, 300);
  PARAM(C_LAG, 8000);
  PARAM(C_SP, 5200);
  PARAM(C_TAIL, 22000);
  PARAM(C_SHORT, 0);
  PARAM(C_AT, 72);
  PARAM(C_LATE, 0);
  PARAM(C_LMASK, 0xAA0);
  PARAM(C_AM, 100);
  PARAM(C_ODD, 1300);
  PARAM(C_READY, 10000);
  auto gemm_cost = [&](int prob) {
    static const int nkb[NPROB] = {16, 8, 8, 16, 64, 16};
    return nkb[prob] * C_KB + C_TILE + (prob == 0 ? C_QX : 0);
  };
  memset(p.g, 0xFF, sizeof(p.g));
  int n1[NCLUSTER];
  long t1[NCLUSTER];
  long ready[16];
  for (int c = 0; c < NCLUSTER; c++) { n1[c] = 0; t1[c] = C_START; }
  for (int i = 0; i < 16; i++) ready[i] = 0;
  auto add = [&](int c, int prob, int mp, int nt) {
    p.g[c][n1[c]++] = (uint16_t)((prob << 8) | (mp << 4) | nt);
    t1[c] += gemm_cost(prob);
    if (prob < 3) {
      const long r = t1[c] + C_READY;
      if (r > ready[nt]) ready[nt] = r;
    }
  };
#ifdef GEMM_ONLY
  for (int c = 0; c < NCLUSTER; c++) {
    for (int i = 0; i < 13; i++) add(c, 0, c & 7, (i + (c >> 3) * 2) & 15);
    p.g[c][n1[c]++] = 0x600;
  }
  return;
#endif
#ifdef ATT_ONLY
  for (int c = 0; c < NCLUSTER; c++) { p.g[c][0] = 0x600; p.g[c][1] = 0x500; }
  for (int i = 0; i < 256; i++) p.order[i] = (uint16_t)(((i & 31) << 4) | (14 - 2 * (i >> 5)));
  return;
#endif
  for (int r = 0; r < 8; r++)
    for (int c = 0; c < NA_CL; c++) {
      const int mp = c & 7, nt = 2 * r + ((c >> 3) & 1);
      for (int j = 0; j < (c < 16 ? 1 : 2); j++) {
        add(c, c < 16 ? 0 : 1 + j, mp, nt);
      }
    }
  long tA = 0;
  for (int c = 0; c < NA_CL; c++) {
    if (t1[c] > tA) tA = t1[c];
    add(c, 4, c & 7, c >> 3);
  }
  for (int r = 0; r < 3; r++)
    for (int j = 0; j < 34; j++) {
      if (j >= 32) { if (r < 2) add(NA_CL + j, 3, j & 7, 4 + r); }
      else if (r < 2 || j >= 16 || (j & 7) >= 2) add(NA_CL + j, 3, j & 7, (j >> 3) + (r == 0 ? 0 : r == 1 ? 8 : 4));
    }
  for (int c = NA_CL; c < NCLUSTER; c++) {
    p.g[c][n1[c]++] = 0x600;
    p.g[c][n1[c]++] = 0x500;
  }
  static const uint16_t order[256] = {
    14, 30, 10, 44, 26, 78, 60, 94, 12, 46, 8, 42, 24, 76, 58, 110, 92, 6, 126, 40, 22, 74, 56, 108,
    90, 4, 124, 38, 20, 72, 54, 106, 28, 62, 142, 158, 88, 2, 140, 122, 36, 18, 174, 156, 70, 52, 190, 104,
    86, 0, 138, 120, 34, 16, 172, 154, 68, 50, 206, 188, 102, 84, 222, 136, 118, 32, 170, 152, 66, 48, 204, 186,
    100, 82, 238, 220, 134, 116, 254, 168, 150, 64, 202, 184, 98, 80, 236, 218, 132, 114, 270, 252, 166, 148, 286, 200,
    182, 96, 234, 216, 130, 112, 268, 250, 164, 146, 302, 284, 198, 180, 318, 232, 214, 128, 266, 248, 162, 144, 300, 282,
    196, 178, 334, 316, 230, 212, 350, 264, 246, 160, 310, 328, 382, 194, 314, 360, 192, 340, 278, 298, 274, 208, 342, 366,
    210, 260, 290, 312, 336, 378, 306, 292, 240, 330, 364, 224, 228, 346, 380, 434, 376, 244, 362, 226, 344, 348, 408, 272,
    304, 176, 320, 368, 280, 412, 390, 332, 262, 288, 258, 256, 242, 402, 294, 388, 422, 296, 406, 398, 384, 374, 326, 352,
    400, 414, 394, 276, 322, 418, 392, 396, 370, 356, 324, 410, 386, 430, 462, 494, 446, 510, 478, 484, 482, 354, 498, 404,
    308, 416, 428, 492, 508, 460, 476, 444, 452, 358, 426, 372, 490, 506, 458, 442, 474, 338, 424, 472, 456, 440, 488, 454,
    450, 438, 470, 486, 420, 436, 468, 500, 504, 466, 502, 448, 496, 432, 480, 464,
  };
  memcpy(p.order, order, sizeof(order));
#ifdef SCHED_PRINT
  uint16_t fixed[256];
  memcpy(fixed, p.order, sizeof(fixed));
  long tf[NB_CL];
  bool done[512], started[NB_CL];
  long fin[16];
  int cnt[NB_CL] = {};
  for (int c = 0; c < NB_CL; c++) { tf[c] = t1[NA_CL + c] + 2000; started[c] = false; }
  for (int i = 0; i < 512; i++) done[i] = i & 1;
  for (int i = 0; i < 16; i++) fin[i] = 0;
  auto alen = [&](int qt) { return (long)(2 * qt + 3) * C_STEP / 2 + C_ITEM + (qt < 2 ? C_SHORT : 0); };
  int nq = NB_CL;
  for (int n = 0; n < 256; n++) {
    int cb = 0;
    for (int c = 1; c < NB_CL; c++)
      if (tf[c] < tf[cb]) cb = c;
    int best = -1;
    long bkey = 0;
    for (int i = 0; i < 512; i++) {
      if (done[i]) continue;
      const int hp = i >> 5;
      long dl = -(long)(16 - hp) * C_SP - C_LAG + ((i >> 4) & 1) * C_ODD;
      if (dl > -C_TAIL) dl = -C_TAIL;
      long key = dl - alen(i & 15) * (dl == -C_TAIL ? C_AT : C_AM) / 100;
      if ((i >> 4) == 31 && (C_LMASK >> (i & 15) & 1)) key += C_LATE;
      if (ready[hp] > tf[cb]) key += (1L << 40) + (ready[hp] - tf[cb]) * 1024;
      if (best < 0 || key < bkey) { best = i; bkey = key; }
    }
    done[best] = true;
    if (!started[cb]) { p.order[cb] = (uint16_t)best; started[cb] = true; }
    else p.order[nq++] = (uint16_t)best;
    if (ready[best >> 5] > tf[cb]) tf[cb] = ready[best >> 5];
    tf[cb] += alen(best & 15) + (cnt[cb]++ & 1 ? -C_STEP / 2 : C_STEP / 2);
    if (tf[cb] + C_LAG > fin[best >> 5]) fin[best >> 5] = tf[cb] + C_LAG;
  }
  if (!getenv("HEUR")) memcpy(p.order, fixed, sizeof(fixed));
#endif
#ifdef SCHED_PRINT
  ord_hook(p.order);
  long t = tA, tmin = tf[0], tmax = tf[0];
  printf("sched: outA start %ld, fin:", t);
  for (int hp = 0; hp < 16; hp++) {
    printf(" %ld", fin[hp] - t);
    if (fin[hp] > t) t = fin[hp];
    t += 4 * C_KB;
  }
  for (int c = 0; c < NB_CL; c++) { if (tf[c] < tmin) tmin = tf[c]; if (tf[c] > tmax) tmax = tf[c]; }
  printf("\nA end %ld, attention end %ld..%ld (+%d), ready[15] %ld nq %d\n", t, tmin, tmax, gemm_cost(5), ready[15], nq);
#endif
}

}

extern "C" void kernel_launch(void* const* d_in, const int* in_sizes, int n_in, void* d_out, int out_size) {
  const bf16* A_x = (const bf16*)d_in[0];
  const bf16* A_c = (const bf16*)d_in[1];
  const bf16* A_wq = (const bf16*)d_in[2];
  const bf16* A_wuk = (const bf16*)d_in[3];
  const bf16* A_wuv = (const bf16*)d_in[4];
  const bf16* A_wo = (const bf16*)d_in[5];
  const bf16* B_x = (const bf16*)d_in[6];
  const bf16* B_wqkv = (const bf16*)d_in[7];
  const bf16* B_wo = (const bf16*)d_in[8];
  bf16* out = (bf16*)d_out;

  static Params p;
  static bf16 *q, *k, *v, *ctx, *qkvb, *ob;
  static bool init = false;
  if (!init) {
    cudaGetSymbolAddress((void**)&q, g_q);
    cudaGetSymbolAddress((void**)&k, g_k);
    cudaGetSymbolAddress((void**)&v, g_v);
    cudaGetSymbolAddress((void**)&qkvb, g_qkvb);
    cudaGetSymbolAddress((void**)&ob, g_ob);
    cudaFuncSetAttribute(mega_kernel, cudaFuncAttributeMaxDynamicSharedMemorySize, SMEM_BYTES);
    build_schedule(p);
    ctx = q;
    init = true;
  }
  make_map(&p.ta[0], A_x, SEQ, DM, 128, 1);
  make_map(&p.tb[0], A_wq, DM, HHD, 64, 2);
  make_store_map(&p.tc[0], q, HHD, 128, 256, SEQ * 128);
  make_map(&p.ta[1], A_c, SEQ, DC, 128, 1);
  make_map(&p.tb[1], A_wuk, DC, HHD, 64, 2);
  make_store_map(&p.tc[1], k, HHD, 128, 256, SEQ * 128);
  make_map(&p.ta[2], A_c, SEQ, DC, 128, 1);
  make_map(&p.tb[2], A_wuv, DC, HHD, 64, 2);
  make_store_map(&p.tc[2], v, HHD, 128, 256, SEQ * 128);
  make_map(&p.ta[3], B_x, SEQ, DM, 128, 1);
  make_map(&p.tb[3], B_wqkv, DM, 3 * DM, 64, 2);
  make_store_map(&p.tc[3], qkvb, 3 * DM, SEQ * 64, 128, SEQ * 128);
  make_map(&p.ta[4], ctx, SEQ, HHD, 128, 1, true);
  make_map(&p.tb[4], A_wo, HHD, DM, 64, 2);
  make_store_map(&p.tc[4], out, 2 * DM, 4 * DM, 8 * DM, 128);
  make_map(&p.ta[5], ob, SEQ, DM, 128, 1, true);
  make_map(&p.tb[5], B_wo, DM, DM, 64, 2);
  make_store_map(&p.tc[5], out, 2 * DM, 4 * DM, 8 * DM, 128);
  make_map(&p.tq, q, SEQ, HHD, 128, 2, true);
  make_map(&p.tk, k, SEQ, HHD, 128, 1, true);
  make_map(&p.tv, v, SEQ, HHD, 128, 1, true);
  make_map(&p.tl, qkvb, SEQ / 2, 6 * DM, 64, 1, true);
  make_map(&p.th, qkvb, SEQ / 2, 6 * DM, 72, 1, true);
  make_map(&p.to, ctx, SEQ, HHD, 128, 2, true);
  p.ob = ob;
  mega_kernel<<<NCTA, 384, SMEM_BYTES, cudaStreamPerThread>>>(p);
}
```

```cpp
#include <cuda_runtime.h>
#include <cuda_bf16.h>
#include <cuda.h>
#include <stdint.h>
#include <string.h>

namespace {

typedef __nv_bfloat16 bf16;

constexpr int SEQ = 2048;
constexpr int NHEAD = 32;
constexpr int HD = 128;
constexpr int DM = 1024;
constexpr int DC = 512;
constexpr int HHD = NHEAD * HD;

__device__ __align__(1024) bf16 g_q[SEQ * HHD];
__device__ __align__(1024) bf16 g_k[SEQ * HHD];
__device__ __align__(1024) bf16 g_v[SEQ * HHD];
__device__ __align__(1024) bf16 g_qkvb[SEQ * 3 * DM];
__device__ __align__(1024) bf16 g_ob[SEQ * DM];
constexpr int CNT_QKV = 0, CNT_CTX = 16, CNT_QKVB = 32, CNT_DONE = 33, CNT_QUEUE = 34, CNT_OB = 35, CNT_N = 39;
__device__ uint32_t g_cnt[CNT_N * 8];
#ifdef TIMELINE
__device__ __align__(16) unsigned long long g_tl[132 * 4 * 64];
#endif


__device__ __forceinline__ uint32_t smem_u32(const void* p) {
  return static_cast<uint32_t>(__cvta_generic_to_shared(p));
}
__device__ __forceinline__ void mbar_init(uint32_t bar, uint32_t count) {
  asm volatile("mbarrier.init.shared::cta.b64 [%0], %1;" ::"r"(bar), "r"(count) : "memory");
}
__device__ __forceinline__ void mbar_expect_tx(uint32_t bar, uint32_t bytes) {
  asm volatile("mbarrier.arrive.expect_tx.shared::cta.b64 _, [%0], %1;" ::"r"(bar), "r"(bytes) : "memory");
}
__device__ __forceinline__ void mbar_arrive(uint32_t bar) {
  asm volatile("mbarrier.arrive.shared::cta.b64 _, [%0];" ::"r"(bar) : "memory");
}
__device__ __forceinline__ void mbar_arrive_if(uint32_t bar, bool on) {
  asm volatile("{\n.reg .pred p;\nsetp.ne.b32 p, %1, 0;\n@p mbarrier.arrive.shared::cta.b64 _, [%0];\n}" ::"r"(bar),
               "r"((int)on)
               : "memory");
}
__device__ __forceinline__ void mbar_arrive_cluster_if(uint32_t bar, uint32_t cta, bool on) {
  asm volatile(
      "{\n.reg .b32 ra;\n.reg .pred p;\nsetp.ne.b32 p, %2, 0;\nmapa.shared::cluster.u32 ra, %0, %1;\n"
      "@p mbarrier.arrive.shared::cluster.b64 _, [ra];\n}" ::"r"(bar),
      "r"(cta), "r"((int)on)
      : "memory");
}
__device__ __forceinline__ bool mbar_try_wait(uint32_t bar, uint32_t parity) {
  uint32_t ok;
  asm volatile(
      "{\n.reg .pred p;\nmbarrier.try_wait.parity.shared::cta.b64 p, [%1], %2;\nselp.u32 %0, 1, 0, p;\n}"
      : "=r"(ok)
      : "r"(bar), "r"(parity)
      : "memory");
  return ok != 0;
}
__device__ __forceinline__ bool mbar_test(uint32_t bar, uint32_t parity) {
  uint32_t ok;
  asm volatile(
      "{\n.reg .pred p;\nmbarrier.test_wait.parity.shared::cta.b64 p, [%1], %2;\nselp.u32 %0, 1, 0, p;\n}"
      : "=r"(ok)
      : "r"(bar), "r"(parity)
      : "memory");
  return ok != 0;
}
#ifdef DBGW
__device__ uint32_t* g_dbg;
__device__ __forceinline__ void mbar_wait_l(uint32_t bar, uint32_t parity, int line) {
  uint32_t t0 = clock();
  bool rec = false;
  while (!mbar_try_wait(bar, parity)) {
    uint32_t d = clock() - t0;
    if (d > (1u << 26) && !rec) { rec = true; g_dbg[blockIdx.x * 16 + (threadIdx.x >> 5)] = (bar & 1023) | (parity << 12) | (line << 16); __threadfence_system(); }
    if (d > (1u << 28)) __trap();
  }
}
#define mbar_wait(b, p) mbar_wait_l(b, p, __LINE__)
#define DBG(i, v) *(volatile uint32_t*)(g_dbg + blockIdx.x * 16 + (i)) = (v)
__device__ __forceinline__ void mbar_wait_unused(uint32_t bar, uint32_t parity) {
#else
#define DBG(i, v)
__device__ __forceinline__ void mbar_wait(uint32_t bar, uint32_t parity) {
#endif
  asm volatile(
      "{\n.reg .pred p;\n.reg .u32 t;\n"
      "mbarrier.try_wait.parity.shared::cta.b64 p, [%0], %1;\n"
      "@p bra DONE;\n"
      "mov.u32 t, 0x100000;\n"
      "LAB_WAIT:\n"
      "mbarrier.try_wait.parity.shared::cta.b64 p, [%0], %1;\n"
      "@p bra DONE;\n"
      "sub.u32 t, t, 1;\n"
      "setp.ne.u32 p, t, 0;\n"
      "@p bra LAB_WAIT;\n"
      "trap;\n"
      "DONE:\n}" ::"r"(bar),
      "r"(parity)
      : "memory");
}
constexpr uint64_t EV_NORMAL = 0x1000000000000000ull;
__device__ __forceinline__ uint64_t policy_first() {
  uint64_t p;
  asm("createpolicy.fractional.L2::evict_first.b64 %0, 1.0;" : "=l"(p));
  return p;
}
#define EV_FIRST policy_first()
__device__ __forceinline__ void tma_load_3d(uint32_t dst, const CUtensorMap* map, int c0, int c1, int c2,
                                            uint32_t bar, uint64_t hint) {
  asm volatile(
      "cp.async.bulk.tensor.3d.shared::cluster.global.mbarrier::complete_tx::bytes.L2::cache_hint [%0], [%1, {%3, %4, %5}], [%2], %6;" ::"r"(dst),
      "l"(map), "r"(bar), "r"(c0), "r"(c1), "r"(c2), "l"(hint)
      : "memory");
}
__device__ __forceinline__ void tma_load_3d_mc(uint32_t dst, const CUtensorMap* map, int c0, int c1, int c2,
                                               uint32_t bar, uint16_t mask, uint64_t hint) {
  asm volatile(
      "cp.async.bulk.tensor.3d.shared::cluster.global.mbarrier::complete_tx::bytes.multicast::cluster.L2::cache_hint [%0], [%1, {%3, %4, %5}], [%2], %6, %7;" ::"r"(dst),
      "l"(map), "r"(bar), "r"(c0), "r"(c1), "r"(c2), "h"(mask), "l"(hint)
      : "memory");
}
__device__ __forceinline__ void tma_store_3d(const CUtensorMap* map, uint32_t src, int c0, int c1, int c2, uint64_t hint) {
  asm volatile("cp.async.bulk.tensor.3d.global.shared::cta.bulk_group.L2::cache_hint [%0, {%2, %3, %4}], [%1], %5;" ::"l"(map),
               "r"(src), "r"(c0), "r"(c1), "r"(c2), "l"(hint)
               : "memory");
}
__device__ __forceinline__ void tma_store_4d(const CUtensorMap* map, uint32_t src, int c2, int c3, uint64_t hint) {
  asm volatile("cp.async.bulk.tensor.4d.global.shared::cta.bulk_group.L2::cache_hint [%0, {%2, %2, %3, %4}], [%1], %5;" ::"l"(map),
               "r"(src), "r"(0), "r"(c2), "r"(c3), "l"(hint)
               : "memory");
}
__device__ __forceinline__ void bulk_commit() { asm volatile("cp.async.bulk.commit_group;" ::: "memory"); }
template <int N>
__device__ __forceinline__ void bulk_wait_read() {
  asm volatile("cp.async.bulk.wait_group.read %0;" ::"n"(N) : "memory");
}
template <int N>
__device__ __forceinline__ void bulk_wait() {
  asm volatile("cp.async.bulk.wait_group %0;" ::"n"(N) : "memory");
}
__device__ __forceinline__ void fence_proxy_async_smem() {
  asm volatile("fence.proxy.async.shared::cta;" ::: "memory");
}
__device__ __forceinline__ void prefetch_tmap(const CUtensorMap* map) {
  asm volatile("prefetch.tensormap [%0];" ::"l"(map) : "memory");
}
__device__ __forceinline__ bool elect_one() {
  uint32_t pred;
  asm volatile("{\n.reg .pred P;\nelect.sync _|P, 0xffffffff;\nselp.b32 %0, 1, 0, P;\n}" : "=r"(pred));
  return pred != 0;
}
__device__ __forceinline__ void named_bar_sync(int id, int n) {
  asm volatile("bar.sync %0, %1;" ::"r"(id), "r"(n) : "memory");
}
__device__ __forceinline__ void named_bar_arrive(int id, int n) {
  asm volatile("bar.arrive %0, %1;" ::"r"(id), "r"(n) : "memory");
}
__device__ __forceinline__ void named_bar_sync_if(int id, int n, bool on) {
  asm volatile("{\n.reg .pred p;\nsetp.ne.b32 p, %2, 0;\n@p bar.sync %0, %1;\n}" ::"r"(id), "r"(n), "r"((int)on) : "memory");
}
__device__ __forceinline__ void named_bar_arrive_if(int id, int n, bool on) {
  asm volatile("{\n.reg .pred p;\nsetp.ne.b32 p, %2, 0;\n@p bar.arrive %0, %1;\n}" ::"r"(id), "r"(n), "r"((int)on) : "memory");
}
template <int N>
__device__ __forceinline__ void reg_alloc() {
  asm volatile("setmaxnreg.inc.sync.aligned.u32 %0;" ::"n"(N));
}
template <int N>
__device__ __forceinline__ void reg_dealloc() {
  asm volatile("setmaxnreg.dec.sync.aligned.u32 %0;" ::"n"(N));
}
__device__ __forceinline__ void wgmma_fence() { asm volatile("wgmma.fence.sync.aligned;" ::: "memory"); }
__device__ __forceinline__ void wgmma_commit() { asm volatile("wgmma.commit_group.sync.aligned;" ::: "memory"); }
template <int N>
__device__ __forceinline__ void wgmma_wait() {
  asm volatile("wgmma.wait_group.sync.aligned %0;" ::"n"(N) : "memory");
}
template <int N>
__device__ __forceinline__ void fence_regs(float (&d)[N]) {
#pragma unroll
  for (int i = 0; i < N; i++) asm volatile("" : "+f"(d[i])::"memory");
}
__device__ __forceinline__ void fence_regs(uint32_t (&d)[32]) {
#pragma unroll
  for (int i = 0; i < 16; i++) asm volatile("" : "+r"(d[i])::"memory");
}
template <int N>
__device__ __forceinline__ void undef_regs(float (&d)[N]) {
#pragma unroll
  for (int i = 0; i < N; i++) d[i] = 0.f;
}
template <int N>
__device__ __forceinline__ void undef_regs(uint32_t (&d)[N]) {
#pragma unroll
  for (int i = 0; i < N; i++) d[i] = 0u;
}
__device__ __forceinline__ uint32_t pack_bf16(float lo, float hi) {
  uint32_t r;
  asm("cvt.rn.bf16x2.f32 %0, %1, %2;" : "=r"(r) : "f"(hi), "f"(lo));
  return r;
}
__device__ __forceinline__ void stmatrix_x4(uint32_t addr, uint32_t r0, uint32_t r1, uint32_t r2, uint32_t r3) {
  asm volatile("stmatrix.sync.aligned.m8n8.x4.shared.b16 [%0], {%1, %2, %3, %4};" ::"r"(addr), "r"(r0), "r"(r1),
               "r"(r2), "r"(r3)
               : "memory");
}
__device__ __forceinline__ void stmatrix_x4_p(uint32_t addr, uint32_t r0, uint32_t r1, uint32_t r2, uint32_t r3,
                                              bool on) {
  asm volatile("{\n.reg .pred p;\nsetp.ne.b32 p, %5, 0;\n@p stmatrix.sync.aligned.m8n8.x4.shared.b16 [%0], {%1, %2, %3, %4};\n}" ::"r"(addr),
               "r"(r0), "r"(r1), "r"(r2), "r"(r3), "r"((int)on)
               : "memory");
}
__device__ __forceinline__ float ex2(float x) {
  float y;
  asm("ex2.approx.ftz.f32 %0, %1;" : "=f"(y) : "f"(x));
  return y;
}
__device__ __forceinline__ float rcp(float x) {
  float y;
  asm("rcp.approx.ftz.f32 %0, %1;" : "=f"(y) : "f"(x));
  return y;
}
__device__ __forceinline__ float ex2v(float x) {
  float y;
  asm volatile("ex2.approx.ftz.f32 %0, %1;" : "=f"(y) : "f"(x));
  return y;
}
__device__ __forceinline__ float addv(float a, float b) {
  float y;
  asm volatile("add.f32 %0, %1, %2;" : "=f"(y) : "f"(a), "f"(b));
  return y;
}
__device__ __forceinline__ void mbar_arrive_elect(uint32_t bar, bool on) {
  asm volatile("{\n.reg .pred p, q;\nelect.sync _|q, 0xffffffff;\nsetp.ne.and.b32 p, %1, 0, q;\n@p mbarrier.arrive.shared::cta.b64 _, [%0];\n}" ::"r"(bar),
               "r"((int)on)
               : "memory");
}
__device__ __forceinline__ float mbar_test2(uint32_t bar0, uint32_t par0, uint32_t bar1, uint32_t par1) {
  float f;
  asm volatile(
      "{\n.reg .pred p, q;\nmbarrier.test_wait.parity.shared::cta.b64 p, [%1], %2;\n"
      "mbarrier.test_wait.parity.shared::cta.b64 q, [%3], %4;\nand.pred p, p, q;\nselp.f32 %0, 0f00000000, 0f80000000, p;\n}"
      : "=f"(f)
      : "r"(bar0), "r"(par0), "r"(bar1), "r"(par1)
      : "memory");
  return f;
}
__device__ __forceinline__ void mbar_wait_rest(uint32_t bar, uint32_t parity, bool ok) {
  asm volatile(
      "{\n.reg .pred p;\n.reg .u32 t;\n"
      "setp.ne.b32 p, %2, 0;\n"
      "@p bra DONE;\n"
      "mov.u32 t, 0x100000;\n"
      "LAB_WAIT:\n"
      "mbarrier.try_wait.parity.shared::cta.b64 p, [%0], %1;\n"
      "@p bra DONE;\n"
      "sub.u32 t, t, 1;\n"
      "setp.ne.u32 p, t, 0;\n"
      "@p bra LAB_WAIT;\n"
      "trap;\n"
      "DONE:\n}" ::"r"(bar),
      "r"(parity), "r"((int)ok)
      : "memory");
}
__device__ __forceinline__ void send_peer(uint32_t addr, uint32_t bar, uint32_t v) {
  asm volatile(
      "{\n.reg .b32 ra, rb;\nmapa.shared::cluster.u32 ra, %0, 1;\nmapa.shared::cluster.u32 rb, %1, 1;\n"
      "st.async.weak.shared::cluster.mbarrier::complete_tx::bytes.b32 [ra], %2, [rb];\n}" ::"r"(addr),
      "r"(bar), "r"(v)
      : "memory");
}
__device__ __forceinline__ void cnt_signal(int idx, uint32_t inc = 1) {
  asm volatile("red.release.gpu.global.add.u32 [%0], %1;" ::"l"(g_cnt + idx * 8), "r"(inc) : "memory");
}
__device__ __forceinline__ void cnt_signal_done(int idx, uint32_t inc = 1) {
  asm volatile("fence.proxy.async.global;" ::: "memory");
  cnt_signal(idx, inc);
}
__device__ __forceinline__ uint32_t cnt_next(int idx) {
  uint32_t v;
  asm volatile("atom.relaxed.gpu.global.add.u32 %0, [%1], 1;" : "=r"(v) : "l"(g_cnt + idx * 8) : "memory");
  return v;
}
__device__ __forceinline__ void cnt_wait(int idx, uint32_t target) {
  asm volatile(
      "{\n.reg .pred p;\n.reg .u32 v, t0, t1;\n"
      "ld.acquire.gpu.global.u32 v, [%0];\n"
      "setp.ge.u32 p, v, %1;\n"
      "@p bra DONE;\n"
      "mov.u32 t0, %%clock;\n"
      "LAB_WAIT:\n"
      "nanosleep.u32 100;\n"
      "ld.acquire.gpu.global.u32 v, [%0];\n"
      "setp.ge.u32 p, v, %1;\n"
      "@p bra DONE;\n"
      "mov.u32 t1, %%clock;\n"
      "sub.u32 t1, t1, t0;\n"
      "setp.lt.u32 p, t1, 0x80000000;\n"
      "@p bra LAB_WAIT;\n"
      "trap;\n"
      "DONE:\n}" ::"l"(g_cnt + idx * 8),
      "r"(target)
      : "memory");
}
__device__ __forceinline__ void cnt_wait_bit(int idx, uint32_t bit, uint32_t& v) {
  asm volatile(
      "{\n.reg .pred p;\n.reg .u32 x, t0, t1;\n"
      "and.b32 x, %0, %2;\n"
      "setp.ne.u32 p, x, 0;\n"
      "@p bra DONE;\n"
      "mov.u32 t0, %%clock;\n"
      "LAB_WAIT:\n"
      "ld.acquire.gpu.global.u32 %0, [%1];\n"
      "and.b32 x, %0, %2;\n"
      "setp.ne.u32 p, x, 0;\n"
      "@p bra DONE;\n"
      "nanosleep.u32 64;\n"
      "mov.u32 t1, %%clock;\n"
      "sub.u32 t1, t1, t0;\n"
      "setp.lt.u32 p, t1, 0x80000000;\n"
      "@p bra LAB_WAIT;\n"
      "trap;\n"
      "DONE:\n}" : "+r"(v) : "l"(g_cnt + idx * 8),
      "r"(bit)
      : "memory");
}
__device__ __forceinline__ bool cnt_done(uint32_t total) {
  uint32_t old;
  asm volatile("atom.acq_rel.gpu.global.add.u32 %0, [%1], 1;" : "=r"(old) : "l"(g_cnt + CNT_DONE * 8) : "memory");
  return old == total - 1;
}
__device__ __forceinline__ void cnt_rearm() {
#pragma unroll
  for (int i = 0; i < CNT_N; i++) g_cnt[i * 8] = 0;
}
__device__ __forceinline__ void fence_proxy_async_global() { asm volatile("fence.proxy.async.global;" ::: "memory"); }
#ifdef TIMELINE
__device__ __forceinline__ void tl_rec(int role, int& n, uint32_t code) {
  unsigned long long t;
  asm volatile("mov.u64 %0, %%globaltimer;" : "=l"(t));
  uint32_t c;
  asm volatile("mov.u32 %0, %%clock;" : "=r"(c));
  if (n < 32) {
    g_tl[(blockIdx.x * 4 + role) * 64 + 2 * n] = t;
    g_tl[(blockIdx.x * 4 + role) * 64 + 2 * n + 1] = ((unsigned long long)code << 32) | c;
  }
  n++;
}
#define TL(role, code) tl_rec(role, tln, code)
__device__ __forceinline__ void tl_rec_p(int role, int& n, uint32_t code, bool on) {
  unsigned long long t;
  asm volatile("mov.u64 %0, %%globaltimer;" : "=l"(t));
  uint32_t c;
  asm volatile("mov.u32 %0, %%clock;" : "=r"(c));
  asm volatile("{\n.reg .pred p;\nsetp.ne.b32 p, %3, 0;\n@p st.global.v2.u64 [%0], {%1, %2};\n}" ::"l"(g_tl + (blockIdx.x * 4 + role) * 64 + 2 * n),
               "l"(t), "l"(((unsigned long long)code << 32) | c), "r"((int)(on && n < 32)) : "memory");
  n++;
}
#define TL0(code) tl_rec_p(0, tln, code, threadIdx.x == 0)
#define TL_DECL int tln = 0
#ifdef TLWAIT
#define TW_DECL uint32_t w0 = 0, w1 = 0, w2 = 0, w3 = 0; int tln3 = 0
#define TW(w, stmt) { uint32_t c0_ = clock(); stmt; w += clock() - c0_; }
#define TW_FLUSH() { tl_rec_p(3, tln3, (min(w0, 65534u) << 16) | min(w1, 65534u), threadIdx.x == TLWAIT); tl_rec_p(3, tln3, (min(w2, 65534u) << 16) | min(w3, 65534u), threadIdx.x == TLWAIT); w0 = w1 = w2 = w3 = 0; }
#define TW_END() tl_rec_p(3, tln3, 0xFFFF, threadIdx.x == TLWAIT)
#endif
#else
#define TL(role, code)
#define TL0(code)
#define TL_DECL
#endif
#ifdef TRACE
__device__ uint32_t g_tr[2 * 2 * 4096];
#define TR_DECL int trn = 0; const bool tron = (blockIdx.x == TRACE || blockIdx.x == TRACE2) && (threadIdx.x & 127) == TRW * 32; uint32_t* trp = g_tr + ((blockIdx.x == TRACE ? 0 : 2) + (threadIdx.x >> 7)) * 4096
#ifndef TRW
#define TRW 0
#endif
#ifndef TRM
#define TRM 0xFFFF
#endif
#define TRI(id, code) if ((TRM >> (id)) & 1) { asm volatile("{\n.reg .pred p;\nsetp.ne.b32 p, %2, 0;\n@p st.global.u32 [%0], %1;\n}" ::"l"(trp + trn), "r"(((uint32_t)clock() << 4) | (code)), "r"((int)(tron && trn < 4095)) : "memory"); trn++; }
#define TR(code) TRI(code, code)
#else
#define TR_DECL
#define TR(code)
#define TRI(id, code)
#endif
#ifndef TLWAIT
#define TW_DECL
#define TW(w, stmt) stmt
#define TW_FLUSH()
#define TW_END()
#endif

__device__ __forceinline__ uint32_t make_desc(uint32_t addr, uint32_t lbo_bytes) {
  return (addr >> 4) + ((lbo_bytes >> 4) << 16);
}

__device__ __forceinline__ void wgmma_ss_n128(float (&d)[64], uint32_t da, uint32_t db, int scale_d) {
  asm volatile("{\n.reg .pred p;\n.reg .b64 a, b;\nsetp.ne.b32 p, %66, 0;\nmov.b64 a, {%64, 0x40000040};\nmov.b64 b, {%65, 0x40000040};\n"
    "wgmma.mma_async.sync.aligned.m64n128k16.f32.bf16.bf16 {%0, %1, %2, %3, %4, %5, %6, %7, %8, %9, %10, %11, %12, %13, %14, %15, %16, %17, %18, %19, %20, %21, %22, %23, %24, %25, %26, %27, %28, %29, %30, %31, %32, %33, %34, %35, %36, %37, %38, %39, %40, %41, %42, %43, %44, %45, %46, %47, %48, %49, %50, %51, %52, %53, %54, %55, %56, %57, %58, %59, %60, %61, %62, %63}, a, b, p, 1, 1, 0, 0;\n}\n"
    : "+f"(d[0]), "+f"(d[1]), "+f"(d[2]), "+f"(d[3]), "+f"(d[4]), "+f"(d[5]), "+f"(d[6]), "+f"(d[7]), "+f"(d[8]), "+f"(d[9]), "+f"(d[10]), "+f"(d[11]), "+f"(d[12]), "+f"(d[13]), "+f"(d[14]), "+f"(d[15]), "+f"(d[16]), "+f"(d[17]), "+f"(d[18]), "+f"(d[19]), "+f"(d[20]), "+f"(d[21]), "+f"(d[22]), "+f"(d[23]), "+f"(d[24]), "+f"(d[25]), "+f"(d[26]), "+f"(d[27]), "+f"(d[28]), "+f"(d[29]), "+f"(d[30]), "+f"(d[31]), "+f"(d[32]), "+f"(d[33]), "+f"(d[34]), "+f"(d[35]), "+f"(d[36]), "+f"(d[37]), "+f"(d[38]), "+f"(d[39]), "+f"(d[40]), "+f"(d[41]), "+f"(d[42]), "+f"(d[43]), "+f"(d[44]), "+f"(d[45]), "+f"(d[46]), "+f"(d[47]), "+f"(d[48]), "+f"(d[49]), "+f"(d[50]), "+f"(d[51]), "+f"(d[52]), "+f"(d[53]), "+f"(d[54]), "+f"(d[55]), "+f"(d[56]), "+f"(d[57]), "+f"(d[58]), "+f"(d[59]), "+f"(d[60]), "+f"(d[61]), "+f"(d[62]), "+f"(d[63])
    : "r"(da), "r"(db), "r"(scale_d));
}
__device__ __forceinline__ void wgmma_ss_n64(float (&d)[32], uint32_t da, uint32_t db, int scale_d) {
  asm volatile("{\n.reg .pred p;\n.reg .b64 a, b;\nsetp.ne.b32 p, %34, 0;\nmov.b64 a, {%32, 0x40000040};\nmov.b64 b, {%33, 0x40000040};\n"
    "wgmma.mma_async.sync.aligned.m64n64k16.f32.bf16.bf16 {%0, %1, %2, %3, %4, %5, %6, %7, %8, %9, %10, %11, %12, %13, %14, %15, %16, %17, %18, %19, %20, %21, %22, %23, %24, %25, %26, %27, %28, %29, %30, %31}, a, b, p, 1, 1, 0, 0;\n}\n"
    : "+f"(d[0]), "+f"(d[1]), "+f"(d[2]), "+f"(d[3]), "+f"(d[4]), "+f"(d[5]), "+f"(d[6]), "+f"(d[7]), "+f"(d[8]), "+f"(d[9]), "+f"(d[10]), "+f"(d[11]), "+f"(d[12]), "+f"(d[13]), "+f"(d[14]), "+f"(d[15]), "+f"(d[16]), "+f"(d[17]), "+f"(d[18]), "+f"(d[19]), "+f"(d[20]), "+f"(d[21]), "+f"(d[22]), "+f"(d[23]), "+f"(d[24]), "+f"(d[25]), "+f"(d[26]), "+f"(d[27]), "+f"(d[28]), "+f"(d[29]), "+f"(d[30]), "+f"(d[31])
    : "r"(da), "r"(db), "r"(scale_d));
}
__device__ __forceinline__ void wgmma_rs_n128_tb(float (&d)[64], uint32_t a0, uint32_t a1, uint32_t a2, uint32_t a3, uint32_t db, int scale_d) {
  asm volatile("{\n.reg .pred p;\n.reg .b64 b;\nsetp.ne.b32 p, %69, 0;\nmov.b64 b, {%68, 0x40000040};\n"
    "wgmma.mma_async.sync.aligned.m64n128k16.f32.bf16.bf16 {%0, %1, %2, %3, %4, %5, %6, %7, %8, %9, %10, %11, %12, %13, %14, %15, %16, %17, %18, %19, %20, %21, %22, %23, %24, %25, %26, %27, %28, %29, %30, %31, %32, %33, %34, %35, %36, %37, %38, %39, %40, %41, %42, %43, %44, %45, %46, %47, %48, %49, %50, %51, %52, %53, %54, %55, %56, %57, %58, %59, %60, %61, %62, %63}, {%64, %65, %66, %67}, b, p, 1, 1, 1;\n}\n"
    : "+f"(d[0]), "+f"(d[1]), "+f"(d[2]), "+f"(d[3]), "+f"(d[4]), "+f"(d[5]), "+f"(d[6]), "+f"(d[7]), "+f"(d[8]), "+f"(d[9]), "+f"(d[10]), "+f"(d[11]), "+f"(d[12]), "+f"(d[13]), "+f"(d[14]), "+f"(d[15]), "+f"(d[16]), "+f"(d[17]), "+f"(d[18]), "+f"(d[19]), "+f"(d[20]), "+f"(d[21]), "+f"(d[22]), "+f"(d[23]), "+f"(d[24]), "+f"(d[25]), "+f"(d[26]), "+f"(d[27]), "+f"(d[28]), "+f"(d[29]), "+f"(d[30]), "+f"(d[31]), "+f"(d[32]), "+f"(d[33]), "+f"(d[34]), "+f"(d[35]), "+f"(d[36]), "+f"(d[37]), "+f"(d[38]), "+f"(d[39]), "+f"(d[40]), "+f"(d[41]), "+f"(d[42]), "+f"(d[43]), "+f"(d[44]), "+f"(d[45]), "+f"(d[46]), "+f"(d[47]), "+f"(d[48]), "+f"(d[49]), "+f"(d[50]), "+f"(d[51]), "+f"(d[52]), "+f"(d[53]), "+f"(d[54]), "+f"(d[55]), "+f"(d[56]), "+f"(d[57]), "+f"(d[58]), "+f"(d[59]), "+f"(d[60]), "+f"(d[61]), "+f"(d[62]), "+f"(d[63])
    : "r"(a0), "r"(a1), "r"(a2), "r"(a3), "r"(db), "r"(scale_d));
}
__device__ __forceinline__ void wgmma_ss_n72_init(float (&d)[36], uint32_t da, uint32_t db) {
  asm volatile("{\n.reg .pred p;\n.reg .b64 a, b;\nsetp.ne.b32 p, 0, 0;\nmov.b64 a, {%36, 0x40000040};\nmov.b64 b, {%37, 0x40000040};\n"
    "wgmma.mma_async.sync.aligned.m64n72k16.f32.bf16.bf16 {%0, %1, %2, %3, %4, %5, %6, %7, %8, %9, %10, %11, %12, %13, %14, %15, %16, %17, %18, %19, %20, %21, %22, %23, %24, %25, %26, %27, %28, %29, %30, %31, %32, %33, %34, %35}, a, b, p, 1, 1, 0, 0;\n}\n"
    : "=f"(d[0]), "=f"(d[1]), "=f"(d[2]), "=f"(d[3]), "=f"(d[4]), "=f"(d[5]), "=f"(d[6]), "=f"(d[7]), "=f"(d[8]), "=f"(d[9]), "=f"(d[10]), "=f"(d[11]), "=f"(d[12]), "=f"(d[13]), "=f"(d[14]), "=f"(d[15]), "=f"(d[16]), "=f"(d[17]), "=f"(d[18]), "=f"(d[19]), "=f"(d[20]), "=f"(d[21]), "=f"(d[22]), "=f"(d[23]), "=f"(d[24]), "=f"(d[25]), "=f"(d[26]), "=f"(d[27]), "=f"(d[28]), "=f"(d[29]), "=f"(d[30]), "=f"(d[31]), "=f"(d[32]), "=f"(d[33]), "=f"(d[34]), "=f"(d[35])
    : "r"(da), "r"(db));
}
__device__ __forceinline__ void wgmma_ss_n72(float (&d)[36], uint32_t da, uint32_t db, int scale_d) {
  asm volatile("{\n.reg .pred p;\n.reg .b64 a, b;\nsetp.ne.b32 p, %38, 0;\nmov.b64 a, {%36, 0x40000040};\nmov.b64 b, {%37, 0x40000040};\n"
    "wgmma.mma_async.sync.aligned.m64n72k16.f32.bf16.bf16 {%0, %1, %2, %3, %4, %5, %6, %7, %8, %9, %10, %11, %12, %13, %14, %15, %16, %17, %18, %19, %20, %21, %22, %23, %24, %25, %26, %27, %28, %29, %30, %31, %32, %33, %34, %35}, a, b, p, 1, 1, 0, 0;\n}\n"
    : "+f"(d[0]), "+f"(d[1]), "+f"(d[2]), "+f"(d[3]), "+f"(d[4]), "+f"(d[5]), "+f"(d[6]), "+f"(d[7]), "+f"(d[8]), "+f"(d[9]), "+f"(d[10]), "+f"(d[11]), "+f"(d[12]), "+f"(d[13]), "+f"(d[14]), "+f"(d[15]), "+f"(d[16]), "+f"(d[17]), "+f"(d[18]), "+f"(d[19]), "+f"(d[20]), "+f"(d[21]), "+f"(d[22]), "+f"(d[23]), "+f"(d[24]), "+f"(d[25]), "+f"(d[26]), "+f"(d[27]), "+f"(d[28]), "+f"(d[29]), "+f"(d[30]), "+f"(d[31]), "+f"(d[32]), "+f"(d[33]), "+f"(d[34]), "+f"(d[35])
    : "r"(da), "r"(db), "r"(scale_d));
}
template <int OA, int OB>
__device__ __forceinline__ void wgmma_ss_n128_tb(float (&d)[64], uint32_t da, uint32_t db, int scale_d) {
  asm volatile("{\n.reg .pred p;\n.reg .b64 a, b;\n.reg .b32 x, y;\nsetp.ne.b32 p, %66, 0;\nadd.u32 x, %64, %67;\nadd.u32 y, %65, %68;\nmov.b64 a, {x, 0x40000040};\nmov.b64 b, {y, 0x40000040};\n"
    "wgmma.mma_async.sync.aligned.m64n128k16.f32.bf16.bf16 {%0, %1, %2, %3, %4, %5, %6, %7, %8, %9, %10, %11, %12, %13, %14, %15, %16, %17, %18, %19, %20, %21, %22, %23, %24, %25, %26, %27, %28, %29, %30, %31, %32, %33, %34, %35, %36, %37, %38, %39, %40, %41, %42, %43, %44, %45, %46, %47, %48, %49, %50, %51, %52, %53, %54, %55, %56, %57, %58, %59, %60, %61, %62, %63}, a, b, p, 1, 1, 0, 1;\n}\n"
    : "+f"(d[0]), "+f"(d[1]), "+f"(d[2]), "+f"(d[3]), "+f"(d[4]), "+f"(d[5]), "+f"(d[6]), "+f"(d[7]), "+f"(d[8]), "+f"(d[9]), "+f"(d[10]), "+f"(d[11]), "+f"(d[12]), "+f"(d[13]), "+f"(d[14]), "+f"(d[15]), "+f"(d[16]), "+f"(d[17]), "+f"(d[18]), "+f"(d[19]), "+f"(d[20]), "+f"(d[21]), "+f"(d[22]), "+f"(d[23]), "+f"(d[24]), "+f"(d[25]), "+f"(d[26]), "+f"(d[27]), "+f"(d[28]), "+f"(d[29]), "+f"(d[30]), "+f"(d[31]), "+f"(d[32]), "+f"(d[33]), "+f"(d[34]), "+f"(d[35]), "+f"(d[36]), "+f"(d[37]), "+f"(d[38]), "+f"(d[39]), "+f"(d[40]), "+f"(d[41]), "+f"(d[42]), "+f"(d[43]), "+f"(d[44]), "+f"(d[45]), "+f"(d[46]), "+f"(d[47]), "+f"(d[48]), "+f"(d[49]), "+f"(d[50]), "+f"(d[51]), "+f"(d[52]), "+f"(d[53]), "+f"(d[54]), "+f"(d[55]), "+f"(d[56]), "+f"(d[57]), "+f"(d[58]), "+f"(d[59]), "+f"(d[60]), "+f"(d[61]), "+f"(d[62]), "+f"(d[63])
    : "r"(da), "r"(db), "r"(scale_d), "n"(OA), "n"(OB));
}
template <int OA, int OB>
__device__ __forceinline__ void wgmma_ss_n256_tbo(float (&d)[128], uint32_t da, uint32_t db, int scale_d) {
  asm volatile("{\n.reg .pred p;\n.reg .b64 a, b;\n.reg .b32 x, y;\nsetp.ne.b32 p, %130, 0;\nadd.u32 x, %128, %131;\nadd.u32 y, %129, %132;\nmov.b64 a, {x, 0x40000040};\nmov.b64 b, {y, 0x40000040};\n"
    "wgmma.mma_async.sync.aligned.m64n256k16.f32.bf16.bf16 {%0, %1, %2, %3, %4, %5, %6, %7, %8, %9, %10, %11, %12, %13, %14, %15, %16, %17, %18, %19, %20, %21, %22, %23, %24, %25, %26, %27, %28, %29, %30, %31, %32, %33, %34, %35, %36, %37, %38, %39, %40, %41, %42, %43, %44, %45, %46, %47, %48, %49, %50, %51, %52, %53, %54, %55, %56, %57, %58, %59, %60, %61, %62, %63, %64, %65, %66, %67, %68, %69, %70, %71, %72, %73, %74, %75, %76, %77, %78, %79, %80, %81, %82, %83, %84, %85, %86, %87, %88, %89, %90, %91, %92, %93, %94, %95, %96, %97, %98, %99, %100, %101, %102, %103, %104, %105, %106, %107, %108, %109, %110, %111, %112, %113, %114, %115, %116, %117, %118, %119, %120, %121, %122, %123, %124, %125, %126, %127}, a, b, p, 1, 1, 0, 1;\n}\n"
    : "+f"(d[0]), "+f"(d[1]), "+f"(d[2]), "+f"(d[3]), "+f"(d[4]), "+f"(d[5]), "+f"(d[6]), "+f"(d[7]), "+f"(d[8]), "+f"(d[9]), "+f"(d[10]), "+f"(d[11]), "+f"(d[12]), "+f"(d[13]), "+f"(d[14]), "+f"(d[15]), "+f"(d[16]), "+f"(d[17]), "+f"(d[18]), "+f"(d[19]), "+f"(d[20]), "+f"(d[21]), "+f"(d[22]), "+f"(d[23]), "+f"(d[24]), "+f"(d[25]), "+f"(d[26]), "+f"(d[27]), "+f"(d[28]), "+f"(d[29]), "+f"(d[30]), "+f"(d[31]), "+f"(d[32]), "+f"(d[33]), "+f"(d[34]), "+f"(d[35]), "+f"(d[36]), "+f"(d[37]), "+f"(d[38]), "+f"(d[39]), "+f"(d[40]), "+f"(d[41]), "+f"(d[42]), "+f"(d[43]), "+f"(d[44]), "+f"(d[45]), "+f"(d[46]), "+f"(d[47]), "+f"(d[48]), "+f"(d[49]), "+f"(d[50]), "+f"(d[51]), "+f"(d[52]), "+f"(d[53]), "+f"(d[54]), "+f"(d[55]), "+f"(d[56]), "+f"(d[57]), "+f"(d[58]), "+f"(d[59]), "+f"(d[60]), "+f"(d[61]), "+f"(d[62]), "+f"(d[63]), "+f"(d[64]), "+f"(d[65]), "+f"(d[66]), "+f"(d[67]), "+f"(d[68]), "+f"(d[69]), "+f"(d[70]), "+f"(d[71]), "+f"(d[72]), "+f"(d[73]), "+f"(d[74]), "+f"(d[75]), "+f"(d[76]), "+f"(d[77]), "+f"(d[78]), "+f"(d[79]), "+f"(d[80]), "+f"(d[81]), "+f"(d[82]), "+f"(d[83]), "+f"(d[84]), "+f"(d[85]), "+f"(d[86]), "+f"(d[87]), "+f"(d[88]), "+f"(d[89]), "+f"(d[90]), "+f"(d[91]), "+f"(d[92]), "+f"(d[93]), "+f"(d[94]), "+f"(d[95]), "+f"(d[96]), "+f"(d[97]), "+f"(d[98]), "+f"(d[99]), "+f"(d[100]), "+f"(d[101]), "+f"(d[102]), "+f"(d[103]), "+f"(d[104]), "+f"(d[105]), "+f"(d[106]), "+f"(d[107]), "+f"(d[108]), "+f"(d[109]), "+f"(d[110]), "+f"(d[111]), "+f"(d[112]), "+f"(d[113]), "+f"(d[114]), "+f"(d[115]), "+f"(d[116]), "+f"(d[117]), "+f"(d[118]), "+f"(d[119]), "+f"(d[120]), "+f"(d[121]), "+f"(d[122]), "+f"(d[123]), "+f"(d[124]), "+f"(d[125]), "+f"(d[126]), "+f"(d[127])
    : "r"(da), "r"(db), "r"(scale_d), "n"(OA), "n"(OB));
}

constexpr int NCTA = 132;
constexpr int NCLUSTER = 66;
constexpr int NPROB = 6;
#ifdef GEMM_ONLY
#define DO_LOCAL false
#define DO_ATT false
#else
#define DO_LOCAL true
#define DO_ATT true
#endif
#ifdef ATT_ONLY
#define NA_CL_ 0
#define NITEMS 768
#else
#define NA_CL_ 32
#define NITEMS 256
#endif
constexpr int G1_MAX = 20, NA_CL = NA_CL_, NB_CL = NCLUSTER - NA_CL;
constexpr int TILE32K = 32768;
constexpr uint32_t DBASE = 1024;
constexpr int OFF_STG = 4 * TILE32K;
constexpr int OFF_A = 5 * TILE32K;
constexpr int OFF_BAR = 7 * TILE32K;
constexpr int L_K = 8192, L_V = L_K + 9216, L_P = L_V + 9216;
constexpr int SMEM_BYTES = OFF_BAR + 1024;
constexpr int B_GFULL = 0, B_GEMPTY = 32, B_AFULL = 64, B_AEMPTY = 104, B_QFULL = 144, B_QEMPTY = 160,
              B_SFULL = 176, B_SEMPTY = 208, B_OFULL = 240, B_STGFREE = 256, S_CODE = 272, B_SFULL2 = 304,
              B_MAIL = 336, S_MAIL = 368;
#ifndef FS
#define FS 2
#endif
#ifndef HW
#define HW 1
#endif
#ifndef PACE
#define PACE 900u
#define DELAY 1300u
#endif
#ifndef REG_C
#define REG_C 232
#define REG_P 40
#endif

struct Params {
  CUtensorMap ta[NPROB];
  CUtensorMap tb[NPROB];
  CUtensorMap tc[NPROB];
  CUtensorMap tq, tk, tv, tl, th;
  bf16* ob;
  uint16_t g[NCLUSTER][G1_MAX];
  uint16_t order[256];
};
__device__ __forceinline__ uint32_t tail_item(uint32_t code) {
  return (code & 0x7FFF) < 32 ? (5u << 8) | ((code & 4) << 4) | ((code & 0x18) << 1) | (code & 3) : 0xFFFFu;
}
#ifndef HM
#define HM 0x39383F00
#endif
#define HINT(b) ((HM >> (b) & 1) ? EV_FIRST : EV_NORMAL)
__device__ __forceinline__ uint32_t lds32(uint32_t a) {
  uint32_t v;
  asm volatile("ld.shared.u32 %0, [%1];" : "=r"(v) : "r"(a) : "memory");
  return v;
}
__device__ __forceinline__ uint4 lds128(uint32_t a) {
  uint4 v;
  asm volatile("ld.shared.v4.u32 {%0, %1, %2, %3}, [%4];" : "=r"(v.x), "=r"(v.y), "=r"(v.z), "=r"(v.w) : "r"(a) : "memory");
  return v;
}
__device__ __forceinline__ void sts64(uint32_t a, float x, float y) {
  asm volatile("st.shared.v2.f32 [%0], {%1, %2};" ::"r"(a), "f"(x), "f"(y) : "memory");
}
__device__ __forceinline__ void sts32(uint32_t a, uint32_t v) {
  asm volatile("st.shared.u32 [%0], %1;" ::"r"(a), "r"(v) : "memory");
}
__device__ __forceinline__ uint32_t opaque_tid() {
  uint32_t t;
  asm volatile("mov.u32 %0, %%tid.x;" : "=r"(t));
  return t;
}
__device__ __forceinline__ uint32_t stg_off(uint32_t tid) {
  return (tid >> 5) * 2048 + (tid & 15) * 128 + ((((tid >> 4) & 1) ^ (tid & 7)) << 4);
}
__device__ __forceinline__ int prob_nkb4(int prob) { return (0x4F4224 >> (prob * 4) & 15) + (prob == 4); }

constexpr float SM_C = 0.08838834764831845f * 1.4426950408889634f;
constexpr float SM_HI = 1099511627776.0f;
constexpr float SM_LO = 8.673617379884035e-19f;
__device__ __forceinline__ void softmax_max(const float (&s)[64], float& a0, float& a1) {
  a0 = fmaxf(s[0], s[1]);
  a1 = fmaxf(s[2], s[3]);
#pragma unroll
  for (int j = 1; j < 16; j++) {
    a0 = fmaxf(a0, fmaxf(s[4 * j], s[4 * j + 1]));
    a1 = fmaxf(a1, fmaxf(s[4 * j + 2], s[4 * j + 3]));
  }
  a0 = fmaxf(a0, __shfl_xor_sync(0xffffffffu, a0, 1));
  a1 = fmaxf(a1, __shfl_xor_sync(0xffffffffu, a1, 1));
  a0 = fmaxf(a0, __shfl_xor_sync(0xffffffffu, a0, 2));
  a1 = fmaxf(a1, __shfl_xor_sync(0xffffffffu, a1, 2));
}
template <int J0, int J1, bool OFS, int N>
__device__ __forceinline__ void softmax_exp(const float (&s)[64], float b0, float b1, uint32_t (&out)[N], float& t0,
                                            float& t1) {
#pragma unroll
  for (int j = J0; j < J1; j++) {
    const float e0 = ex2(OFS ? s[4 * j] + b0 : s[4 * j]);
    const float e1 = ex2(OFS ? s[4 * j + 1] + b0 : s[4 * j + 1]);
    const float e2 = ex2(OFS ? s[4 * j + 2] + b1 : s[4 * j + 2]);
    const float e3 = ex2(OFS ? s[4 * j + 3] + b1 : s[4 * j + 3]);
    t0 += e0 + e1;
    t1 += e2 + e3;
    out[2 * j] = pack_bf16(e0, e1);
    out[2 * j + 1] = pack_bf16(e2, e3);
  }
}

__device__ __forceinline__ uint32_t scale_q(uint32_t x) {
  uint32_t t, y;
  asm("mul.rn.bf16x2 %0, %1, %2;" : "=r"(t) : "r"(x), "r"(0xb9d8b9d8u));
  asm("fma.rn.bf16x2 %0, %1, %2, %3;" : "=r"(y) : "r"(x), "r"(0x3e033e03u), "r"(t));
  return y;
}

__global__ void __cluster_dims__(2, 1, 1) __launch_bounds__(384, 1) mega_kernel(const __grid_constant__ Params p) {
  extern __shared__ __align__(1024) uint8_t smem_raw[];
#ifdef TRACE
  const uint32_t c_entry = clock();
#endif
  const uint32_t sbase = smem_u32(smem_raw);
  const uint32_t s_bar = sbase + OFF_BAR;
  const int cluster_id = blockIdx.x >> 1;
  const bool isB = cluster_id >= NA_CL;
#if !defined(ATT_ONLY) && !defined(GEMM_ONLY)
#define EARLY 1
#else
#define EARLY 0
#endif
  const int prob0 = isB ? 3 : cluster_id >> 4;
  const int ng0 = (isB ? (cluster_id - NA_CL) >> 3 : (cluster_id >> 3) & 1) * 4;
  const uint32_t t0 = clock();
  auto early = [&](int s) {
    const uint32_t full = s_bar + B_GFULL + 8 * s;
    mbar_expect_tx(full, 49152);
    tma_load_3d(sbase + OFF_A + s * 16384, &p.ta[prob0], 0, (blockIdx.x & 15) * 128, s, full, EV_NORMAL);
    tma_load_3d(sbase + s * TILE32K, &p.tb[prob0], 0, s * 64, ng0, full, EV_NORMAL);
    tma_load_3d(sbase + s * TILE32K + 16384, &p.tb[prob0], 0, s * 64, ng0 + 2, full, EV_NORMAL);
  };
  if ((threadIdx.x >> 5) == 8) {
    if (elect_one()) {
      mbar_init(s_bar + B_GFULL, 1);
      asm volatile("fence.mbarrier_init.release.cluster;" ::: "memory");
      if (EARLY && !isB) {
        early(0);
      } else {
        prefetch_tmap(&p.ta[prob0]);
        prefetch_tmap(&p.tb[prob0]);
      }
      for (int s = 1; s < 4; s++) mbar_init(s_bar + B_GFULL + 8 * s, 1);
      asm volatile("fence.mbarrier_init.release.cluster;" ::: "memory");
    }
    __syncwarp();
    named_bar_arrive(7, 288);
  }
  const int warp0 = __shfl_sync(0xffffffffu, threadIdx.x >> 5, 0);
  if (warp0 >= 8) reg_dealloc<REG_P>();
#define CLUSTER_ARRIVE() asm volatile("barrier.cluster.arrive.relaxed.aligned;" ::: "memory")
#define CLUSTER_WAIT() asm volatile("barrier.cluster.wait.acquire.aligned;" ::: "memory")

  if (warp0 >= 8) {
    if (warp0 == 10 && elect_one()) {
      if ((sbase & 0x3FFFFu) != DBASE) __trap();
      for (int s = 0; s < 4; s++) {
        mbar_init(s_bar + B_GEMPTY + 8 * s, 4);
        mbar_init(s_bar + B_SFULL + 8 * s, 4);
        mbar_init(s_bar + B_SFULL2 + 8 * s, 4);
        mbar_init(s_bar + B_SEMPTY + 8 * s, 1);
        mbar_init(s_bar + B_AFULL + 8 * s, 1);
        mbar_init(s_bar + B_AEMPTY + 8 * s, isB ? 4 : s ? 8 : 2);
        mbar_init(s_bar + B_MAIL + 8 * s, 1);
      }
      for (int s = 0; s < 2; s++) {
        mbar_init(s_bar + B_QFULL + 8 * s, 1);
        mbar_init(s_bar + B_QEMPTY + 8 * s, 2);
      }
      mbar_init(s_bar + B_OFULL, 8);
      mbar_init(s_bar + B_STGFREE, 1);
      asm volatile("fence.mbarrier_init.release.cluster;" ::: "memory");
    }
    __syncwarp();
    CLUSTER_ARRIVE();
    if (EARLY && warp0 == 8 && elect_one()) {
#pragma unroll 1
      for (int s = !isB; s < 4; s++) {
        while ((uint32_t)clock() - t0 < s * PACE + (isB ? DELAY : 0u)) {}
        early(s);
      }
    }
    __syncwarp();
    CLUSTER_WAIT();
    const uint32_t rank = blockIdx.x & 1;
    if (warp0 == 8) {
      if (elect_one()) {
        TL_DECL;
        uint32_t gphase = 1 - EARLY;
        uint32_t tail = 0;
        int gi = 0;
        uint32_t aswz = 0, lastq = 0, n = 0;
        uint32_t aprev = ~0u;
        for (int seg = 0; seg < 2; seg++) {
          for (;;) {
            uint32_t item = p.g[cluster_id][gi++];
            if (item == 0x500u) item = tail;
            if (item >= 0x600u) break;
            const int prob = item >> 8;
            const int rt = ((item >> 4) & 15) * 2 + rank;
            const int ngrp0 = (item & 15) * 4;
            const int nkb4 = prob_nkb4(prob);
            const CUtensorMap* ta = &p.ta[prob - (prob == 2)];
            const CUtensorMap* tb = &p.tb[prob];
            const uint64_t ahint = p.g[cluster_id][gi] >= 0x400u ? EV_FIRST : EV_NORMAL;
            const int rot4 = prob < 4 ? 1 - gi : 0;
            const uint32_t akey = (item + 0x100u) & 0x6F0u;
            const bool keep = akey == aprev;
            aprev = akey;
            TL(1, item);
            uint32_t seen = 0;
            if (prob == 5) {
              cnt_wait_bit(CNT_OB + (rt >> 2), 32u << (rt & 3) * 8, seen);
              fence_proxy_async_global();
            }
            for (int kb4 = EARLY && gi == 1; kb4 < nkb4; kb4++) {
#pragma unroll 1
              for (int s = 0; s < 4; s++) {
                const int bs = s ^ (n & 1);
                if (prob == 4 && !(s & 1)) {
                  cnt_wait_bit(CNT_CTX + rt, 1u << (kb4 * 2 + (s >> 1)), seen);
                  fence_proxy_async_global();
                }
                if (prob == 5 && kb4 == 0) {
                  mbar_wait(s_bar + B_AEMPTY + 8 * bs, (~(n + (s & 1)) >> 1) & 1);
                  if (s == 2) mbar_wait(s_bar + B_QEMPTY + (aswz ? 0 : 8), lastq);
                }
                mbar_wait(s_bar + B_GEMPTY + 8 * s, gphase);
                const uint32_t full = s_bar + B_GFULL + 8 * s;
                const int kb = ((kb4 + rot4) & (nkb4 - 1)) * 4 + s;
                if (keep && kb4 == 0) {
                  mbar_expect_tx(full, 32768);
                } else {
                  mbar_expect_tx(full, 49152);
                  tma_load_3d(sbase + OFF_A + ((s * 16384) ^ aswz), ta, 0, rt * 128, kb, full, ahint);
                }
                tma_load_3d_mc(sbase + bs * TILE32K + rank * 16384, tb, 0, kb * 64, ngrp0 + rank * 2, full,
                               (uint16_t)3, HINT(8 + prob));
              }
              gphase ^= 1;
            }
          }
          if (seg == 0 && isB && DO_ATT) {
            int pv_row = 0, pv_col = 0;
            uint64_t pv_hint = 0;
            bool pv_own = false;
#define ACQ_SLOT(slot, n)                                                              \
  {                                                                                    \
    if ((n) < 2) mbar_wait(s_bar + B_GEMPTY + 8 * (slot), gphase);                     \
    mbar_wait(s_bar + B_AEMPTY + 8 * (slot), (~(n) >> 1) & 1);                         \
  }
#define LOAD_KV(map, slot, row, col, own, hint)                                        \
  {                                                                                    \
    const uint32_t full = s_bar + B_AFULL + 8 * (slot);                                \
    mbar_expect_tx(full, TILE32K);                                                     \
    if (own) {                                                                         \
      tma_load_3d(sbase + (slot) * TILE32K, map, 0, row, col, full, hint);             \
      tma_load_3d(sbase + (slot) * TILE32K + 16384, map, 0, row, (col) + 1, full, hint); \
    } else {                                                                           \
      tma_load_3d_mc(sbase + (slot) * TILE32K + rank * 16384, map, 0, row, (col) + rank, full, (uint16_t)3, hint); \
    }                                                                                  \
  }
#define LOAD_V()                                                                       \
  {                                                                                    \
    const uint32_t vs = 3 - (n & 1);                                                   \
    ACQ_SLOT(vs, n - 1);                                                               \
    LOAD_KV(&p.tv, vs, pv_row, pv_col, pv_own, pv_hint)                                \
  }
#ifdef ATT_ONLY
#define NEXT_CODE() (nxt < NITEMS ? p.order[nxt & 255] : 0x8000u + 64)
#else
#define NEXT_CODE() (nxt < 256 ? p.order[nxt] : nxt + (0x8000u - 256))
#endif
            uint32_t code = p.order[cluster_id - NA_CL];
            int it = 0;
            for (;; it++) {
              if (it == 1) mbar_wait(s_bar + B_STGFREE, 0);
              if (code & 0x8000u) break;
              const int head = code >> 4;
              const int q0 = code & 15, up = rank == (it & 1);
              TL(1, 0x1000 | code | up);
#ifndef ATT_ONLY
              cnt_wait(CNT_QKV + (head >> 1), 48);
#endif
              fence_proxy_async_global();
              {
                const int b = it & 1;
                if (it < 2) {
                  mbar_wait(s_bar + B_GEMPTY + 16 * b, gphase);
                  mbar_wait(s_bar + B_GEMPTY + 16 * b + 8, gphase);
                }
                mbar_wait(s_bar + B_QEMPTY + 8 * b, ((it >> 1) & 1) ^ 1);
                mbar_expect_tx(s_bar + B_QFULL + 8 * b, TILE32K);
                tma_load_3d(sbase + OFF_A + b * TILE32K, &p.tq, 0, (q0 + up) * 128, head * 2, s_bar + B_QFULL + 8 * b, HINT(24));
              }
#pragma unroll 1
              for (int i = q0 + (up & it); i >= -(up & ~it); i--) {
                const int t = i < 0 ? q0 + 1 : i;
                if (rank == 0 && i == min(q0, 1)) {
                  const uint32_t nxt = cnt_next(CNT_QUEUE) + NB_CL;
                  code = NEXT_CODE();
                  send_peer(s_bar + S_MAIL + 4 * (it & 3), s_bar + B_MAIL + 8 * (it & 3), code);
                }
                if (i == 0) {
                  if (rank) {
                    mbar_expect_tx(s_bar + B_MAIL + 8 * (it & 3), 4);
                    mbar_wait(s_bar + B_MAIL + 8 * (it & 3), (it >> 2) & 1);
                    code = lds32(s_bar + S_MAIL + 4 * (it & 3));
                  }
                  sts32(s_bar + S_CODE + 4 * ((it + 1) & 7), code);
                }
                ACQ_SLOT(n & 1, n);
                LOAD_KV(&p.tk, n & 1, t * 128, head * 2, t > q0, HINT(t >= q0 ? 29 : 25))
                if (n) LOAD_V();
                n++;
                pv_row = t * 128;
                pv_col = head * 2;
                pv_own = t > q0;
                pv_hint = HINT(t >= q0 ? 29 : 26);
              }
            }
            ACQ_SLOT(n & 1, n);
            mbar_arrive(s_bar + B_AFULL + 8 * (n & 1));
            LOAD_V();
            if (rank & it) {
              ACQ_SLOT(2 + (n & 1), n);
#pragma unroll 1
              for (int i = 0; i < 8; i++) mbar_arrive_cluster_if(s_bar + B_AEMPTY + 8 * ((n & 1) + (i & 2)), i & 1, true);
              n++;
            }
            tail = tail_item(code);
            aswz = (it & 1) * TILE32K;
            mbar_wait(s_bar + B_QEMPTY + 8 * (it & 1), ((it >> 1) & 1) ^ 1);
            lastq = ((it - 1) >> 1) & 1;
            if (tail == 0xFFFFu) {
#pragma unroll 1
              for (int s = 0; s < 4; s++) mbar_wait(s_bar + B_AEMPTY + 8 * (s ^ (n & 1)), (~(n + (s & 1)) >> 1) & 1);
            }
          }
        }
        if (cnt_done(NCTA * 2)) cnt_rearm();
#pragma unroll 1
        for (int s = 0; s < 4; s++) mbar_wait(s_bar + B_GEMPTY + 8 * s, gphase);
        TL(1, 0xFFFF);
      }
    } else if (warp0 == 9) {
      if (elect_one()) {
        TL_DECL;
        uint32_t tail = 0;
        int gi = 0;
        uint32_t aswz = 0;
        bool rearm = false;
        for (int seg = 0; seg < 2; seg++) {
          for (;;) {
            uint32_t item = p.g[cluster_id][gi++];
            if (item == 0x500u) item = tail;
            if (item >= 0x600u) break;
            const int prob = item >> 8;
            const int rt = ((item >> 4) & 15) * 2 + rank;
            const int cg = (item & 15) * 4 + (prob == 5 ? 16 : 0);
            const CUtensorMap* tc = &p.tc[prob];
            const int nl = (p.g[cluster_id][gi] >> 8) == 4 && DO_LOCAL ? 8 : 1;
            const int grp = (blockIdx.x & 15) * 2 + ((blockIdx.x >> 4) & 1), r0 = (blockIdx.x >> 5) * 512;
            prefetch_tmap(tc);
            if (gi == 1 && prob == 1) prefetch_tmap(&p.tb[2]);
            if (p.g[cluster_id][gi] == 0x600u) {
              prefetch_tmap(&p.tq);
              prefetch_tmap(&p.tk);
              prefetch_tmap(&p.tv);
            }
            if (nl > 1) {
              prefetch_tmap(&p.ta[4]);
              prefetch_tmap(&p.tb[4]);
              prefetch_tmap(&p.tl);
              prefetch_tmap(&p.th);
              cnt_wait(CNT_QKVB, 192);
              fence_proxy_async_global();
            }
            if (prob >= 4) rearm = cnt_done(NCTA * 2);
            const bool lastt = p.g[cluster_id][gi] >= 0x600u;
#pragma unroll 1
            for (int c = 0; c < 8; c++) {
              const int q = lastt ? c & 3 : c >> 1, w = lastt ? c >> 2 : c & 1;
              const int idx = w * 2 + (q & 1);
              const bool alt = lastt && q >= 2;
              mbar_wait(s_bar + (alt ? B_SFULL2 : B_SFULL) + 8 * idx, lastt ? seg : q >> 1);
              tma_store_4d(tc, sbase + (alt ? OFF_A + ((q * 16384) ^ aswz) + w * 8192 : OFF_STG + idx * 8192),
                           rt * 64 + w * 32, cg + q, HINT(16 + prob));
              bulk_commit();
              if (c > 0 && !lastt) {
                bulk_wait_read<1>();
                mbar_arrive(s_bar + B_SEMPTY + 8 * ((w ^ 1) * 2 + (((c - 1) >> 1) & 1)));
              }
            }
            bulk_wait_read<0>();
            mbar_arrive(s_bar + (lastt ? B_STGFREE : B_SEMPTY + 8 * 3));
#pragma unroll 1
            for (int c = 0; c < nl; c++) {
              if (nl > 1) {
                mbar_wait(s_bar + B_AEMPTY, (c & 1) ^ 1);
                mbar_expect_tx(s_bar + B_AFULL, L_V);
                tma_load_3d(sbase + OFF_STG, &p.tl, 0, r0 + c * 64, grp, s_bar + B_AFULL, HINT(28));
                tma_load_3d(sbase + OFF_STG + L_K, &p.th, 0, r0 + c * 64 - 8, 32 + grp, s_bar + B_AFULL, HINT(28));
                mbar_wait(s_bar + B_AEMPTY + 8, (c & 1) ^ 1);
                mbar_expect_tx(s_bar + B_AFULL + 8, 9216);
                tma_load_3d(sbase + OFF_STG + L_V, &p.th, 0, r0 + c * 64 - 8, 64 + grp, s_bar + B_AFULL + 8, HINT(28));
              }
              if (c) {
                mbar_wait(s_bar + B_OFULL, ~c & 1);
                cnt_signal(CNT_OB + (blockIdx.x >> 5) * 2 + ((c - 1) >> 2), 1u << ((c - 1) & 3) * 8);
              } else if (prob < 4) {
                bulk_wait<0>();
                cnt_signal_done(prob == 3 ? CNT_QKVB : CNT_QKV + (item & 15));
                TL(2, item);
              }
            }
            if (nl > 1) {
              mbar_wait(s_bar + B_OFULL, 1);
              cnt_signal(CNT_OB + (blockIdx.x >> 5) * 2 + 1, 1u << 24);
              TL(2, 0x600);
            }
          }
          if (seg == 0 && isB && DO_ATT) {
#ifdef ATT_ONLY
            mbar_arrive(s_bar + B_STGFREE);
#endif
            uint32_t code = p.order[cluster_id - NA_CL];
            for (int it = 0; !(code & 0x8000u); it++) {
              code |= rank == (it & 1);
              aswz = (~it & 1) * TILE32K;
              mbar_wait(s_bar + B_OFULL, it & 1);
              tma_store_3d(&p.tq, sbase + OFF_STG, 0, (code & 15) * 128, (code >> 4) * 2, HINT(27));
              bulk_commit();
              const uint32_t nxt = lds32(s_bar + S_CODE + 4 * ((it + 1) & 7));
              bulk_wait_read<0>();
              mbar_arrive(s_bar + B_STGFREE);
              bulk_wait<0>();
              cnt_signal_done(CNT_CTX + (code & 15), 1u << (code >> 4));
              TL(2, 0x1000 | code);
              if (nxt >= 26 * 16) {
                prefetch_tmap(&p.ta[5]);
                prefetch_tmap(&p.tb[5]);
              }
              code = nxt;
            }
            tail = tail_item(code);
            if (tail == 0xFFFFu) rearm = cnt_done(NCTA * 2);
          }
        }
        if (rearm) cnt_rearm();
        TL(2, 0xFFFF);
      }
    }
  } else {
    CLUSTER_ARRIVE();
    reg_alloc<REG_C>();
    named_bar_sync(7, 288);
    const int warp = __shfl_sync(0xffffffffu, opaque_tid() >> 5, 0);
    const int wg = warp >> 2;
    const int lane = threadIdx.x & 31;
    TL_DECL;
    TR_DECL;
#ifdef TRACE
    if (tron) trp[trn] = (c_entry << 4) | 12;
    trn++;
    TRI(9, 13);
#endif
    named_bar_arrive_if(1, 256, wg == 1);
    uint32_t gphase = 0;
    uint32_t tail = 0, aswz = 0, rot = 0, stgpar = 1;
    const uint32_t etgt = warp & 1;
    int gi = 0;
    for (int seg = 0; seg < 2; seg++) {
      uint32_t item = p.g[cluster_id][gi++];
      if (item == 0x500u) item = tail;
      if (item < 0x600u) {
        float acc[128];
        uint32_t pk[64];
        int have = 0;
#define G_STORE_CHUNK(q)                                                                               \
  {                                                                                                    \
    const uint32_t st_base = sbase + OFF_STG + wg * 8192 + stg_off(opaque_tid());                      \
    if (have == 2) { _Pragma("unroll") for (int j = 0; j < 16; j++) pk[(q) * 16 + j] = scale_q(pk[(q) * 16 + j]); } \
    mbar_wait(s_bar + B_SEMPTY + 8 * (wg * 2 + ((q) & 1)), (((q) >> 1) & 1) ^ 1);                      \
    _Pragma("unroll") for (int j = 0; j < 4; j++)                                                      \
        stmatrix_x4((st_base ^ (j << 5)) + ((q) & 1) * 8192, pk[(q) * 16 + j * 4],                     \
                    pk[(q) * 16 + j * 4 + 1], pk[(q) * 16 + j * 4 + 2], pk[(q) * 16 + j * 4 + 3]);     \
    fence_proxy_async_smem();                                                                          \
    __syncwarp();                                                                                      \
    mbar_arrive_elect(s_bar + B_SFULL + 8 * (wg * 2 + ((q) & 1)), true);                              \
  }
#define G_STAGE(s) G_STAGE_Y(s, false, false, )
#define G_STAGE_X(s, ...) G_STAGE_Y(s, false, false, __VA_ARGS__)
#define G_STAGE_Y(s, first, last, ...)                                                                    \
  {                                                                                                       \
    mbar_wait_rest(s_bar + B_GFULL + 8 * (s), gphase, gok && (first));                                    \
    TR(9);                                                                                                \
    const uint32_t da = make_desc(DBASE + OFF_A + (((s) * 16384) ^ aswz) + wg * 8192, 16);                \
    const uint32_t db = make_desc(DBASE + ((s) ^ rot) * TILE32K, 8192);                                   \
    named_bar_sync_if(5 + wg, 256, !(first));                                                             \
    wgmma_fence();                                                                                        \
    _Pragma("unroll") for (int k = 0; k < 5; k++) {                                                       \
      __VA_ARGS__;                                                                                        \
      if (k == 0) wgmma_ss_n256_tbo<0, 0>(acc, da, db, !(first));                                         \
      if (k == 1) wgmma_ss_n256_tbo<2, 128>(acc, da, db, 1);                                              \
      if (k == 2) wgmma_ss_n256_tbo<4, 256>(acc, da, db, 1);                                              \
      if (k == 3) wgmma_ss_n256_tbo<6, 384>(acc, da, db, 1);                                              \
    }                                                                                                     \
    wgmma_commit();                                                                                       \
    named_bar_arrive_if(6 - wg, 256, !(wg ? (last) : (first)));                                           \
    if (!(first)) {                                                                                       \
      wgmma_wait<1>();                                                                                    \
      mbar_arrive_cluster_if(s_bar + B_GEMPTY + 8 * (((s) + 3) & 3), etgt, lane == 0 && (warp & 3) < 2);  \
    }                                                                                                     \
  }
        TL0(item);
        undef_regs(acc);
        {
          constexpr bool gok = false;
#ifdef TRE
          const uint32_t e0 = clock() - c_entry;
          mbar_wait(s_bar + B_GFULL, gphase);
          if (threadIdx.x == 0 && seg == 0) g_tr[16001 + 2 * blockIdx.x] = e0 | ((clock() - c_entry) << 16);
#endif
          G_STAGE_Y(0, true, false, )
        }
        if (seg == 0) CLUSTER_WAIT();
        undef_regs(pk);
        for (;;) {
          constexpr bool gok = false;
          const int nkb4 = prob_nkb4(item >> 8);
          const uint32_t next = p.g[cluster_id][gi++];
          G_STAGE(1)
          if (have) G_STORE_CHUNK(0)
          G_STAGE(2)
          G_STAGE(3)
          if (have) G_STORE_CHUNK(1)
          gphase ^= 1;
          G_STAGE(0)
          G_STAGE(1)
          if (have) G_STORE_CHUNK(2)
          G_STAGE(2)
          if (have) G_STORE_CHUNK(3)
          G_STAGE_Y(3, false, nkb4 == 2, )
          gphase ^= 1;
          int kb4 = 2;
          if (nkb4 == 16 && DO_LOCAL) {
            constexpr uint32_t aswz = 0, rot = 0;
            G_STAGE(0)
            G_STAGE(1)
            for (; kb4 < 10; kb4++) {
              float ls[36];
              TR(10);
              mbar_wait(s_bar + B_AFULL, kb4 & 1);
              TR(11);
              {
                const uint32_t dq = make_desc(DBASE + OFF_STG + wg * 64, 16);
                G_STAGE_X(2, if (k == 1) wgmma_ss_n72_init(ls, dq, dq + L_K / 16); if (k == 3) wgmma_ss_n72(ls, dq + 2, dq + L_K / 16 + 2, 1))
              }
              mbar_wait(s_bar + B_AFULL + 8, kb4 & 1);
              const int tid = opaque_tid();
              uint32_t vw[16];
              uint4 pw[8];
              {
                const uint32_t va = sbase + OFF_STG + L_V + ((tid >> 4) & 7) * 1024 + wg * 64 + (tid & 15) * 4;
#pragma unroll
                for (int j = 1; j < 16; j++) vw[j] = lds32((va ^ ((j & 7) << 4)) + j * 128);
              }
              G_STAGE(3)
              gphase ^= 1;
              fence_regs(ls);
              mbar_arrive_if(s_bar + B_AEMPTY, (threadIdx.x & 127) == 0);
              {
                const int d = (tid & 3) * 2 - ((tid >> 2) & 7);
                const bool p0 = d > 0, p1 = d >= 0;
                const int w = warp & 3;
                float x0, x1, y0, y1;
#define L_PICK(w_)                                   \
  {                                                  \
    x0 = p0 ? ls[8 * (w_)] : ls[8 * (w_) + 4];       \
    x1 = p1 ? ls[8 * (w_) + 1] : ls[8 * (w_) + 5];   \
    y0 = p0 ? ls[8 * (w_) + 6] : ls[8 * (w_) + 10];  \
    y1 = p1 ? ls[8 * (w_) + 7] : ls[8 * (w_) + 11];  \
  }
                if (w == 0) {
                  if (kb4 == 2 && blockIdx.x < 32) ls[0] = ls[1] = -INFINITY;
                  L_PICK(0)
                } else if (w == 1) L_PICK(1)
                else if (w == 2) L_PICK(2)
                else L_PICK(3)
                constexpr float C = 0.17677669529663687f * 1.4426950408889634f;
                float mx = fmaxf(x0, x1), my = fmaxf(y0, y1);
                mx = fmaxf(mx, __shfl_xor_sync(0xffffffffu, mx, 1));
                my = fmaxf(my, __shfl_xor_sync(0xffffffffu, my, 1));
                mx = -C * fmaxf(mx, __shfl_xor_sync(0xffffffffu, mx, 2));
                my = -C * fmaxf(my, __shfl_xor_sync(0xffffffffu, my, 2));
                x0 = ex2(fmaf(x0, C, mx));
                x1 = ex2(fmaf(x1, C, mx));
                y0 = ex2(fmaf(y0, C, my));
                y1 = ex2(fmaf(y1, C, my));
                float sx = x0 + x1, sy = y0 + y1;
                sx += __shfl_xor_sync(0xffffffffu, sx, 1);
                sy += __shfl_xor_sync(0xffffffffu, sy, 1);
                sx += __shfl_xor_sync(0xffffffffu, sx, 2);
                sy += __shfl_xor_sync(0xffffffffu, sy, 2);
                sx = rcp(sx);
                sy = rcp(sy);
                const uint32_t pa = sbase + OFF_STG + L_P + (tid >> 5) * 512 + (tid & 31) * 8;
                sts64(pa, x0 * sx, x1 * sx);
                sts64(pa + 256, y0 * sy, y1 * sy);
                __syncwarp();
              }
              const uint32_t pr = sbase + OFF_STG + L_P + (tid >> 4) * 256;
              uint32_t* dst = reinterpret_cast<uint32_t*>(p.ob) + (blockIdx.x & 15) * (SEQ * 32) + wg * 16 + (tid & 15) +
                              (((blockIdx.x >> 5) * 512 + (kb4 - 2) * 64 + ((tid >> 4) & 7) * 8) * 2 + ((blockIdx.x >> 4) & 1)) * 32;
#define L_PV(g0)                                                                                       \
  _Pragma("unroll") for (int g = (g0); g < (g0) + 4; g++) {                                            \
    const uint4 a = pw[2 * (g & 3)], b = pw[2 * (g & 3) + 1];                                          \
    const uint32_t w[8] = {a.x, a.y, a.z, a.w, b.x, b.y, b.z, b.w};                                    \
    float o0 = 0.f, o1 = 0.f;                                                                          \
    _Pragma("unroll") for (int c = 0; c < 8; c++) {                                                    \
      const uint32_t u = vw[c > g ? c : c + 8];                                                        \
      o0 = fmaf(__uint_as_float(w[c]), __uint_as_float(u << 16), o0);                                  \
      o1 = fmaf(__uint_as_float(w[c]), __uint_as_float(u & 0xFFFF0000u), o1);                          \
    }                                                                                                  \
    dst[g * 64] = pack_bf16(o0, o1);                                                                   \
  }
#pragma unroll
              for (int j = 0; j < 8; j++) pw[j] = lds128(pr + j * 16);
              mbar_arrive_elect(s_bar + B_AEMPTY + 8, true);
              G_STAGE(0)
              L_PV(0)
#pragma unroll
              for (int j = 0; j < 8; j++) pw[j] = lds128(pr + 128 + j * 16);
              G_STAGE(1)
              L_PV(4)
              __syncwarp();
              mbar_arrive_elect(s_bar + B_OFULL, true);
            }
            G_STAGE(2)
            G_STAGE(3)
            gphase ^= 1;
            kb4++;
          }
          const bool fin = next >= 0x600u;
          for (; kb4 < nkb4 - fin; kb4++) {
            G_STAGE(0)
            G_STAGE(1)
            G_STAGE(2)
            G_STAGE_Y(3, false, kb4 + 1 == nkb4, )
            gphase ^= 1;
          }
          if (fin) break;
          wgmma_wait<0>();
          mbar_arrive_cluster_if(s_bar + B_GEMPTY + 8 * 3, etgt, lane == 0 && (warp & 3) < 2);
          {
            const bool gok = mbar_test(s_bar + B_GFULL, gphase);
            fence_regs(acc);
#pragma unroll
            for (int j = 0; j < 64; j++) pk[j] = pack_bf16(acc[2 * j], acc[2 * j + 1]);
            have = item < 0x100u ? 2 : 1;
            item = next;
            TL0(item);
            G_STAGE_Y(0, true, false, )
          }
        }
        {
          constexpr bool gok = false;
          G_STAGE(0)
#if FS == 2
          G_STAGE(1)
#endif
          wgmma_wait<0>();
          mbar_arrive_cluster_if(s_bar + B_GEMPTY + 8 * (FS - 1), etgt, lane == 0 && (warp & 3) < 2);
          fence_regs(acc);
          float lo[64], hi[64];
#pragma unroll
          for (int j = 0; j < 64; j++) {
            asm volatile("mov.b32 %0, %1;" : "=f"(lo[j]) : "f"(acc[j]));
            asm volatile("mov.b32 %0, %1;" : "=f"(hi[j]) : "f"(acc[64 + j]));
          }
#pragma unroll
          for (int s = FS; s < 4; s++) {
            mbar_wait(s_bar + B_GFULL + 8 * s, gphase);
            const uint32_t da = make_desc(DBASE + OFF_A + ((s * 16384) ^ aswz) + wg * 8192, 16);
            const uint32_t db = make_desc(DBASE + (s ^ rot) * TILE32K, 8192);
            if (s == FS) named_bar_sync(5 + wg, 256);
            wgmma_fence();
            wgmma_ss_n128_tb<0, 0>(lo, da, db, 1);
            wgmma_ss_n128_tb<2, 128>(lo, da, db, 1);
            wgmma_ss_n128_tb<4, 256>(lo, da, db, 1);
            wgmma_ss_n128_tb<6, 384>(lo, da, db, 1);
            wgmma_commit();
          }
          wgmma_fence();
#pragma unroll
          for (int s = FS; s < 4; s++) {
            const uint32_t da = make_desc(DBASE + OFF_A + ((s * 16384) ^ aswz) + wg * 8192, 16);
            const uint32_t db = make_desc(DBASE + (s ^ rot) * TILE32K, 8192);
            wgmma_ss_n128_tb<0, 1024>(hi, da, db, 1);
            wgmma_ss_n128_tb<2, 1152>(hi, da, db, 1);
            wgmma_ss_n128_tb<4, 1280>(hi, da, db, 1);
            wgmma_ss_n128_tb<6, 1408>(hi, da, db, 1);
          }
          wgmma_commit();
          named_bar_arrive_if(6, 256, wg == 0);
          gphase ^= 1;
          const uint32_t so = sbase + stg_off(opaque_tid());
          mbar_wait(s_bar + B_STGFREE, stgpar);
          mbar_wait(s_bar + B_SEMPTY + 16 * wg, 1);
          mbar_wait(s_bar + B_SEMPTY + 16 * wg + 8, 1);
#define FIN_HALF(x, base, stride, bar, pub)                                                                                \
  fence_regs(x);                                                                                                      \
  _Pragma("unroll") for (int j = 0; j < 8; j++)                                                                       \
      stmatrix_x4(((base) ^ ((j & 3) << 5)) + (j >> 2) * (stride), pack_bf16(x[8 * j], x[8 * j + 1]),                 \
                  pack_bf16(x[8 * j + 2], x[8 * j + 3]), pack_bf16(x[8 * j + 4], x[8 * j + 5]), pack_bf16(x[8 * j + 6], x[8 * j + 7])); \
  if (pub) FIN_PUBLISH(bar)
#define FIN_PUBLISH(bar)                                   \
  {                                                        \
    fence_proxy_async_smem();                              \
    __syncwarp();                                          \
    mbar_arrive_elect(s_bar + (bar) + 16 * wg, true);      \
    mbar_arrive_elect(s_bar + (bar) + 16 * wg + 8, true);  \
  }
          wgmma_wait<1>();
          FIN_HALF(lo, so + OFF_STG + wg * 8192, 8192, B_SFULL, true)
          wgmma_wait<0>();
          TRI(12, 8);
#pragma unroll
          for (int s = FS; s < 4; s++) mbar_arrive_cluster_if(s_bar + B_GEMPTY + 8 * s, etgt, lane == 0 && (warp & 3) < 2);
          FIN_HALF(hi, so + OFF_A + (32768 ^ aswz), 16384, B_SFULL2, !(seg == 0 && isB && DO_ATT))
          TRI(12, 10);
        }
      }
#ifdef ATT_ONLY
      if (seg == 0) CLUSTER_WAIT();
#endif
      if (seg == 0 && isB && DO_ATT) {
        float o[64], s[64];
        uint32_t pa[32], pb[32];
        undef_regs(o);
        undef_regs(s);
        undef_regs(pa);
        undef_regs(pb);
        uint32_t phase = 0;
        const bool sig = (threadIdx.x & 127) == 0, sig2 = (threadIdx.x & 95) == 0;
#ifndef ATT_ONLY
        FIN_PUBLISH(B_SFULL2)
#endif

#define ISSUE_PV(pr, slot_)                                                             \
  {                                                                                     \
    const uint32_t dv = make_desc(DBASE + (slot_) * TILE32K, 16384);                    \
    if (!phalf) {                                                                       \
      wgmma_fence();                                                                    \
      _Pragma("unroll") for (int k = 0; k < 8; k++)                                     \
          wgmma_rs_n128_tb(o, pr[4 * k], pr[4 * k + 1], pr[4 * k + 2], pr[4 * k + 3], dv + k * 128, (k != 0) || !pfirst); \
      wgmma_commit();                                                                   \
    } else {                                                                            \
      wgmma_fence();                                                                    \
      _Pragma("unroll") for (int k = 0; k < 4; k++)                                     \
          wgmma_rs_n128_tb(o, pr[16 + 4 * k], pr[17 + 4 * k], pr[18 + 4 * k], pr[19 + 4 * k], dv + k * 128, (k != 0) || !pfirst); \
      wgmma_commit();                                                                   \
    }                                                                                   \
  }
#define EPILOGUE(on_)                                                                             \
  _Pragma("unroll") for (int j = 0; j < 8; j++) {                                                 \
    const int b = j * 8;                                                                          \
    stmatrix_x4_p((st_o ^ ((j & 3) << 5)) + (j >> 2) * 16384,                                     \
                  pack_bf16(o[b] * sc0, o[b + 1] * sc0), pack_bf16(o[b + 2] * sc1, o[b + 3] * sc1),   \
                  pack_bf16(o[b + 4] * sc0, o[b + 5] * sc0), pack_bf16(o[b + 6] * sc1, o[b + 7] * sc1), on_); \
  }
#define PUBLISH_O()                                  \
  {                                                  \
    fence_proxy_async_smem();                        \
    __syncwarp();                                    \
    mbar_arrive_elect(s_bar + B_OFULL, true);        \
  }
#define FINAL_SCALE()     \
  {                                                    \
    sc0 = t0 + __shfl_xor_sync(0xffffffffu, t0, 1);    \
    sc1 = t1 + __shfl_xor_sync(0xffffffffu, t1, 1);    \
    t0 = t1 = 0.f;                                     \
    sc0 += __shfl_xor_sync(0xffffffffu, sc0, 2);       \
    sc1 += __shfl_xor_sync(0xffffffffu, sc1, 2);       \
    sc0 = rcp(sc0);            \
    sc1 = rcp(sc1);                                    \
  }
        float l0 = 1.f, l1 = 1.f, t0 = 1.f, t1 = 1.f;
        float b0 = 0.f, b1 = 0.f, sc0 = 0.f, sc1 = 0.f;
        int gen = 0;
        int pfirst = 1;
        int phalf = 2;
        int fresh = 1;
        int diag = blockIdx.x & 1, dlast = !diag;
        int opub = 0;
        int last = 0;
        float rdy;
        float x0 = 0.f, x1 = 0.f, x2 = 0.f, x3 = 0.f;
        bool rs = false;
        uint32_t code = p.order[cluster_id - NA_CL];
        int it = 0, nit = 0, rem = (code & 15) + dlast;
        TL0(0x1000 | code | rem);
        const float mrow = float((warp & 3) * 16 + (lane >> 2) - (lane & 3) * 2);
        const float lo0 = mrow < 0.f && wg == HW ? 0.f : SM_LO;
        const uint32_t st_o = sbase + OFF_STG + stg_off(opaque_tid() ^ (HW * 128));
#define MMA_PART(N_, acc_, PIN, PAR)                                                                       \
  {                                                                                                        \
    const uint32_t dq = make_desc(DBASE + OFF_A + (it & 1) * TILE32K + (wg ^ HW) * 8192, 16);              \
    const uint32_t dk = make_desc(DBASE + (PAR) * TILE32K, 16);                                            \
    TRI(0, fresh ? 7 : 0);                                                                                 \
    named_bar_sync(1 + wg, 256);                                                                           \
    TRI(1, fresh ? 6 : 1);                                                                                 \
    wgmma_fence();                                                                                         \
    uint32_t cv;                                                                                           \
    bool rv;                                                                                               \
    _Pragma("unroll") for (int k = 0; k < 8; k++) {                                                        \
      wgmma_ss_n##N_(acc_, dq + (k >> 2) * 1024 + (k & 3) * 2, dk + (k >> 2) * 1024 + (k & 3) * 2, k != 0); \
      if (k == 1) cv = lds32(s_bar + S_CODE + 4 * ((it + 1) & 7));        \
      if (k == 3) rv = mbar_test(s_bar + B_AFULL + 8 * (3 - (PAR)), phase ^ (1 - (PAR)));                  \
    }                                                                                                      \
    wgmma_commit();                                                                                        \
    code = __reduce_or_sync(0xffffffffu, cv);                                                              \
    if (opub) PUBLISH_O();                                                                                 \
    if (N_ == 128 && fresh) FINAL_SCALE();                                                                 \
    last = rem == 0 && (code & 0x8000u);                                                                   \
    nit = it + (rem == 0 && !last);                                                                        \
    mbar_wait_rest(s_bar + B_AFULL + 8 * (3 - (PAR)), phase ^ (1 - (PAR)), rv);                            \
    ISSUE_PV(PIN, 3 - (PAR));                                                                              \
    named_bar_arrive(2 - wg, 256);                                                                         \
    TR(2);                                                                                                 \
    wgmma_wait<1>();                                                                                       \
    fence_regs(acc_);                                                                                      \
    TR(3);                                                                                                 \
    mbar_arrive_cluster_if(s_bar + B_AEMPTY + 8 * (PAR), etgt, sig2);                                      \
    mbar_arrive_if(s_bar + B_QEMPTY + 8 * (it & 1), sig && rem == 0);                                      \
    if (N_ == 64 && fresh) FINAL_SCALE();                                                                  \
    l0 = t0;                                                                                               \
    l1 = t1;                                                                                               \
  }
#define LOW_SUM() ((t0 < lo0) | (t1 < SM_LO))
#define SECOND_HALF(POUT, PAR, FRESH, ...)                                                                 \
  wgmma_wait<0>();                                                                                         \
  fence_regs(o);                                                                                           \
  mbar_arrive_cluster_if(s_bar + B_AEMPTY + 8 * (3 - (PAR)), etgt, sig2 && ((PAR) || !(FRESH) || it > 0)); \
  TR(8);                                                                                                   \
  __VA_ARGS__;                                                                                             \
  t0 += x0 + x1;                                                                                           \
  t1 += x2 + x3;                                                                                           \
  POUT[16] = pack_bf16(x0, x1);                                                                            \
  POUT[17] = pack_bf16(x2, x3);                                                                            \
  softmax_exp<9, ZPOS, false>(s, 0.f, 0.f, POUT, t0, t1);                                                  \
  {                                                                                                        \
           \
    const uint32_t z = (__float_as_uint(t0) | __float_as_uint(t1)) >> 31;                                  \
    rdy = mbar_test2(s_bar + B_AFULL + 8 * (1 - (PAR)), (phase ^ (PAR)) + z, s_bar + B_QFULL + 8 * (nit & 1), ((nit >> 1) & 1) + z); \
  }                                                                                                        \
  softmax_exp<ZPOS, TPOS, false>(s, 0.f, 0.f, POUT, t0, t1);                                               \
  t0 = addv(t0, rdy);                                                                                      \
  softmax_exp<TPOS, 16, false>(s, 0.f, 0.f, POUT, t0, t1);                                                 \
                                                                                \
  phalf = diag && wg == HW;                                                                                \
  opub = (FRESH) && it > 0;                                                                                \
  pfirst = FRESH;                                                                                          \
  fresh = rem == 0;                                                                                        \
  it = nit;                                                                                                \
  rem = fresh ? (code & 15) + ((blockIdx.x ^ ~it) & 1) : rem - 1;                                          \
  dlast = !((blockIdx.x | it) & 1);                                                                        \
  diag = dlast ? rem == 0 : fresh;                                                                         \
  if (fresh && !last) { TL0(0x1000 | code | rem); }                                                        \
  if (PAR) phase ^= 1;                                                                                     \
                                                      \
  const float lim = __uint_as_float(__float_as_uint(last ? -1.f : SM_HI) | __float_as_uint(rdy));   \
  TR(4);
#ifndef TPOS
#define TPOS 15
#define ZPOS 13
#endif
#define TEST_STG() rs = mbar_test(s_bar + B_STGFREE, ~it & 1) | (it == 0);
#define SHIFT_S(j0_)                                                                                       \
  if (gen) { _Pragma("unroll") for (int j = (j0_); j < 64; j++) s[j] += (j & 2) ? b1 : b0; }
#define NEXT_STEP(NEXT, LOW)                                                                               \
  if (!__any_sync(0xffffffffu, !(t0 + t1 <= (diag && wg == HW ? -1.f : lim)) | (LOW))) goto plain##NEXT;   \
  if (!__any_sync(0xffffffffu, !(t0 + t1 <= lim) | (LOW))) goto half##NEXT;
#define STEP_END(POUT, PAR, NEXT, ...)                                                                     \
  if (fresh) {                                                                                             \
    __VA_ARGS__;                                                                                           \
    mbar_wait_rest(s_bar + B_STGFREE, ~it & 1, rs);                                                        \
    SECOND_HALF(POUT, PAR, 1, EPILOGUE(it > 0))                                                            \
    if (phalf && opub) {                                                     \
      PUBLISH_O();                                                                                         \
      opub = 0;                                                                                            \
    }                                                                                                      \
    NEXT_STEP(NEXT, LOW_SUM())                                                                             \
  } else {                                                                                                 \
    SECOND_HALF(POUT, PAR, 0, )                                                                            \
    NEXT_STEP(NEXT, false)                                                                                 \
  }
#define STEP_BEGIN(PIN, POUT, PAR, ...)                                                                    \
  {                                                                                                        \
    if (__any_sync(0xffffffffu, !(t0 + t1 <= SM_HI) | (LOW_SUM() & (pfirst != 0)))) {                           \
              \
      if (phalf) { _Pragma("unroll") for (int j = 0; j < 32; j++) asm volatile("mov.b32 %0, 0xff800000;" : "=f"(s[j])); } \
      float d0, d1;                                                                                        \
      softmax_max(s, d0, d1);                                                                              \
      if (!pfirst) {                                                                                       \
        d0 = fmaxf(d0, 0.f);                                                                               \
        d1 = fmaxf(d1, 0.f);                                                                               \
      }                                                                                                    \
      const float r0 = pfirst ? 1.f : ex2(-d0), r1 = pfirst ? 1.f : ex2(-d1);                              \
      t0 = l0 * r0;                                                                                        \
      t1 = l1 * r1;                                                                                        \
      softmax_exp<0, 16, true>(s, -d0, -d1, PIN, t0, t1);                                                  \
      b0 -= d0;                                                                                            \
      b1 -= d1;                                                                                            \
      gen = 1;                                                                                             \
      _Pragma("unroll") for (int j = 0; j < 16; j++) {                                                     \
        o[4 * j] *= r0;                                                                                    \
        o[4 * j + 1] *= r0;                                                                                \
        o[4 * j + 2] *= r1;                                                                                \
        o[4 * j + 3] *= r1;                                                                                \
      }                                                                                                    \
    }                                                                                                      \
    if (last) {                                                                                            \
      __VA_ARGS__;                                                                                         \
      break;                                                                                               \
    }                                                                                                      \
  }                                                                                                        \
  inputs##PAR:                                                                                             \
  {                                                                                                        \
    const bool rq = mbar_test(s_bar + B_QFULL + 8 * (it & 1), (it >> 1) & 1);                              \
    mbar_wait(s_bar + B_AFULL + 8 * (PAR), phase);                                                         \
    mbar_wait_rest(s_bar + B_QFULL + 8 * (it & 1), (it >> 1) & 1, rq);                                     \
  }                                                                                                        \
  if (diag && wg == HW) {                                                                                  \
  half##PAR:                                                                                               \
                                                     \
    float sl[32];                                                                                          \
    undef_regs(sl);                                                                                        \
    MMA_PART(64, sl, PIN, PAR)                                                                             \
    _Pragma("unroll") for (int j = 0; j < 32; j++) asm volatile("mov.b32 %0, %1;" : "=f"(s[32 + j]) : "f"(sl[j])); \
    SHIFT_S(32)                                                                                            \
    TEST_STG()                                                                                             \
    _Pragma("unroll") for (int j = 0; j < 8; j++) {                                                        \
      if (float(8 * j) > mrow) s[32 + 4 * j] = -3e38f;                                                     \
      if (float(8 * j + 1) > mrow) s[33 + 4 * j] = -3e38f;                                                 \
      if (float(8 * j - 8) > mrow) s[34 + 4 * j] = -3e38f;                                                 \
      if (float(8 * j - 7) > mrow) s[35 + 4 * j] = -3e38f;                                                 \
    }                                                                                                      \
    x0 = ex2v(s[32]), x1 = ex2v(s[33]), x2 = ex2v(s[34]), x3 = ex2v(s[35]);                                \
  } else {                                                                                                 \
  plain##PAR:                                                                                              \
    MMA_PART(128, s, PIN, PAR)                                                                             \
    if (diag || gen) {                                                                                     \
      SHIFT_S(0)                                                                                           \
                                     \
      TEST_STG()                                                                                           \
      const float rowf = diag ? mrow : 64.f;                                                               \
      _Pragma("unroll") for (int j = 0; j < 8; j++) {                                                      \
        s[32 + 4 * j] = fmaf(__saturatef(float(8 * j) - rowf), -3e38f, s[32 + 4 * j]);                     \
        s[33 + 4 * j] = fmaf(__saturatef(float(8 * j + 1) - rowf), -3e38f, s[33 + 4 * j]);                 \
        s[34 + 4 * j] = fmaf(__saturatef(float(8 * j - 8) - rowf), -3e38f, s[34 + 4 * j]);                 \
        s[35 + 4 * j] = fmaf(__saturatef(float(8 * j - 7) - rowf), -3e38f, s[35 + 4 * j]);                 \
      }                                                                                                    \
      softmax_exp<0, 8, false>(s, 0.f, 0.f, POUT, t0, t1);                                                 \
      x0 = ex2v(s[32]), x1 = ex2v(s[33]), x2 = ex2v(s[34]), x3 = ex2v(s[35]);                              \
    } else {                                                                                               \
      TEST_STG()                                                                                           \
      softmax_exp<0, 8, false>(s, 0.f, 0.f, POUT, t0, t1);                                                 \
      x0 = ex2v(s[32]), x1 = ex2v(s[33]), x2 = ex2v(s[34]), x3 = ex2v(s[35]);                              \
    }                                                                                                      \
  }
        for (;;) {
          STEP_END(pa, 1, 0, if (phalf == 2) { wgmma_wait<0>(); goto inputs0; })
          STEP_BEGIN(pa, pb, 0, rot = 0; phase ^= 1)
          STEP_END(pb, 0, 1, )
          STEP_BEGIN(pb, pa, 1, rot = 1; _Pragma("unroll") for (int j = 0; j < 32; j++) asm volatile("mov.b32 %0, %1;" : "=r"(pa[j]) : "r"(pb[j])))
        }
        {
          mbar_wait(s_bar + B_AFULL + 8 * (3 - rot), phase);
          TRI(12, 2);
          ISSUE_PV(pa, 3 - rot);
          if (opub) PUBLISH_O();
          FINAL_SCALE();
          mbar_wait(s_bar + B_STGFREE, it & 1);
          wgmma_wait<0>();
          fence_regs(o);
          TRI(12, 4);
          mbar_arrive_cluster_if(s_bar + B_AEMPTY + 8 * (3 - rot), etgt, sig2);
          EPILOGUE(true);
          PUBLISH_O();
          TRI(12, 5);
          stgpar = ~it & 1;
          tail = tail_item(code);
          aswz = (~it & 1) * TILE32K;
          rot ^= blockIdx.x & ~it & 1;
        }
      }
    }
    TL0(0xFFFF);
    TRI(15, 15);
  }
}

typedef CUresult (*EncodeFn)(CUtensorMap*, CUtensorMapDataType, cuuint32_t, void*, const cuuint64_t*,
                             const cuuint64_t*, const cuuint32_t*, const cuuint32_t*, CUtensorMapInterleave,
                             CUtensorMapSwizzle, CUtensorMapL2promotion, CUtensorMapFloatOOBfill);

EncodeFn get_encode() {
  static EncodeFn fn = nullptr;
  if (!fn) {
    void* p = nullptr;
    cudaDriverEntryPointQueryResult st;
    cudaGetDriverEntryPoint("cuTensorMapEncodeTiled", &p, cudaEnableDefault, &st);
    fn = (EncodeFn)p;
  }
  return fn;
}

void make_map(CUtensorMap* m, const void* ptr, int rows, int cols, int box_rows, int box_groups, bool blocked = false) {
  cuuint64_t dims[3] = {64, (cuuint64_t)rows, (cuuint64_t)(cols / 64)};
  cuuint64_t strides[2] = {(cuuint64_t)(blocked ? 128 : cols * 2), (cuuint64_t)(blocked ? rows * 128 : 128)};
  cuuint32_t box[3] = {64, (cuuint32_t)box_rows, (cuuint32_t)box_groups};
  cuuint32_t es[3] = {1, 1, 1};
  CUtensorMapL2promotion prom = blocked || box_groups == 1 ? CU_TENSOR_MAP_L2_PROMOTION_NONE : CU_TENSOR_MAP_L2_PROMOTION_L2_256B;
  get_encode()(m, CU_TENSOR_MAP_DATA_TYPE_BFLOAT16, 3, const_cast<void*>(ptr), dims, strides, box, es,
               CU_TENSOR_MAP_INTERLEAVE_NONE, CU_TENSOR_MAP_SWIZZLE_128B, prom,
               CU_TENSOR_MAP_FLOAT_OOB_FILL_NONE);
}

void make_store_map(CUtensorMap* m, const void* ptr, int cols, uint64_t s_par, uint64_t s_pair, uint64_t s_grp) {
  cuuint64_t dims[4] = {64, 2, SEQ / 2, (cuuint64_t)(cols / 64)};
  cuuint64_t strides[3] = {s_par, s_pair, s_grp};
  cuuint32_t box[4] = {64, 2, 32, 1};
  cuuint32_t es[4] = {1, 1, 1, 1};
  get_encode()(m, CU_TENSOR_MAP_DATA_TYPE_BFLOAT16, 4, const_cast<void*>(ptr), dims, strides, box, es,
               CU_TENSOR_MAP_INTERLEAVE_NONE, CU_TENSOR_MAP_SWIZZLE_128B, CU_TENSOR_MAP_L2_PROMOTION_NONE,
               CU_TENSOR_MAP_FLOAT_OOB_FILL_NONE);
}

#ifdef SCHED_PRINT
static int envi(const char* n, int d) { const char* e = getenv(n); return e ? (int)strtol(e, 0, 0) : d; }
#define PARAM(name, val) const int name = envi(#name, val)
#else
#define PARAM(name, val) const int name = val
#endif
void build_schedule(Params& p) {
  PARAM(C_KB, 1028);
  PARAM(C_TILE, 10);
  PARAM(C_QX, 0);
  PARAM(C_START, 4500);
  PARAM(C_STEP, 2052);
  PARAM(C_ITEM, 300);
  PARAM(C_LAG, 8000);
  PARAM(C_SP, 5200);
  PARAM(C_TAIL, 22000);
  PARAM(C_SHORT, 0);
  PARAM(C_AT, 72);
  PARAM(C_LATE, 0);
  PARAM(C_LMASK, 0xAA0);
  PARAM(C_AM, 100);
  PARAM(C_ODD, 1300);
  PARAM(C_READY, 10000);
  auto gemm_cost = [&](int prob) {
    static const int nkb[NPROB] = {16, 8, 8, 16, 64, 16};
    return nkb[prob] * C_KB + C_TILE + (prob == 0 ? C_QX : 0);
  };
  memset(p.g, 0xFF, sizeof(p.g));
  int n1[NCLUSTER];
  long t1[NCLUSTER];
  long ready[16];
  for (int c = 0; c < NCLUSTER; c++) { n1[c] = 0; t1[c] = C_START; }
  for (int i = 0; i < 16; i++) ready[i] = 0;
  auto add = [&](int c, int prob, int mp, int nt) {
    p.g[c][n1[c]++] = (uint16_t)((prob << 8) | (mp << 4) | nt);
    t1[c] += gemm_cost(prob);
    if (prob < 3) {
      const long r = t1[c] + C_READY;
      if (r > ready[nt]) ready[nt] = r;
    }
  };
#ifdef GEMM_ONLY
  for (int c = 0; c < NCLUSTER; c++) {
    for (int i = 0; i < 13; i++) add(c, 0, c & 7, (i + (c >> 3) * 2) & 15);
    p.g[c][n1[c]++] = 0x600;
  }
  return;
#endif
#ifdef ATT_ONLY
  for (int c = 0; c < NCLUSTER; c++) { p.g[c][0] = 0x600; p.g[c][1] = 0x500; }
  for (int i = 0; i < 256; i++) p.order[i] = (uint16_t)(((i & 31) << 4) | (14 - 2 * (i >> 5)));
  return;
#endif
  for (int r = 0; r < 8; r++)
    for (int c = 0; c < NA_CL; c++) {
      const int mp = c & 7, nt = 2 * r + ((c >> 3) & 1);
      for (int j = 0; j < (c < 16 ? 1 : 2); j++) {
        add(c, c < 16 ? 0 : 1 + j, mp, nt);
      }
    }
  long tA = 0;
  for (int c = 0; c < NA_CL; c++) {
    if (t1[c] > tA) tA = t1[c];
    add(c, 4, c & 7, c >> 3);
  }
  for (int r = 0; r < 3; r++)
    for (int j = 0; j < 34; j++) {
      if (j >= 32) { if (r < 2) add(NA_CL + j, 3, j & 7, 4 + r); }
      else if (r < 2 || j >= 16 || (j & 7) >= 2) add(NA_CL + j, 3, j & 7, (j >> 3) + (r == 0 ? 0 : r == 1 ? 8 : 4));
    }
  for (int c = NA_CL; c < NCLUSTER; c++) {
    p.g[c][n1[c]++] = 0x600;
    p.g[c][n1[c]++] = 0x500;
  }
  static const uint16_t order[256] = {
    14, 30, 10, 44, 26, 78, 60, 94, 12, 46, 8, 42, 24, 76, 58, 110, 92, 6, 126, 40, 22, 74, 56, 108,
    90, 4, 124, 38, 20, 72, 54, 106, 28, 62, 142, 158, 88, 2, 140, 122, 36, 18, 174, 156, 70, 52, 190, 104,
    86, 0, 138, 120, 34, 16, 172, 154, 68, 50, 206, 188, 102, 84, 222, 136, 118, 32, 170, 152, 66, 48, 204, 186,
    100, 82, 238, 220, 134, 116, 254, 168, 150, 64, 202, 184, 98, 80, 236, 218, 132, 114, 270, 252, 166, 148, 286, 200,
    182, 96, 234, 216, 130, 112, 268, 250, 164, 146, 302, 284, 198, 180, 318, 232, 214, 128, 266, 248, 162, 144, 300, 282,
    196, 178, 334, 316, 230, 212, 350, 264, 246, 160, 310, 328, 382, 194, 314, 360, 192, 340, 278, 298, 274, 208, 342, 366,
    210, 260, 290, 312, 336, 378, 306, 292, 240, 330, 364, 224, 228, 346, 380, 434, 376, 244, 362, 226, 344, 348, 408, 272,
    304, 176, 320, 368, 280, 412, 390, 332, 262, 288, 258, 256, 242, 402, 294, 388, 422, 296, 406, 398, 384, 374, 326, 352,
    400, 414, 394, 276, 322, 418, 392, 396, 370, 356, 324, 410, 386, 430, 462, 494, 446, 510, 478, 484, 482, 354, 498, 404,
    308, 416, 428, 492, 508, 460, 476, 444, 452, 358, 426, 372, 490, 506, 458, 442, 474, 338, 424, 472, 456, 440, 488, 454,
    450, 438, 470, 486, 420, 436, 468, 500, 504, 466, 502, 448, 496, 432, 480, 464,
  };
  memcpy(p.order, order, sizeof(order));
#ifdef SCHED_PRINT
  uint16_t fixed[256];
  memcpy(fixed, p.order, sizeof(fixed));
  long tf[NB_CL];
  bool done[512], started[NB_CL];
  long fin[16];
  int cnt[NB_CL] = {};
  for (int c = 0; c < NB_CL; c++) { tf[c] = t1[NA_CL + c] + 2000; started[c] = false; }
  for (int i = 0; i < 512; i++) done[i] = i & 1;
  for (int i = 0; i < 16; i++) fin[i] = 0;
  auto alen = [&](int qt) { return (long)(2 * qt + 3) * C_STEP / 2 + C_ITEM + (qt < 2 ? C_SHORT : 0); };
  int nq = NB_CL;
  for (int n = 0; n < 256; n++) {
    int cb = 0;
    for (int c = 1; c < NB_CL; c++)
      if (tf[c] < tf[cb]) cb = c;
    int best = -1;
    long bkey = 0;
    for (int i = 0; i < 512; i++) {
      if (done[i]) continue;
      const int hp = i >> 5;
      long dl = -(long)(16 - hp) * C_SP - C_LAG + ((i >> 4) & 1) * C_ODD;
      if (dl > -C_TAIL) dl = -C_TAIL;
      long key = dl - alen(i & 15) * (dl == -C_TAIL ? C_AT : C_AM) / 100;
      if ((i >> 4) == 31 && (C_LMASK >> (i & 15) & 1)) key += C_LATE;
      if (ready[hp] > tf[cb]) key += (1L << 40) + (ready[hp] - tf[cb]) * 1024;
      if (best < 0 || key < bkey) { best = i; bkey = key; }
    }
    done[best] = true;
    if (!started[cb]) { p.order[cb] = (uint16_t)best; started[cb] = true; }
    else p.order[nq++] = (uint16_t)best;
    if (ready[best >> 5] > tf[cb]) tf[cb] = ready[best >> 5];
    tf[cb] += alen(best & 15) + (cnt[cb]++ & 1 ? -C_STEP / 2 : C_STEP / 2);
    if (tf[cb] + C_LAG > fin[best >> 5]) fin[best >> 5] = tf[cb] + C_LAG;
  }
  if (!getenv("HEUR")) memcpy(p.order, fixed, sizeof(fixed));
#endif
#ifdef SCHED_PRINT
  ord_hook(p.order);
  long t = tA, tmin = tf[0], tmax = tf[0];
  printf("sched: outA start %ld, fin:", t);
  for (int hp = 0; hp < 16; hp++) {
    printf(" %ld", fin[hp] - t);
    if (fin[hp] > t) t = fin[hp];
    t += 4 * C_KB;
  }
  for (int c = 0; c < NB_CL; c++) { if (tf[c] < tmin) tmin = tf[c]; if (tf[c] > tmax) tmax = tf[c]; }
  printf("\nA end %ld, attention end %ld..%ld (+%d), ready[15] %ld nq %d\n", t, tmin, tmax, gemm_cost(5), ready[15], nq);
#endif
}

}

extern "C" void kernel_launch(void* const* d_in, const int* in_sizes, int n_in, void* d_out, int out_size) {
  const bf16* A_x = (const bf16*)d_in[0];
  const bf16* A_c = (const bf16*)d_in[1];
  const bf16* A_wq = (const bf16*)d_in[2];
  const bf16* A_wuk = (const bf16*)d_in[3];
  const bf16* A_wuv = (const bf16*)d_in[4];
  const bf16* A_wo = (const bf16*)d_in[5];
  const bf16* B_x = (const bf16*)d_in[6];
  const bf16* B_wqkv = (const bf16*)d_in[7];
  const bf16* B_wo = (const bf16*)d_in[8];
  bf16* out = (bf16*)d_out;

  static Params p;
  static bf16 *q, *k, *v, *ctx, *qkvb, *ob;
  static bool init = false;
  if (!init) {
    cudaGetSymbolAddress((void**)&q, g_q);
    cudaGetSymbolAddress((void**)&k, g_k);
    cudaGetSymbolAddress((void**)&v, g_v);
    cudaGetSymbolAddress((void**)&qkvb, g_qkvb);
    cudaGetSymbolAddress((void**)&ob, g_ob);
    cudaFuncSetAttribute(mega_kernel, cudaFuncAttributeMaxDynamicSharedMemorySize, SMEM_BYTES);
    build_schedule(p);
    ctx = q;
    init = true;
  }
  make_map(&p.ta[0], A_x, SEQ, DM, 128, 1);
  make_map(&p.tb[0], A_wq, DM, HHD, 64, 2);
  make_store_map(&p.tc[0], q, HHD, 128, 256, SEQ * 128);
  make_map(&p.ta[1], A_c, SEQ, DC, 128, 1);
  make_map(&p.tb[1], A_wuk, DC, HHD, 64, 2);
  make_store_map(&p.tc[1], k, HHD, 128, 256, SEQ * 128);
  make_map(&p.ta[2], A_c, SEQ, DC, 128, 1);
  make_map(&p.tb[2], A_wuv, DC, HHD, 64, 2);
  make_store_map(&p.tc[2], v, HHD, 128, 256, SEQ * 128);
  make_map(&p.ta[3], B_x, SEQ, DM, 128, 1);
  make_map(&p.tb[3], B_wqkv, DM, 3 * DM, 64, 2);
  make_store_map(&p.tc[3], qkvb, 3 * DM, SEQ * 64, 128, SEQ * 128);
  make_map(&p.ta[4], ctx, SEQ, HHD, 128, 1, true);
  make_map(&p.tb[4], A_wo, HHD, DM, 64, 2);
  make_store_map(&p.tc[4], out, 2 * DM, 4 * DM, 8 * DM, 128);
  make_map(&p.ta[5], ob, SEQ, DM, 128, 1, true);
  make_map(&p.tb[5], B_wo, DM, DM, 64, 2);
  make_store_map(&p.tc[5], out, 2 * DM, 4 * DM, 8 * DM, 128);
  make_map(&p.tq, q, SEQ, HHD, 128, 2, true);
  make_map(&p.tk, k, SEQ, HHD, 128, 1, true);
  make_map(&p.tv, v, SEQ, HHD, 128, 1, true);
  make_map(&p.tl, qkvb, SEQ / 2, 6 * DM, 64, 1, true);
  make_map(&p.th, qkvb, SEQ / 2, 6 * DM, 72, 1, true);
  p.ob = ob;
  mega_kernel<<<NCTA, 384, SMEM_BYTES, cudaStreamPerThread>>>(p);
}
```
